```python
import torch

def _softmax(x, axis=-1):
    return torch.softmax(x, dim=axis)

def _gelu(x):
    return torch.nn.functional.gelu(x, approximate='tanh')

def _silu(x):
    return torch.nn.functional.silu(x)

def _sigmoid(x):
    return torch.sigmoid(x)

def _layernorm(x, axis=-1, eps=1e-05):
    m = x.mean(dim=axis, keepdim=True)
    v = x.var(dim=axis, keepdim=True, unbiased=False)
    return (x - m) / torch.sqrt(v + eps)

def _scatter_add(tgt, idx, src, axis=0):
    return tgt.clone().index_add_(axis, idx, src)

def _segment_sum(src, seg, n):
    out = torch.zeros((n,) + src.shape[1:], dtype=src.dtype)
    return out.index_add_(0, seg, src)

def _pad(x, pw):
    flat = tuple((v for pair in reversed(pw) for v in pair))
    return torch.nn.functional.pad(x, flat)
kernel_name = 'concat_heads__memory_aug_recurrent_mem_tr__ssm_conv_h3__prompt'

def setup_inputs():

    _w = lambda a: (lambda t: t.to(torch.bfloat16) if t.is_floating_point() else t)(torch.as_tensor(a))

    def _A_setup():
        B, S, Dm = (1, 2048, 1024)
        H, Dh = (32, 128)
        M, seg = (8, 32)
        seg = min(seg, S)
        S = S // seg * seg
        return {'x': _w((lambda *s: torch.randn(*s, dtype=torch.bfloat16) * 0.05)(B, S, Dm)), 'mem0': _w((lambda *s: torch.randn(*s, dtype=torch.bfloat16) * 0.4)(B, M, Dm)), 'Wq': _w((lambda *s: torch.randn(*s, dtype=torch.bfloat16) * 6.4)(Dm, H, Dh) * Dm ** (-0.5)), 'Wk': _w((lambda *s: torch.randn(*s, dtype=torch.bfloat16) * 6.4)(Dm, H, Dh) * Dm ** (-0.5)), 'Wv': _w((lambda *s: torch.randn(*s, dtype=torch.bfloat16) * 0.4)(Dm, H, Dh) * Dm ** (-0.5)), 'Wo': _w((lambda *s: torch.randn(*s, dtype=torch.bfloat16) * 0.4)(H, Dh, Dm) * (H * Dh) ** (-0.5)), 'seg_len': seg}
    _A_in = _A_setup()

    def _B_setup():
        B, S, D = (1, 2048, 1024)
        ks = 4
        return {'q': _w((lambda *s: torch.randn(*s, dtype=torch.bfloat16) * 0.05)(B, S, D)), 'k': _w((lambda *s: torch.randn(*s, dtype=torch.bfloat16) * 0.4)(B, S, D)), 'v': _w((lambda *s: torch.randn(*s, dtype=torch.bfloat16) * 0.4)(B, S, D)), 'shift_k': _w((lambda *s: torch.randn(*s, dtype=torch.bfloat16) * 0.4)(D, ks) * 0.5), 'ssm_k': _w((lambda *s: torch.randn(*s, dtype=torch.bfloat16) * 0.4)(D, S) * (1.0 / S ** 0.5)), 'ssm_D': _w((lambda *s: torch.randn(*s, dtype=torch.bfloat16) * 0.4)(D))}
    _B_in = _B_setup()
    return {'A_x': _A_in['x'], 'A_mem0': _A_in['mem0'], 'A_Wq': _A_in['Wq'], 'A_Wk': _A_in['Wk'], 'A_Wv': _A_in['Wv'], 'A_Wo': _A_in['Wo'], 'A_seg_len': _A_in['seg_len'], 'B_q': _B_in['q'], 'B_k': _B_in['k'], 'B_v': _B_in['v'], 'B_shift_k': _B_in['shift_k'], 'B_ssm_k': _B_in['ssm_k'], 'B_ssm_D': _B_in['ssm_D']}

def reference(A_x, A_mem0, A_Wq, A_Wk, A_Wv, A_Wo, A_seg_len, B_q, B_k, B_v, B_shift_k, B_ssm_k, B_ssm_D):

    def _A_ref(x, mem0, Wq, Wk, Wv, Wo, seg_len):
        B, S, Dm = x.shape
        H, Dh = (Wq.shape[1], Wq.shape[2])
        M = mem0.shape[1]
        scale = Dh ** (-0.5)
        n_seg = S // seg_len
        L = M + seg_len
        idx = torch.arange(L)
        mask = (idx[:, None] < M) | (idx[:, None] >= idx[None, :])
        mem = mem0
        outs = []
        for s in range(n_seg):
            xs = x[:, s * seg_len:(s + 1) * seg_len, :].clone()
            h = torch.concatenate([mem, xs], axis=1)
            q = torch.einsum('btd,dhe->bhte', h, Wq)
            k = torch.einsum('btd,dhe->bhte', h, Wk)
            v = torch.einsum('btd,dhe->bhte', h, Wv)
            scores = torch.einsum('bhqe,bhke->bhqk', q, k) * scale
            scores = torch.where(mask[None, None], scores, -1000000000.0)
            p = _softmax(scores, axis=-1)
            o = torch.einsum('bhqk,bhke->bhqe', p, v)
            o = torch.einsum('bhte,hed->btd', o, Wo)
            mem = o[:, :M, :].clone()
            outs.append(o[:, M:, :])
        return torch.concatenate(outs, axis=1)

    def _B_ref(q, k, v, shift_k, ssm_k, ssm_D):
        B, S, D = q.shape
        ks = shift_k.shape[-1]
        k_pad = _pad(k, ((0, 0), (ks - 1, 0), (0, 0)))
        k_shift = torch.zeros_like(k)
        for t in range(ks):
            k_shift = k_shift + k_pad[:, t:t + S, :] * shift_k[:, ks - 1 - t][None, None, :]
        kv = k_shift * v
        L = 2 * S
        kv_pad = _pad(kv, ((0, 0), (0, S), (0, 0)))
        kf_pad = _pad(ssm_k, ((0, 0), (0, S)))
        kv_f = (lambda x, axes=(-2, -1): torch.fft.rfft2(x.float(), dim=axes))(kv_pad[:, None, :, :], axes=(1, 2))
        kf_f = (lambda x, axes=(-2, -1): torch.fft.rfft2(x.float(), dim=axes))(kf_pad[:, None, :], axes=(1, 2))
        kf_f = (lambda x, *d: x.permute(*d))(kf_f, 1, 2, 0)
        y_f = kv_f * kf_f[None, :, :, :]
        y = (lambda x, s, axes=(-2, -1): torch.fft.irfft2(x, s=s, dim=axes).to(torch.bfloat16))(y_f, (1, L), axes=(1, 2))[:, 0, :S, :]
        y = y + kv * ssm_D[None, None, :]
        return q * y
    a = _A_ref(A_x, A_mem0, A_Wq, A_Wk, A_Wv, A_Wo, A_seg_len)
    b = _B_ref(B_q, B_k, B_v, B_shift_k, B_ssm_k, B_ssm_D)
    return torch.concatenate([a, b], axis=-1)
```

```cpp
#include <cuda_runtime.h>
#include <cuda_bf16.h>
#include <cuda.h>
#include <stdint.h>

namespace {

constexpr int S_LEN = 2048;
constexpr int DM = 1024;
constexpr int NH = 32;
constexpr int DH = 128;
constexpr int HD = NH * DH;
constexpr int SEG = 32;
constexpr int NSEG = S_LEN / SEG;
constexpr int OUT_LD = 2048;

typedef __nv_bfloat16 bf16;
#define K3_N 160

__device__ __forceinline__ uint32_t smem_u32(const void* p) { return (uint32_t)__cvta_generic_to_shared(p); }

__device__ __forceinline__ void mbar_init(uint32_t bar, uint32_t count) {
  asm volatile("mbarrier.init.shared::cta.b64 [%0], %1;" ::"r"(bar), "r"(count) : "memory");
}
__device__ __forceinline__ void mbar_expect_tx(uint32_t bar, uint32_t bytes) {
  asm volatile("mbarrier.arrive.expect_tx.shared::cta.b64 _, [%0], %1;" ::"r"(bar), "r"(bytes) : "memory");
}
__device__ __forceinline__ void mbar_arrive(uint32_t bar) {
  asm volatile("mbarrier.arrive.shared::cta.b64 _, [%0];" ::"r"(bar) : "memory");
}
__device__ __forceinline__ bool mbar_try(uint32_t bar, uint32_t parity) {
  uint32_t ok;
  asm volatile("{.reg .pred p; mbarrier.try_wait.parity.shared::cta.b64 p, [%1], %2; selp.u32 %0, 1, 0, p;}"
               : "=r"(ok) : "r"(bar), "r"(parity) : "memory");
  return ok;
}
template <int HINT = 1>
__device__ __forceinline__ void mbar_wait(uint32_t bar, uint32_t parity) {
  int guard = 0;
  while (__builtin_expect(!mbar_try(bar, parity), HINT)) { if (++guard > (1 << 22)) __trap(); }
}
__device__ __forceinline__ void tma_load_2d(uint32_t dst, const CUtensorMap* map, int c0, int c1, uint32_t bar) {
  asm volatile("cp.async.bulk.tensor.2d.shared::cluster.global.mbarrier::complete_tx::bytes [%0], [%1, {%3, %4}], [%2];"
               ::"r"(dst), "l"(map), "r"(bar), "r"(c0), "r"(c1) : "memory");
}
__device__ __forceinline__ void tma_load_3d(uint32_t dst, const CUtensorMap* map, int c0, int c1, int c2, uint32_t bar) {
  asm volatile("cp.async.bulk.tensor.3d.shared::cluster.global.mbarrier::complete_tx::bytes [%0], [%1, {%3, %4, %5}], [%2];"
               ::"r"(dst), "l"(map), "r"(bar), "r"(c0), "r"(c1), "r"(c2) : "memory");
}
__device__ __forceinline__ void tma_load_4d(uint32_t dst, const CUtensorMap* map, int c0, int c1, int c2, int c3, uint32_t bar) {
  asm volatile("cp.async.bulk.tensor.4d.shared::cluster.global.mbarrier::complete_tx::bytes [%0], [%1, {%3, %4, %5, %6}], [%2];"
               ::"r"(dst), "l"(map), "r"(bar), "r"(c0), "r"(c1), "r"(c2), "r"(c3) : "memory");
}
__device__ __forceinline__ void tma_store_2d(const CUtensorMap* map, uint32_t src, int c0, int c1) {
  asm volatile("cp.async.bulk.tensor.2d.global.shared::cta.bulk_group [%0, {%2, %3}], [%1];"
               ::"l"(map), "r"(src), "r"(c0), "r"(c1) : "memory");
}
__device__ __forceinline__ void tma_prefetch_desc(const CUtensorMap* map) {
  asm volatile("prefetch.tensormap [%0];" ::"l"(map) : "memory");
}
__device__ __forceinline__ void fence_async_smem() { asm volatile("fence.proxy.async.shared::cta;" ::: "memory"); }
__device__ __forceinline__ void bulk_commit() { asm volatile("cp.async.bulk.commit_group;" ::: "memory"); }
template <int N> __device__ __forceinline__ void bulk_wait_read() { asm volatile("cp.async.bulk.wait_group.read %0;" ::"n"(N) : "memory"); }
template <int N> __device__ __forceinline__ void bulk_wait() { asm volatile("cp.async.bulk.wait_group %0;" ::"n"(N) : "memory"); }
__device__ __forceinline__ void named_bar(int id, int n) { asm volatile("bar.sync %0, %1;" ::"r"(id), "r"(n) : "memory"); }

__device__ __forceinline__ void named_bar_arrive(int id, int n) { asm volatile("bar.arrive %0, %1;" ::"r"(id), "r"(n) : "memory"); }
__device__ __forceinline__ float ex2(float x) { float y; asm("ex2.approx.ftz.f32 %0, %1;" : "=f"(y) : "f"(x)); return y; }
__device__ __forceinline__ float rcp(float x) { float y; asm("rcp.approx.ftz.f32 %0, %1;" : "=f"(y) : "f"(x)); return y; }

__device__ __forceinline__ void sts32(uint32_t a, uint32_t x) { asm volatile("st.shared.b32 [%0], %1;" ::"r"(a), "r"(x) : "memory"); }
__device__ __forceinline__ uint32_t lds32(uint32_t a) { uint32_t x; asm volatile("ld.shared.b32 %0, [%1];" : "=r"(x) : "r"(a) : "memory"); return x; }
__device__ __forceinline__ uint32_t lds32v(uint32_t a) { uint32_t x; asm volatile("ld.volatile.shared.b32 %0, [%1];" : "=r"(x) : "r"(a) : "memory"); return x; }
__device__ __forceinline__ void sts128(uint32_t a, const uint4& v) { asm volatile("st.shared.v4.b32 [%0], {%1,%2,%3,%4};" ::"r"(a), "r"(v.x), "r"(v.y), "r"(v.z), "r"(v.w) : "memory"); }
__device__ __forceinline__ void sts128f(uint32_t a, const float4& v) { asm volatile("st.shared.v4.f32 [%0], {%1,%2,%3,%4};" ::"r"(a), "f"(v.x), "f"(v.y), "f"(v.z), "f"(v.w) : "memory"); }
__device__ __forceinline__ uint4 lds128(uint32_t a) { uint4 v; asm volatile("ld.shared.v4.b32 {%0,%1,%2,%3}, [%4];" : "=r"(v.x), "=r"(v.y), "=r"(v.z), "=r"(v.w) : "r"(a) : "memory"); return v; }
__device__ __forceinline__ float4 lds128f(uint32_t a) { float4 v; asm volatile("ld.shared.v4.f32 {%0,%1,%2,%3}, [%4];" : "=f"(v.x), "=f"(v.y), "=f"(v.z), "=f"(v.w) : "r"(a) : "memory"); return v; }

__device__ __forceinline__ void cp_async16(uint32_t dst, const void* src) { asm volatile("cp.async.cg.shared.global [%0], [%1], 16;" ::"r"(dst), "l"(src) : "memory"); }
__device__ __forceinline__ void cp_async_commit() { asm volatile("cp.async.commit_group;" ::: "memory"); }
template <int N> __device__ __forceinline__ void cp_async_wait_group() { asm volatile("cp.async.wait_group %0;" ::"n"(N) : "memory"); }

__device__ __forceinline__ void wg_fence() { asm volatile("wgmma.fence.sync.aligned;" ::: "memory"); }
__device__ __forceinline__ void wg_commit() { asm volatile("wgmma.commit_group.sync.aligned;" ::: "memory"); }
template <int N> __device__ __forceinline__ void wg_wait() { asm volatile("wgmma.wait_group.sync.aligned %0;" ::"n"(N) : "memory"); }
__device__ __forceinline__ uint64_t make_desc(uint32_t addr, uint32_t lbo, uint32_t sbo, uint32_t swz) {
  return (uint64_t)((addr & 0x3FFFF) >> 4) | ((uint64_t)(lbo >> 4) << 16) | ((uint64_t)(sbo >> 4) << 32) | ((uint64_t)swz << 62);
}

__device__ __forceinline__ void ldsm_x4(uint32_t (&r)[4], uint32_t addr) {
  asm volatile("ldmatrix.sync.aligned.m8n8.x4.shared.b16 {%0,%1,%2,%3}, [%4];"
               : "=r"(r[0]), "=r"(r[1]), "=r"(r[2]), "=r"(r[3]) : "r"(addr) : "memory");
}
__device__ __forceinline__ void ldsm_x4_t(uint32_t (&r)[4], uint32_t addr) {
  asm volatile("ldmatrix.sync.aligned.m8n8.x4.trans.shared.b16 {%0,%1,%2,%3}, [%4];"
               : "=r"(r[0]), "=r"(r[1]), "=r"(r[2]), "=r"(r[3]) : "r"(addr) : "memory");
}
__device__ __forceinline__ void ldsm_x2(uint32_t& r0, uint32_t& r1, uint32_t addr) {
  asm volatile("ldmatrix.sync.aligned.m8n8.x2.shared.b16 {%0,%1}, [%2];" : "=r"(r0), "=r"(r1) : "r"(addr) : "memory");
}
__device__ __forceinline__ void stsm_x4(uint32_t addr, uint32_t r0, uint32_t r1, uint32_t r2, uint32_t r3) {
  asm volatile("stmatrix.sync.aligned.m8n8.x4.shared.b16 [%0], {%1,%2,%3,%4};"
               ::"r"(addr), "r"(r0), "r"(r1), "r"(r2), "r"(r3) : "memory");
}
__device__ __forceinline__ void mma16816(float (&c)[4], const uint32_t (&a)[4], uint32_t b0, uint32_t b1) {
  asm volatile("mma.sync.aligned.m16n8k16.row.col.f32.bf16.bf16.f32 {%0,%1,%2,%3}, {%4,%5,%6,%7}, {%8,%9}, {%0,%1,%2,%3};"
               : "+f"(c[0]), "+f"(c[1]), "+f"(c[2]), "+f"(c[3])
               : "r"(a[0]), "r"(a[1]), "r"(a[2]), "r"(a[3]), "r"(b0), "r"(b1));
}
__device__ __forceinline__ void mma1688(float (&c)[4], uint32_t a0, uint32_t a1, uint32_t b0) {
  asm volatile("mma.sync.aligned.m16n8k8.row.col.f32.bf16.bf16.f32 {%0,%1,%2,%3}, {%4,%5}, {%6}, {%0,%1,%2,%3};"
               : "+f"(c[0]), "+f"(c[1]), "+f"(c[2]), "+f"(c[3]) : "r"(a0), "r"(a1), "r"(b0));
}
__device__ __forceinline__ uint32_t pack_bf16(float lo, float hi) {
  uint32_t r;
  asm("cvt.rn.bf16x2.f32 %0, %1, %2;" : "=r"(r) : "f"(hi), "f"(lo));
  return r;
}
__device__ __forceinline__ float bf_lo(uint32_t w) { return __uint_as_float(w << 16); }
__device__ __forceinline__ float bf_hi(uint32_t w) { return __uint_as_float(w & 0xFFFF0000u); }

__device__ __forceinline__ uint4 ld_relaxed4(const void* p) {
  uint4 v;
  asm volatile("ld.relaxed.gpu.global.v4.u32 {%0,%1,%2,%3}, [%4];" : "=r"(v.x), "=r"(v.y), "=r"(v.z), "=r"(v.w) : "l"(p) : "memory");
  return v;
}
__device__ __forceinline__ void st_relaxed4(void* p, uint32_t a, uint32_t b, uint32_t c, uint32_t d) {
  asm volatile("st.relaxed.gpu.global.v4.u32 [%0], {%1,%2,%3,%4};" ::"l"(p), "r"(a), "r"(b), "r"(c), "r"(d) : "memory");
}
__device__ __forceinline__ void st_relaxed2(void* p, uint32_t a, uint32_t b) {
  asm volatile("st.relaxed.gpu.global.v2.u32 [%0], {%1,%2};" ::"l"(p), "r"(a), "r"(b) : "memory");
}
__device__ __forceinline__ void st_relaxed1(void* p, uint32_t a) {
  asm volatile("st.relaxed.gpu.global.u32 [%0], %1;" ::"l"(p), "r"(a) : "memory");
}

__device__ __forceinline__ uint2 ld_relaxed2(const void* p) {
  uint2 v;
  asm volatile("ld.relaxed.gpu.global.v2.u32 {%0,%1}, [%2];" : "=r"(v.x), "=r"(v.y) : "l"(p) : "memory");
  return v;
}
__device__ __forceinline__ void sts64(uint32_t a, uint32_t x, uint32_t y) { asm volatile("st.shared.v2.b32 [%0], {%1,%2};" ::"r"(a), "r"(x), "r"(y) : "memory"); }
__device__ __forceinline__ uint2 lds64(uint32_t a) { uint2 v; asm volatile("ld.shared.v2.b32 {%0,%1}, [%2];" : "=r"(v.x), "=r"(v.y) : "r"(a) : "memory"); return v; }
__device__ __forceinline__ void lds128r(uint32_t (&r)[4], uint32_t a) {
  asm volatile("ld.shared.v4.b32 {%0,%1,%2,%3}, [%4];" : "=r"(r[0]), "=r"(r[1]), "=r"(r[2]), "=r"(r[3]) : "r"(a) : "memory");
}
__device__ __forceinline__ uint32_t movmat(uint32_t a) { uint32_t d; asm volatile("movmatrix.sync.aligned.m8n8.trans.b16 %0, %1;" : "=r"(d) : "r"(a)); return d; }
__device__ __forceinline__ uint32_t mapa(uint32_t addr, uint32_t rank) { uint32_t r; asm volatile("mapa.shared::cluster.u32 %0, %1, %2;" : "=r"(r) : "r"(addr), "r"(rank)); return r; }
__device__ __forceinline__ void st_async1(uint32_t dst, uint32_t a, uint32_t bar) {
  asm volatile("st.async.weak.shared::cluster.mbarrier::complete_tx::bytes.b32 [%0], %1, [%2];" ::"r"(dst), "r"(a), "r"(bar) : "memory");
}
__device__ __forceinline__ void st_async2(uint32_t dst, uint32_t a, uint32_t b, uint32_t bar) {
  asm volatile("st.async.weak.shared::cluster.mbarrier::complete_tx::bytes.v2.b32 [%0], {%1,%2}, [%3];" ::"r"(dst), "r"(a), "r"(b), "r"(bar) : "memory");
}
__device__ __forceinline__ void st_async4(uint32_t dst, uint32_t a, uint32_t b, uint32_t c, uint32_t d, uint32_t bar) {
  asm volatile("st.async.weak.shared::cluster.mbarrier::complete_tx::bytes.v4.b32 [%0], {%1,%2,%3,%4}, [%5];" ::"r"(dst), "r"(a), "r"(b), "r"(c), "r"(d), "r"(bar) : "memory");
}
__device__ __forceinline__ void cluster_arrive() { asm volatile("barrier.cluster.arrive.release.aligned;" ::: "memory"); }
__device__ __forceinline__ void cluster_wait() { asm volatile("barrier.cluster.wait.acquire.aligned;" ::: "memory"); }

__device__ __forceinline__ void wgmma_k3_ss_ta(float (&d)[80], uint64_t da, uint64_t db, int scale_d) {
  asm volatile("{.reg .pred p; setp.ne.b32 p, %82, 0;\n"
    "wgmma.mma_async.sync.aligned.m64n160k16.f32.bf16.bf16 {%0, %1, %2, %3, %4, %5, %6, %7, %8, %9, %10, %11, %12, %13, %14, %15, %16, %17, %18, %19, %20, %21, %22, %23, %24, %25, %26, %27, %28, %29, %30, %31, %32, %33, %34, %35, %36, %37, %38, %39, %40, %41, %42, %43, %44, %45, %46, %47, %48, %49, %50, %51, %52, %53, %54, %55, %56, %57, %58, %59, %60, %61, %62, %63, %64, %65, %66, %67, %68, %69, %70, %71, %72, %73, %74, %75, %76, %77, %78, %79}, %80, %81, p, 1, 1, 1, 0;}"
    : "+f"(d[0]), "+f"(d[1]), "+f"(d[2]), "+f"(d[3]), "+f"(d[4]), "+f"(d[5]), "+f"(d[6]), "+f"(d[7]), "+f"(d[8]), "+f"(d[9]), "+f"(d[10]), "+f"(d[11]), "+f"(d[12]), "+f"(d[13]), "+f"(d[14]), "+f"(d[15]), "+f"(d[16]), "+f"(d[17]), "+f"(d[18]), "+f"(d[19]), "+f"(d[20]), "+f"(d[21]), "+f"(d[22]), "+f"(d[23]), "+f"(d[24]), "+f"(d[25]), "+f"(d[26]), "+f"(d[27]), "+f"(d[28]), "+f"(d[29]), "+f"(d[30]), "+f"(d[31]), "+f"(d[32]), "+f"(d[33]), "+f"(d[34]), "+f"(d[35]), "+f"(d[36]), "+f"(d[37]), "+f"(d[38]), "+f"(d[39]), "+f"(d[40]), "+f"(d[41]), "+f"(d[42]), "+f"(d[43]), "+f"(d[44]), "+f"(d[45]), "+f"(d[46]), "+f"(d[47]), "+f"(d[48]), "+f"(d[49]), "+f"(d[50]), "+f"(d[51]), "+f"(d[52]), "+f"(d[53]), "+f"(d[54]), "+f"(d[55]), "+f"(d[56]), "+f"(d[57]), "+f"(d[58]), "+f"(d[59]), "+f"(d[60]), "+f"(d[61]), "+f"(d[62]), "+f"(d[63]), "+f"(d[64]), "+f"(d[65]), "+f"(d[66]), "+f"(d[67]), "+f"(d[68]), "+f"(d[69]), "+f"(d[70]), "+f"(d[71]), "+f"(d[72]), "+f"(d[73]), "+f"(d[74]), "+f"(d[75]), "+f"(d[76]), "+f"(d[77]), "+f"(d[78]), "+f"(d[79])
    : "l"(da), "l"(db), "r"(scale_d));
}
__device__ __forceinline__ void wgmma_m64n32_ss_ta(float (&d)[16], uint64_t da, uint64_t db, int scale_d) {
  asm volatile("{.reg .pred p; setp.ne.b32 p, %18, 0;\n"
    "wgmma.mma_async.sync.aligned.m64n32k16.f32.bf16.bf16 {%0, %1, %2, %3, %4, %5, %6, %7, %8, %9, %10, %11, %12, %13, %14, %15}, %16, %17, p, 1, 1, 1, 0;}"
    : "+f"(d[0]), "+f"(d[1]), "+f"(d[2]), "+f"(d[3]), "+f"(d[4]), "+f"(d[5]), "+f"(d[6]), "+f"(d[7]), "+f"(d[8]), "+f"(d[9]), "+f"(d[10]), "+f"(d[11]), "+f"(d[12]), "+f"(d[13]), "+f"(d[14]), "+f"(d[15])
    : "l"(da), "l"(db), "r"(scale_d));
}

__device__ __forceinline__ void wgmma_m64n32_rs(float (&d)[16], const uint32_t (&a)[4], uint64_t db, int scale_d) {
  asm volatile("{.reg .pred p; setp.ne.b32 p, %21, 0;\n"
    "wgmma.mma_async.sync.aligned.m64n32k16.f32.bf16.bf16 {%0, %1, %2, %3, %4, %5, %6, %7, %8, %9, %10, %11, %12, %13, %14, %15}, {%16, %17, %18, %19}, %20, p, 1, 1, 0;}"
    : "+f"(d[0]), "+f"(d[1]), "+f"(d[2]), "+f"(d[3]), "+f"(d[4]), "+f"(d[5]), "+f"(d[6]), "+f"(d[7]), "+f"(d[8]), "+f"(d[9]), "+f"(d[10]), "+f"(d[11]), "+f"(d[12]), "+f"(d[13]), "+f"(d[14]), "+f"(d[15])
    : "r"(a[0]), "r"(a[1]), "r"(a[2]), "r"(a[3]), "l"(db), "r"(scale_d));
}

#define X_POS 7
#define D_A 3400
#define D_O 1900
#define VT_POS 4
#define O_EARLY 8
#define V_PRE 4
#define O_PRE 16
#define SFENCE(i) asm volatile("{.reg .pred p; setp.eq.u32 p, %0, %1; @p trap;}" ::"r"(s), "r"(4096 + (i)) : "memory")
constexpr int RING = 4;
constexpr uint32_t EMPTY = 0xFFFFFFFFu;
namespace xo {
constexpr uint32_t SLOT = 1u << 20, HEAD = 16384;
constexpr uint32_t OM = 0;
constexpr uint32_t VM = 512;
constexpr uint32_t PT = 1024;
constexpr uint32_t PM = 1536;
constexpr uint32_t VT = 8192;
constexpr uint32_t MEM = NH * HEAD;
constexpr uint32_t O = RING * SLOT;
constexpr uint32_t BYTES = O + S_LEN * HD * 2;
}
__device__ __align__(1024) uint4 g_scratch[2 * (xo::BYTES / 16)];
__device__ unsigned g_epoch;

struct ChainMaps {
  CUtensorMap wq, wk, wv;
  CUtensorMap wo;
  CUtensorMap x;
};

namespace chain {
constexpr int OFF_X = 65536;
constexpr int OFF_MEM = 131072;
constexpr int OFF_WS = 0;
constexpr int OFF_FP = 147456;
constexpr int OFF_KT = 163840;
constexpr int OFF_QT = 180224;
constexpr int OFF_VT = 196608;
constexpr int OFF_PX = 204800;
constexpr int OFF_S4 = OFF_PX + 1536;
constexpr int OFF_QM = 212992;
constexpr int OFF_KM = 215040;
constexpr int OFF_S1 = 217088;
constexpr int OFF_WVR = 0;
constexpr int OFF_WOR = 147456;
constexpr int OFF_RED = 212992;
constexpr int OFF_VPX = 221184;
constexpr int OFF_RX = 223232;
constexpr int OFF_TR = 225280;
constexpr int OFF_BAR = 229376;
constexpr int BAR_X = OFF_BAR, BAR_TOK = OFF_BAR + 16, BAR_EX = OFF_BAR + 32, BAR_P = OFF_BAR + 40, GRID_TGT = OFF_BAR + 128;
constexpr int SMEM = OFF_BAR + 256;
constexpr uint32_t SB_LO = 1024;
constexpr float SCALE = 0.08838834764831845f, L2E = 1.4426950408889634f;
}

__device__ __forceinline__ uint32_t umax4(const uint4& v) { return max(max(v.x, v.y), max(v.z, v.w)); }
__device__ __forceinline__ uint32_t umax4(const uint32_t (&v)[4]) { return max(max(v[0], v[1]), max(v[2], v[3])); }
__device__ __forceinline__ bool warp_incomplete(uint32_t m) { return __any_sync(0xffffffffu, m == EMPTY); }
#define PIN(x) asm volatile("" : "+r"(x))
#define KEEPALIVE(a, z) do { float _d0, _d1, _d2, _d3; asm volatile("mma.sync.aligned.m16n8k16.row.col.f32.bf16.bf16.f32 {%0,%1,%2,%3}, {%4,%5,%6,%7}, {%4,%5}, {%8,%8,%8,%8};" \
    : "=f"(_d0), "=f"(_d1), "=f"(_d2), "=f"(_d3) : "r"(a[0]), "r"(a[1]), "r"(a[2]), "r"(a[3]), "f"(0.f)); \
      \
    asm volatile("{.reg .pred p; setp.ne.u32 p, %0, 0; @p st.shared.f32 [%0], %1;}" ::"r"(z), "f"(_d0 + _d3) : "memory"); } while (0)
constexpr int POLL_LIMIT = 1 << 17;

__device__ __forceinline__ uint32_t keep(uint32_t x) { return __shfl_sync(0xffffffffu, x, threadIdx.x & 31); }
__device__ __forceinline__ char* gptr(uint32_t hi, uint32_t lo) { return (char*)(((uint64_t)hi << 32) | lo); }
__device__ __forceinline__ uint32_t slot_off(int n) { return ((uint32_t)n & (RING - 1)) * xo::SLOT; }
__device__ __forceinline__ void acc_fence(float (&a)[16]) {
#pragma unroll
  for (int i = 0; i < 16; i++) asm volatile("" : "+f"(a[i]) :: "memory");
}
__device__ __forceinline__ void gather_issue(uint32_t dst, const char* src, uint32_t pred = 1) {
  asm volatile("{.reg .pred p; setp.ne.u32 p, %2, 0;\n"
               "@p cp.async.cg.shared.global [%0], [%1], 16; @p cp.async.cg.shared.global [%0 + 512], [%1 + 512], 16;\n"
               "@p cp.async.cg.shared.global [%0 + 1024], [%1 + 1024], 16; @p cp.async.cg.shared.global [%0 + 1536], [%1 + 1536], 16;\n"
               "cp.async.commit_group;}" ::"r"(dst), "l"(src), "r"(pred) : "memory");
}
__device__ __forceinline__ bool gather_incomplete(uint32_t dst) {
  const uint4 v0 = lds128(dst), v1 = lds128(dst + 512), v2 = lds128(dst + 1024), v3 = lds128(dst + 1536);
  return warp_incomplete(max(max(umax4(v0), umax4(v1)), max(umax4(v2), umax4(v3))));
}
__device__ __forceinline__ uint32_t ld_relaxed1(const void* p) {
  uint32_t v;
  asm volatile("ld.relaxed.gpu.global.u32 %0, [%1];" : "=r"(v) : "l"(p) : "memory");
  return v;
}
__device__ __forceinline__ uint32_t clock32() { uint64_t c; asm volatile("mov.u64 %0, %%clock64;" : "=l"(c) :: "memory"); return (uint32_t)c; }
#define WAIT_UNTIL(t, ka) do { while ((int)(clock32() - (t)) < 0) KEEPALIVE(ka, zr); } while (0)
__device__ __forceinline__ void issue_x(uint32_t sb, const CUtensorMap* map, int n, int part) {
  asm volatile("{.reg .pred p; elect.sync _|p, 0xffffffff;\n"
               "@p cp.async.bulk.tensor.3d.shared::cluster.global.mbarrier::complete_tx::bytes [%0], [%1, {%3, %4, %5}], [%2];}"
               ::"r"(sb + chain::OFF_X + part * 32768), "l"(map), "r"(sb + chain::BAR_X + 8 * part), "r"(0), "r"(n * SEG), "r"(part * 8) : "memory");
}
__device__ __forceinline__ void expect_elect(uint32_t bar, uint32_t bytes) {
  asm volatile("{.reg .pred p; elect.sync _|p, 0xffffffff; @p mbarrier.arrive.expect_tx.shared::cta.b64 _, [%0], %1;}" ::"r"(bar), "r"(bytes) : "memory");
}
template <int WG> __device__ __forceinline__ constexpr uint64_t xdesc(int ks) {
  return (uint64_t)(((chain::SB_LO + chain::OFF_X + WG * 32768 + (ks >> 2) * 4096 + (ks & 3) * 32) >> 4) + (1u << 16)) |
         ((uint64_t)(64u | (1u << 30)) << 32);
}
template <int WG> __device__ __forceinline__ constexpr uint64_t wdesc(int o, int ks) {
  return (uint64_t)(((chain::SB_LO + chain::OFF_WS + WG * 32768 + o * 16384 + ks * 2048) >> 4) + (1u << 16)) | ((uint64_t)(64u | (1u << 30)) << 32);
}
__device__ __forceinline__ void load_mem0(uint32_t sb, const bf16* __restrict__ mem0) {
  uint2 m[8];
#pragma unroll
  for (int r = 0; r < 8; r++) m[r] = __ldg((const uint2*)(mem0 + r * DM) + threadIdx.x);
  const uint32_t d = sb + chain::OFF_MEM + threadIdx.x * 64;
  sts128(d, make_uint4(__byte_perm(m[0].x, m[1].x, 0x5410), __byte_perm(m[2].x, m[3].x, 0x5410), __byte_perm(m[4].x, m[5].x, 0x5410), __byte_perm(m[6].x, m[7].x, 0x5410)));
  sts128(d + 16, make_uint4(__byte_perm(m[0].x, m[1].x, 0x7632), __byte_perm(m[2].x, m[3].x, 0x7632), __byte_perm(m[4].x, m[5].x, 0x7632), __byte_perm(m[6].x, m[7].x, 0x7632)));
  sts128(d + 32, make_uint4(__byte_perm(m[0].y, m[1].y, 0x5410), __byte_perm(m[2].y, m[3].y, 0x5410), __byte_perm(m[4].y, m[5].y, 0x5410), __byte_perm(m[6].y, m[7].y, 0x5410)));
  sts128(d + 48, make_uint4(__byte_perm(m[0].y, m[1].y, 0x7632), __byte_perm(m[2].y, m[3].y, 0x7632), __byte_perm(m[4].y, m[5].y, 0x7632), __byte_perm(m[6].y, m[7].y, 0x7632)));
}
__device__ __forceinline__ void grid_wait(uint32_t sb) {
  if (threadIdx.x == 0) {
    const uint32_t target = lds32(sb + chain::GRID_TGT);
    uint32_t v; int guard = 0;
    do { asm volatile("ld.acquire.gpu.global.u32 %0, [%1];" : "=r"(v) : "l"(&g_epoch) : "memory"); } while ((int)(v - target) < 0 && ++guard < (1 << 20));
  }
  named_bar(0, 256);
}
__device__ __forceinline__ uint32_t loop_zero(int s) { uint32_t z; asm volatile("shr.u32 %0, %1, 16;" : "=r"(z) : "r"(s + 1)); return z; }

template <int J, int WG>
__device__ __forceinline__ void role_a(const ChainMaps& maps, const bf16* __restrict__ mem0, const uint32_t sb, const uint32_t xbase_lo, const uint32_t xbase_hi) {
  using namespace chain;
  const int h = blockIdx.x >> 2;
  const uint32_t u16 = (threadIdx.x & 96) * 64 + (threadIdx.x & 31) * 16;
  const uint32_t t16 = keep(u16), l16 = keep((threadIdx.x & 31) * 16);
  const uint32_t a_wl = keep((((threadIdx.x >> 4) & 1) * 8 + (threadIdx.x & 7)) * 128 + (((((threadIdx.x >> 4) & 6) + ((threadIdx.x >> 3) & 1)) ^ (threadIdx.x & 7)) << 4));
  const uint32_t xhi = keep(xbase_hi + (t16 >> 16)), xh = keep(xbase_lo + h * xo::HEAD + u16);
  const uint32_t dxm = xo::MEM + WG * 8192 - h * xo::HEAD;
#define xm (xh + (dxm + zr))
#define last_warp __any_sync(0xffffffffu, tv >= 6144)
#define tv (t16 + zr)
  const CUtensorMap* wm = J ? &maps.wk : &maps.wq;

  uint32_t aW[2][24][4];
  mbar_wait(sb + BAR_P, 0);
#pragma unroll
  for (int ks = 0; ks < 24; ks++) ldsm_x4_t(aW[0][ks], sb + a_wl + OFF_X + WG * 49152 + ks * 2048);
  named_bar(0, 256);
  if (WG == 1 && __any_sync(0xffffffffu, t16 >= 6144)) {
    fence_async_smem();
    if (l16 == 0) {
      mbar_expect_tx(sb + BAR_P + 16, 2 * 16384);
      for (int q = 0; q < 2; q++) tma_load_2d(sb + OFF_X + (4 + q) * 16384, wm, h * DH + (q ^ 1) * 64, q * 512 + 256, sb + BAR_P + 16);
    }
    __syncwarp();
    expect_elect(sb + BAR_X, 32768); expect_elect(sb + BAR_X + 8, 32768); expect_elect(sb + BAR_TOK, 8192);
    issue_x(sb, &maps.x, 0, 0); issue_x(sb, &maps.x, 0, 1);
  }
  mbar_wait(sb + BAR_P + 8, 0);
#pragma unroll
  for (int ks = 0; ks < 16; ks++) ldsm_x4_t(aW[1][ks], sb + a_wl + OFF_X + 6 * 16384 + WG * 32768 + ks * 2048);
  mbar_wait(sb + BAR_P + 16, 0);
#pragma unroll
  for (int ks = 0; ks < 8; ks++) ldsm_x4_t(aW[1][16 + ks], sb + a_wl + OFF_X + (4 + WG) * 16384 + ks * 2048);
  named_bar(0, 256);
  cluster_arrive();
  load_mem0(sb, mem0);
  mbar_wait(sb + BAR_P + 24, 0);
  cluster_wait();
  const uint32_t rsb = mapa(sb, J ^ 1);
  const uint32_t a_ws = sb + a_wl + OFF_WS + WG * 32768;

  uint32_t tref = 0;
#pragma unroll 1
  for (int s = -1; s < (J ? NSEG : NSEG - 1); s++) {
    const bool more = J == 0 || __builtin_expect(s + 1 < NSEG, 1);
    const uint32_t zr = loop_zero(s);
#define wq ((int)(tv >> 11))
#define lv (l16 + zr)
#define gh (xh + slot_off(s))
    if (__builtin_expect(s >= 0, 1)) {
      uint32_t ws[4][4];
      ldsm_x4_t(ws[0], a_ws); ldsm_x4_t(ws[1], a_ws + 16384); ldsm_x4_t(ws[2], a_ws + 2048); ldsm_x4_t(ws[3], a_ws + 16384 + 2048);
      if (__builtin_expect(s > 0, 1)) {
        const uint32_t dst = sb + OFF_MEM + WG * 8192 + t16;
        const char* src = gptr(xhi, xm + slot_off(s));
        WAIT_UNTIL(tref, aW[0][0]);
        uint32_t tries = zr;
#pragma unroll 1
        do {
          gather_issue(dst + zr, src);
          KEEPALIVE(aW[0][0], zr);
          cp_async_wait_group<0>();
        } while (gather_incomplete(dst) && ++tries < POLL_LIMIT);
        named_bar(1 + WG, 128);
      }
      float c[2][2][4];
#pragma unroll
      for (int i = 0; i < 4; i++) c[i >> 1][i & 1][0] = c[i >> 1][i & 1][1] = c[i >> 1][i & 1][2] = c[i >> 1][i & 1][3] = 0.f;
      {
        const uint32_t a_mem = sb + OFF_MEM + WG * 8192 + l16;
        uint32_t b[4][4];
        ldsm_x4_t(b[0], a_mem); ldsm_x4_t(b[1], a_mem + 12 * 512);
#pragma unroll
        for (int i = 0; i < 16; i++) {
          if (i + 2 < 16) { const int n = i + 2, pn = (n & 3) == 1 ? 12 + (n >> 2) : 3 * (n >> 2) + ((n & 3) ? (n & 3) - 1 : 0); ldsm_x4_t(b[n & 3], a_mem + pn * 512); }
          if (i < 12) {
            const uint32_t a = a_ws + ((i >> 2) + 1) * 4096;
            if ((i & 3) == 2) { ldsm_x4_t(ws[0], a); ldsm_x4_t(ws[1], a + 16384); }
            if ((i & 3) == 3) { ldsm_x4_t(ws[2], a + 2048); ldsm_x4_t(ws[3], a + 16384 + 2048); }
          }
          if (i == VT_POS && WG == 0 && J == 0) gather_issue(sb + OFF_VT + tv, gptr(xhi, gh) + xo::VT);
          if ((i & 3) == 1) {
            mma16816(c[0][0], ws[0], b[i & 3][0], b[i & 3][1]); mma16816(c[1][0], ws[1], b[i & 3][0], b[i & 3][1]);
            mma16816(c[0][1], ws[2], b[i & 3][2], b[i & 3][3]); mma16816(c[1][1], ws[3], b[i & 3][2], b[i & 3][3]);
          } else {
            const int p = 3 * (i >> 2) + ((i & 3) ? (i & 3) - 1 : 0);
            mma16816(c[1][0], aW[1][2 * p], b[i & 3][0], b[i & 3][1]); mma16816(c[1][1], aW[1][2 * p + 1], b[i & 3][2], b[i & 3][3]);
            mma16816(c[0][0], aW[0][2 * p], b[i & 3][0], b[i & 3][1]); mma16816(c[0][1], aW[0][2 * p + 1], b[i & 3][2], b[i & 3][3]);
          }
          if (i == (WG ? 11 : 9) && (J == 1 || WG == 1)) mbar_wait<0>(sb + BAR_TOK + 8 * (s & 1), (s >> 1) & 1);
          else if ((i & 1) && i < 15) SFENCE(i);
          if (i == X_POS && WG == 1 && last_warp) {
            if (more) { issue_x(sb, &maps.x, s + 1, 1); issue_x(sb, &maps.x, s + 1, 0); }
          }
        }
      }
      sts128f(sb + OFF_PX + WG * 512 + t16, make_float4(c[1][0][0] + c[1][1][0], c[1][0][1] + c[1][1][1], c[1][0][2] + c[1][1][2], c[1][0][3] + c[1][1][3]));
      const float4 own = make_float4(c[0][0][0] + c[0][1][0], c[0][0][1] + c[0][1][1], c[0][0][2] + c[0][1][2], c[0][0][3] + c[0][1][3]);
      SFENCE(16);
      named_bar(3, 256);
      {
        const float4 o = lds128f(sb + OFF_PX + (WG ^ 1) * 512 + t16);
        const uint32_t lo = pack_bf16(own.x + o.x, own.y + o.y), hi = pack_bf16(own.z + o.z, own.w + o.w);
        const uint32_t a = (J ? OFF_KM : OFF_QM) + WG * 1024 + wq * 256 + (lv >> 2);
        if (J == 1 && more) { st_async1(rsb + a, lo, rsb + BAR_EX); st_async1(rsb + a + 128, hi, rsb + BAR_EX); }
        sts32(sb + a, lo); sts32(sb + a + 128, hi);
      }
      tref = clock32() + D_A;
      const uint32_t kt = sb + OFF_KT + (s & 1) * 8192;
      if (J == 0) {
        uint32_t am[4][4], kb[4][4];
        uint2 vm0, vm1;
        const char* pvm = gptr(xhi, gh - (lv >> 1)) + xo::VM;
        if (WG == 0) { vm0 = ld_relaxed2(pvm); vm1 = ld_relaxed2(pvm + 256); }
        if (WG == 1) {
#pragma unroll
          for (int p = 0; p < 4; p++) lds128r(kb[p], kt + t16 + p * 512);
        }
        named_bar(7, 256);
#pragma unroll
        for (int p = 0; p < 4; p++) ldsm_x4_t(am[p], sb + OFF_QM + p * 512 + ((lv & 128) << 1) + ((lv & 256) >> 1) + (lv & 112));
        auto scores = [&]() {
          float c0[2][4], c1[2][4];
#pragma unroll
          for (int i = 0; i < 2; i++) { c0[i][0] = c0[i][1] = c0[i][2] = c0[i][3] = 0.f; c1[i][0] = c1[i][1] = c1[i][2] = c1[i][3] = 0.f; }
#pragma unroll
          for (int p = 0; p < 4; p++) { mma16816(c0[p & 1], am[p], kb[p][0], kb[p][1]); mma16816(c1[p & 1], am[p], kb[p][2], kb[p][3]); }
          const uint32_t r1 = pack_bf16((c0[0][0] + c0[1][0]) + (c1[0][2] + c1[1][2]), (c0[0][1] + c0[1][1]) + (c1[0][3] + c1[1][3]));
          return pack_bf16(bf_lo(r1) * SCALE, bf_hi(r1) * SCALE);
        };
        if (WG == 1) {
          sts32(sb + OFF_S4 + l16 + wq * 4, scores());
          named_bar_arrive(8, 256);
        } else {
          cp_async_wait_group<0>();
          mbar_wait<0>(sb + BAR_EX, s & 1);
#pragma unroll
          for (int p = 0; p < 4; p++) ldsm_x4_t(kb[p], sb + OFF_KM + p * 512 + l16);
          named_bar(8, 256);
          const uint4 sv = lds128(sb + OFF_S4 + l16);
          const uint32_t sm = scores();
          float x[10] = {bf_lo(sm), bf_hi(sm), bf_lo(sv.x), bf_hi(sv.x), bf_lo(sv.y), bf_hi(sv.y), bf_lo(sv.z), bf_hi(sv.z), bf_lo(sv.w), bf_hi(sv.w)};
          float mx = fmaxf(fmaxf(fmaxf(x[2], x[3]), fmaxf(x[4], x[5])), fmaxf(fmaxf(x[6], x[7]), fmaxf(x[8], x[9])));
          mx = fmaxf(mx, fmaxf(x[0], x[1]));
          mx = fmaxf(mx, __shfl_xor_sync(~0u, mx, 1));
          mx = fmaxf(mx, __shfl_xor_sync(~0u, mx, 2));
          uint32_t vb[4][4];
#pragma unroll
          for (int n = 0; n < 4; n++) lds128r(vb[n], sb + OFF_VT + t16 + n * 512);
          const float mb = mx * L2E;
#pragma unroll
          for (int i = 0; i < 10; i++) x[i] = ex2(fmaf(x[i], L2E, -mb));
          if (__builtin_expect(warp_incomplete(max(max(max(umax4(vb[0]), umax4(vb[1])), max(umax4(vb[2]), umax4(vb[3]))), max(max(vm0.x, vm0.y), max(vm1.x, vm1.y)))), 0)) {
            uint32_t tries = zr;
#pragma unroll 1
            do {
              vm0 = ld_relaxed2(pvm); vm1 = ld_relaxed2(pvm + 256);
#pragma unroll
              for (int n = 0; n < 4; n++) { const uint4 v = ld_relaxed4(gptr(xhi, gh) + xo::VT + n * 512); vb[n][0] = v.x; vb[n][1] = v.y; vb[n][2] = v.z; vb[n][3] = v.w; }
            } while (warp_incomplete(max(max(max(umax4(vb[0]), umax4(vb[1])), max(umax4(vb[2]), umax4(vb[3]))), max(max(vm0.x, vm0.y), max(vm1.x, vm1.y)))) && ++tries < POLL_LIMIT);
          }
          uint32_t pq[4];
          pq[0] = pack_bf16(x[2], x[3]); pq[2] = pack_bf16(x[4], x[5]);
          pq[1] = pack_bf16(x[6], x[7]); pq[3] = pack_bf16(x[8], x[9]);
          const uint32_t p4 = pack_bf16(x[0], x[1]);
          float sx = ((x[0] + x[1]) + (x[2] + x[3])) + ((x[4] + x[5]) + (x[6] + x[7])) + (x[8] + x[9]);
          float oa[4][4], ob[4][4];
#pragma unroll
          for (int n = 0; n < 4; n++) { oa[n][0] = oa[n][1] = oa[n][2] = oa[n][3] = 0.f; ob[n][0] = ob[n][1] = ob[n][2] = ob[n][3] = 0.f; }
          sx += __shfl_xor_sync(~0u, sx, 1);
#pragma unroll
          for (int n = 0; n < 4; n++) mma16816(oa[n], pq, vb[n][0], vb[n][1]);
          sx += __shfl_xor_sync(~0u, sx, 2);
#pragma unroll
          for (int n = 0; n < 4; n++) mma16816(ob[n], pq, vb[n][2], vb[n][3]);
          const float rx = rcp(sx);
          mma1688(oa[0], p4, p4, vm0.x); mma1688(oa[1], p4, p4, vm0.y); mma1688(oa[2], p4, p4, vm1.x); mma1688(oa[3], p4, p4, vm1.y);
          SFENCE(24);
          named_bar_arrive(10, 256);
          st_relaxed4(gptr(xhi, gh) + xo::OM, pack_bf16((oa[0][0] + ob[0][2]) * rx, (oa[0][1] + ob[0][3]) * rx), pack_bf16((oa[1][0] + ob[1][2]) * rx, (oa[1][1] + ob[1][3]) * rx),
                      pack_bf16((oa[2][0] + ob[2][2]) * rx, (oa[2][1] + ob[2][3]) * rx), pack_bf16((oa[3][0] + ob[3][2]) * rx, (oa[3][1] + ob[3][3]) * rx));
          st_relaxed4(gptr(xhi, xh + slot_off(s + 3)) + xo::OM, EMPTY, EMPTY, EMPTY, EMPTY);
        }
      } else {
        {
          const int mt = WG | (wq == 3), ktile = wq == 3 ? 2 + WG : wq - 1;
          const uint32_t qt = sb + OFF_QT + (s & 1) * 8192 + mt * 512 + l16;
          uint32_t kb[4][4], q[4][4];
#pragma unroll
          for (int i = 0; i < 4; i++) lds128r(q[i], qt + i * 2048);
          if (__any_sync(0xffffffffu, tv < 2048)) {
            named_bar(7, 256);
#pragma unroll
            for (int p = 0; p < 4; p++) ldsm_x4_t(kb[p], sb + OFF_KM + p * 512 + l16);
          } else {
            named_bar_arrive(7, 256);
#pragma unroll
            for (int p = 0; p < 4; p++) lds128r(kb[p], kt + l16 + ktile * 2048 + p * 512);
          }
          float c0[4] = {0.f, 0.f, 0.f, 0.f}, c1[4] = {0.f, 0.f, 0.f, 0.f};
#pragma unroll
          for (int p = 0; p < 2; p++) {
            mma16816(c0, q[2 * p], kb[p][0], kb[p][1]); lds128r(q[2 * p], qt + 1024 + 2 * p * 2048);
            mma16816(c1, q[2 * p + 1], kb[p][2], kb[p][3]); lds128r(q[2 * p + 1], qt + 1024 + (2 * p + 1) * 2048);
          }
          SFENCE(21);
#pragma unroll
          for (int p = 0; p < 2; p++) { mma16816(c0, q[2 * p], kb[2 + p][0], kb[2 + p][1]); mma16816(c1, q[2 * p + 1], kb[2 + p][2], kb[2 + p][3]); }
          const uint32_t r0 = pack_bf16(c0[0] + c1[0], c0[1] + c1[1]), r1 = pack_bf16(c0[2] + c1[2], c0[3] + c1[3]);
          const uint32_t sa = wq == 0 ? sb + OFF_S1 + (lv >> 2) + mt * 256 : sb + OFF_S4 + l16 + mt * 4096 + ktile * 4;
          sts32(sa, pack_bf16(bf_lo(r0) * SCALE, bf_hi(r0) * SCALE));
          sts32(sa + (wq == 0 ? 128 : 2048), pack_bf16(bf_lo(r1) * SCALE, bf_hi(r1) * SCALE));
        }
        if (WG == 1) { if (!more) named_bar_arrive(8, 256); }
        else {
          named_bar(8, 256);
          const uint4 sv = lds128(sb + OFF_S4 + t16); const uint32_t s1 = lds32(sb + OFF_S1 + wq * 128 + (lv >> 2));
          float y[10] = {bf_lo(s1), bf_hi(s1), bf_lo(sv.x), bf_hi(sv.x), bf_lo(sv.y), bf_hi(sv.y), bf_lo(sv.z), bf_hi(sv.z), bf_lo(sv.w), bf_hi(sv.w)};
          const int rel = wq * 8 + (int)(lv >> 6) - (int)((lv >> 3) & 6);
          const float NEG = -999292928.f;
#pragma unroll
          for (int n = 0; n < 4; n++) {
            if (n * 8 > rel) y[2 * n + 2] = NEG;
            if (n * 8 + 1 > rel) y[2 * n + 3] = NEG;
          }
          float my = fmaxf(fmaxf(fmaxf(y[0], y[1]), fmaxf(y[2], y[3])), fmaxf(fmaxf(y[4], y[5]), fmaxf(y[6], y[7])));
          my = fmaxf(my, fmaxf(y[8], y[9]));
          my = fmaxf(my, __shfl_xor_sync(~0u, my, 1));
          my = fmaxf(my, __shfl_xor_sync(~0u, my, 2));
#pragma unroll
          for (int i = 0; i < 10; i++) y[i] = ex2((y[i] - my) * L2E);
          float sy = ((y[0] + y[1]) + (y[2] + y[3])) + ((y[4] + y[5]) + (y[6] + y[7])) + (y[8] + y[9]);
          sy += __shfl_xor_sync(~0u, sy, 1);
          sy += __shfl_xor_sync(~0u, sy, 2);
          const float ry = rcp(sy);
          st_relaxed4(gptr(xhi, gh) + xo::PT, pack_bf16(y[2] * ry, y[3] * ry), pack_bf16(y[4] * ry, y[5] * ry), pack_bf16(y[6] * ry, y[7] * ry), pack_bf16(y[8] * ry, y[9] * ry));
          const uint32_t l12 = lv - (lv >> 2);
          st_relaxed1(gptr(xhi, gh - l12) + xo::PM, pack_bf16(y[0] * ry, y[1] * ry));
          st_relaxed4(gptr(xhi, xh + slot_off(s + 2)) + xo::PT, EMPTY, EMPTY, EMPTY, EMPTY);
          st_relaxed1(gptr(xhi, xh + slot_off(s + 2) - l12) + xo::PM, EMPTY);
        }
      }
    }
    if (more) {
      float acc[16];
      uint32_t tmp[4][4];
      const uint32_t xph = (s + 1) & 1;
      auto batch = [&](const uint32_t (&a)[24][4], int o) {
        wg_fence();
#pragma unroll
        for (int ks = 4; ks < 8; ks++) wgmma_m64n32_ss_ta(acc, wdesc<WG>(o, ks), xdesc<WG>(24 + ks), ks != 4);
#pragma unroll
        for (int ks = 0; ks < 4; ks++) wgmma_m64n32_rs(acc, tmp[ks], xdesc<WG>(24 + ks), 1);
#pragma unroll
        for (int ks = 0; ks < 24; ks++) wgmma_m64n32_rs(acc, a[ks], xdesc<WG>(ks), 1);
        wg_commit();
      };
#pragma unroll
      for (int ks = 0; ks < 4; ks++) ldsm_x4_t(tmp[ks], a_ws + 16384 + ks * 2048);
      if (J == 1 && WG == 1) { if (__builtin_expect(s >= 0, 1)) named_bar(8, 256); }
      mbar_wait<0>(sb + BAR_X + 8 * WG, xph);
      if (WG == 0) named_bar(12, 256);
      else if (J == 0 && __builtin_expect(s >= 0, 1)) named_bar(10, 256);
      batch(aW[1], 1);
      named_bar_arrive(WG ? 12 : 13, 256);
      wg_wait<0>();
      acc_fence(acc);
#pragma unroll
      for (int ks = 0; ks < 4; ks++) ldsm_x4_t(tmp[ks], a_ws + ks * 2048);
#pragma unroll
      for (int i = 0; i < 4; i++) sts128f(sb + OFF_FP + WG * 8192 + t16 + i * 512, make_float4(acc[4 * i], acc[4 * i + 1], acc[4 * i + 2], acc[4 * i + 3]));
      named_bar(WG ? 13 : 14, 256);
      batch(aW[0], 0);
      if (WG == 1) named_bar(14, 256);
      float4 oth[4];
#pragma unroll
      for (int i = 0; i < 4; i++) oth[i] = lds128f(sb + OFF_FP + (WG ^ 1) * 8192 + t16 + i * 512);
      wg_wait<0>();
      acc_fence(acc);
      uint32_t lt[4], ht[4];
#pragma unroll
      for (int i = 0; i < 4; i++) {
        const float4 o = oth[i];
        lt[i] = movmat(pack_bf16(acc[4 * i] + o.x, acc[4 * i + 1] + o.y)); ht[i] = movmat(pack_bf16(acc[4 * i + 2] + o.z, acc[4 * i + 3] + o.w));
      }
      const uint32_t tb = (J ? OFF_KT : OFF_QT) + xph * 8192;
      if (J == 0) {
        sts128(sb + tb + WG * 1024 + t16, make_uint4(lt[0], lt[1], ht[0], ht[1])); sts128(sb + tb + WG * 1024 + 512 + t16, make_uint4(lt[2], lt[3], ht[2], ht[3]));
      } else {
        const uint32_t a = sb + tb + WG * 1024 + (wq >> 1) * 512 + (wq & 1) * 8 + l16;
#pragma unroll
        for (int i = 0; i < 4; i++) sts64(a + i * 2048, lt[i], ht[i]);
      }
    }
    if (!more) break;
    if (WG == 1 && last_warp) {
      const uint32_t xph = (s + 1) & 1, tb = (J ? OFF_KT : OFF_QT) + xph * 8192;
      named_bar(11, 256);
      fence_async_smem();
        asm volatile("{.reg .pred p; elect.sync _|p, 0xffffffff;\n"
                     "@p cp.async.bulk.shared::cluster.shared::cta.mbarrier::complete_tx::bytes [%0], [%1], 8192, [%2];}"
                     ::"r"(rsb + tb), "r"(sb + tb), "r"(rsb + BAR_TOK + 8 * xph) : "memory");
      if (s + 2 < NSEG) {
        expect_elect(sb + BAR_TOK + 8 * (xph ^ 1), 8192); expect_elect(sb + BAR_X, 32768); expect_elect(sb + BAR_X + 8, 32768);
        if (J == 0) expect_elect(sb + BAR_EX, 2048);
      }
    } else {
      named_bar_arrive(11, 256);
    }
    if (__builtin_expect(s < 0, 0)) grid_wait(sb);
  }
  cp_async_wait_group<0>();
  if (J == 0) mbar_wait(sb + BAR_TOK + 8, 1);
}
#undef wq
#undef xm

template <int WG>
__device__ __forceinline__ void role_v(const ChainMaps& maps, const bf16* __restrict__ mem0, const uint32_t sb, const uint32_t xbase_lo, const uint32_t xbase_hi) {
  using namespace chain;
  const int h = blockIdx.x >> 2, j = blockIdx.x & 1;
  const uint32_t u16 = (threadIdx.x & 96) * 64 + (threadIdx.x & 31) * 16;
  const uint32_t t16 = keep(u16), l16 = keep((threadIdx.x & 31) * 16);
  const int wq0 = (threadIdx.x >> 5) & 3, lm = (threadIdx.x >> 3) & 3, lr = threadIdx.x & 7;
  const uint32_t a_wv = keep(WG * 32768 + ((lm >> 1) * 8 + lr) * 128 + (((2 * wq0 + (lm & 1)) ^ lr) << 4));
  const uint32_t a_wo = keep(OFF_WOR + (WG * 4 + wq0) * 8192 + ((lm >> 1) * 8 + lr) * 64 + (((2 * (j ^ 1) + (lm & 1)) ^ ((lr >> 1) & 3)) << 4));
  const uint32_t xhi = keep(xbase_hi + (t16 >> 16));
  const uint32_t xm = keep(xbase_lo + xo::MEM + WG * 8192 + u16);
  const uint32_t xvt = keep(xbase_lo + h * xo::HEAD + xo::VT + (8 * j + 2 * wq0 + WG) * 512 + (threadIdx.x & 31) * 16);
  const uint32_t xom = keep(xbase_lo + (j * 16 + WG * 4 + wq0) * xo::HEAD + xo::OM + (threadIdx.x & 31) * 16);
  const uint32_t xvm = keep(xbase_lo + h * xo::HEAD + xo::VM + (wq0 & 1) * 256 + (2 * j + (wq0 >> 1)) * 2048 + (threadIdx.x & 31) * 8);
  const int wq = __shfl_sync(0xffffffffu, wq0, 0);

  uint32_t aV[16][4];
  uint32_t aO[16][4];
  uint32_t rot[16][4];
  mbar_wait(sb + BAR_P, 0);
#pragma unroll
  for (int ks = 0; ks < 16; ks++) ldsm_x4_t(aV[ks], sb + a_wv + OFF_X + ks * 2048);
#pragma unroll
  for (int ks = 0; ks < 8; ks++) { ldsm_x4_t(aO[ks], sb + a_wo + ks * 1024); ldsm_x4_t(aO[8 + ks], sb + (a_wo ^ 32) + ks * 1024); }
  named_bar(0, 256);
  if (WG == 1 && wq == 3) {
    fence_async_smem();
    expect_elect(sb + BAR_X, 32768); expect_elect(sb + BAR_X + 8, 32768);
    issue_x(sb, &maps.x, 0, 0); issue_x(sb, &maps.x, 0, 1);
    if (l16 == 0) {
      sts32(sb + GRID_TGT + 4, xbase_lo + xo::MEM + (h * 2 + j) * 256); sts32(sb + GRID_TGT + 8, xbase_lo + xo::O + (h * 2 + j) * 128);
      mbar_expect_tx(sb + BAR_P + 16, 4 * 16384);
      for (int q = 0; q < 4; q++) tma_load_2d(sb + OFF_WOR + q * 16384, &maps.wo, h * 32, j * 2048 + 1024 + q * 256, sb + BAR_P + 16);
    }
    __syncwarp();
  }
  cluster_arrive();
  load_mem0(sb, mem0);
  mbar_wait(sb + BAR_P + 8, 0);
  auto load_v = [&]() {
#pragma unroll
    for (int ks = 0; ks < 16; ks++) ldsm_x4_t(rot[ks], sb + a_wv + OFF_WVR + ks * 2048);
  };
  load_v();
  cluster_wait();
  const uint32_t rsb = mapa(sb, j ^ 1);

  uint32_t tref = 0;
#pragma unroll 1
  for (int s = -1; s < NSEG; s++) {
    const bool more = __builtin_expect(s + 1 < NSEG, 1);
    const uint32_t zr = loop_zero(s);
    if (__builtin_expect(s >= 0, 1)) {
      if (__builtin_expect(s > 0, 1)) {
        const uint32_t dst = sb + OFF_MEM + WG * 8192 + t16;
        const char* src = gptr(xhi, xm + slot_off(s));
        uint32_t tries = zr;
#pragma unroll 1
        do {
          if (tries) gather_issue(dst + zr, src);
          KEEPALIVE(aV[0], zr);
          cp_async_wait_group<0>();
        } while (gather_incomplete(dst) && ++tries < POLL_LIMIT);
        named_bar(1 + WG, 128);
      }
      const uint32_t a_mem = sb + OFF_MEM + WG * 8192 + l16;
      float c[4][4];
#pragma unroll
      for (int i = 0; i < 4; i++) c[i][0] = c[i][1] = c[i][2] = c[i][3] = 0.f;
      uint32_t b[8][4];
#pragma unroll
      for (int p = 0; p < 4; p++) ldsm_x4_t(b[p], a_mem + p * 512);
#pragma unroll
      for (int p = 0; p < 16; p++) {
        if (p + 4 < 16) ldsm_x4_t(b[(p + 4) & 7], a_mem + (p + 4) * 512);
        if (p < 8) { mma16816(c[2 * (p & 1)], aV[2 * p], b[p & 7][0], b[p & 7][1]); mma16816(c[2 * (p & 1) + 1], aV[2 * p + 1], b[p & 7][2], b[p & 7][3]); }
        else { mma16816(c[2 * (p & 1)], rot[2 * p - 16], b[p & 7][0], b[p & 7][1]); mma16816(c[2 * (p & 1) + 1], rot[2 * p - 15], b[p & 7][2], b[p & 7][3]); }
        if ((p & 3) == 3 && p < 15) SFENCE(p);
      }
      const float4 own = make_float4((c[0][0] + c[1][0]) + (c[2][0] + c[3][0]), (c[0][1] + c[1][1]) + (c[2][1] + c[3][1]),
                                     (c[0][2] + c[1][2]) + (c[2][2] + c[3][2]), (c[0][3] + c[1][3]) + (c[2][3] + c[3][3]));
      if (WG == 1) sts128f(sb + OFF_VPX + (wq + zr) * 512 + l16, own);
      named_bar(3, 256);
      if (WG == 0) {
        const float4 o = lds128f(sb + OFF_VPX + (wq + zr) * 512 + l16);
        st_relaxed2(gptr(xhi, xvm + slot_off(s)), pack_bf16(own.x + o.x, own.y + o.y), pack_bf16(own.z + o.z, own.w + o.w));
      }
      tref = clock32() + D_O;
    }
    constexpr int NU = 2 - WG;
    uint4 pt0, pt1, v0[NU], v1[NU]; uint32_t pm0, pm1; uint2 vm[NU];
    auto fetch_p = [&]() {
      const uint32_t b = xvt - (xo::VT + (8 * j + WG) * 512 - WG * 4096) - (wq + zr) * 1024 + slot_off(s);
      pt0 = ld_relaxed4(gptr(xhi, b) + xo::PT); pt1 = ld_relaxed4(gptr(xhi, b) + xo::PT + 2048);
      const char* q = gptr(xhi, b - lv + (lv >> 2)) + xo::PM;
      pm0 = ld_relaxed1(q); pm1 = ld_relaxed1(q + 2048);
    };
    auto fetch_pv = [&]() {
      fetch_p();
#pragma unroll
      for (int u = 0; u < NU; u++) {
        const char* q = gptr(xhi, xvt + slot_off(s)) - WG * 512 - u * 2048;
        v0[u] = ld_relaxed4(q); v1[u] = ld_relaxed4(q + 512);
        vm[u] = ld_relaxed2(gptr(xhi, xvm + slot_off(s)) - u * 2048);
      }
    };
    auto token_pv = [&]() {
      const bool odd = lv & 16;
      char* op = gptr(xhi, lds32(sb + GRID_TGT + 8) + (s * SEG + WG * 16 + (lv >> 6)) * (HD * 2) + wq * 32 + (lv & 16) + ((lv >> 2) & 8));
      uint32_t tries = zr;
#pragma unroll 1
      do { if (tries) fetch_p(); } while (warp_incomplete(max(max(umax4(pt0), umax4(pt1)), max(pm0, pm1))) && ++tries < POLL_LIMIT);
      const uint32_t pa[4] = {pt0.x, pt1.x, pt0.y, pt1.y}, pb[4] = {pt0.z, pt1.z, pt0.w, pt1.w};
#pragma unroll
      for (int u = 0; u < NU; u++) {
        float o0[4] = {0.f, 0.f, 0.f, 0.f}, o1[4] = {0.f, 0.f, 0.f, 0.f};
        mma1688(o0, pm0, pm1, vm[u].x); mma1688(o1, pm0, pm1, vm[u].y);
        mma16816(o0, pa, v0[u].x, v0[u].y); mma16816(o1, pa, v1[u].x, v1[u].y);
        if (WG) { mma16816(o0, pb, v0[u].z, v0[u].w); mma16816(o1, pb, v1[u].z, v1[u].w); }
#pragma unroll
        for (int r = 0; r < 2; r++) {
          const uint32_t w0 = pack_bf16(o0[2 * r], o0[2 * r + 1]), w1 = pack_bf16(o1[2 * r], o1[2 * r + 1]);
          const uint32_t rv = __shfl_xor_sync(~0u, odd ? w0 : w1, 1);
          *(uint2*)(op + r * 8 * HD * 2 - u * 64) = odd ? make_uint2(rv, w1) : make_uint2(w0, rv);
        }
      }
    };
    if (!more) { named_bar(3, 256); if (WG == 1 || wq >= 2) { fetch_pv(); token_pv(); } break; }
    {
      {
        float acc[16];
        mbar_wait<0>(sb + BAR_X + 8 * WG, (s + 1) & 1);
        wg_fence();
#pragma unroll
        for (int ks = 0; ks < 16; ks++) wgmma_m64n32_rs(acc, rot[ks], xdesc<WG>(16 + ks), ks != 0);
        wg_commit();
#pragma unroll
        for (int ks = 0; ks < 16; ks++) wgmma_m64n32_rs(acc, aV[ks], xdesc<WG>(ks), 1);
        wg_commit();
        if (__builtin_expect(s >= 0, 1)) {
          st_relaxed4(gptr(xhi, xvt + slot_off(s + 2)), EMPTY, EMPTY, EMPTY, EMPTY);
          if (WG == 0) st_relaxed2(gptr(xhi, xvm + slot_off(s + 2)), EMPTY, EMPTY);
          if (WG == 0 && wq == 1) expect_elect(sb + BAR_EX, 512);
        } else {
          mbar_wait(sb + BAR_P + 16, 0);
        }
        wg_wait<1>();
#pragma unroll
        for (int ks = 0; ks < O_EARLY; ks++) ldsm_x4_t(rot[ks], sb + (ks < 8 ? a_wo : (a_wo + zr) ^ 32) + (ks & 7) * 1024);
        wg_wait<0>();
        acc_fence(acc);
        constexpr int K = WG * 2, G = 2 - K;
        sts128f(sb + OFF_RED + WG * 1024 + t16, make_float4(acc[G], acc[G + 1], acc[4 + G], acc[5 + G]));
        sts128f(sb + OFF_RED + WG * 1024 + 512 + t16, make_float4(acc[8 + G], acc[9 + G], acc[12 + G], acc[13 + G]));
        named_bar(3, 256);
        const float4 o0 = lds128f(sb + OFF_RED + (WG ^ 1) * 1024 + t16), o1 = lds128f(sb + OFF_RED + (WG ^ 1) * 1024 + 512 + t16);
        st_relaxed4(gptr(xhi, xvt + slot_off(s + 1)),
                    pack_bf16(acc[K] + o0.x, acc[K + 1] + o0.y), pack_bf16(acc[4 + K] + o0.z, acc[5 + K] + o0.w),
                    pack_bf16(acc[8 + K] + o1.x, acc[9 + K] + o1.y), pack_bf16(acc[12 + K] + o1.z, acc[13 + K] + o1.w));
      }
      auto next_x = [&]() {
        if (WG == 1 && wq == 3 && s + 2 < NSEG) {
          expect_elect(sb + BAR_X, 32768); expect_elect(sb + BAR_X + 8, 32768);
          issue_x(sb, &maps.x, s + 2, 0); issue_x(sb, &maps.x, s + 2, 1);
        }
      };
      if (__builtin_expect(s >= 0, 1)) {
#pragma unroll
        for (int ks = O_EARLY; ks < O_PRE; ks++) ldsm_x4_t(rot[ks], sb + (ks < 8 ? a_wo : (a_wo + zr) ^ 32) + (ks & 7) * 1024);
        const char* po = gptr(xhi, xom + slot_off(s));
        WAIT_UNTIL(tref, aV[0]);
        uint4 o[8];
#pragma unroll
        for (int i = 0; i < 4; i++) o[i] = ld_relaxed4(po + i * 2048);
#pragma unroll
        for (int i = 0; i < 4; i++) o[4 + i] = ld_relaxed4(po + 8 * xo::HEAD + i * 2048);
#pragma unroll
        for (int ks = O_PRE; ks < 16; ks++) ldsm_x4_t(rot[ks], sb + (ks < 8 ? a_wo : (a_wo + zr) ^ 32) + (ks & 7) * 1024);
        float d[2][2][4];
#pragma unroll
        for (int i = 0; i < 2; i++)
#pragma unroll
          for (int q = 0; q < 2; q++) { d[i][q][0] = d[i][q][1] = d[i][q][2] = d[i][q][3] = 0.f; }
        uint32_t tries = zr;
#pragma unroll 1
        do {
          if (tries) {
            const bool both = warp_incomplete(max(max(umax4(o[4]), umax4(o[5])), max(umax4(o[6]), umax4(o[7]))));
#pragma unroll
            for (int i = 0; i < 4; i++) o[i] = ld_relaxed4(po + i * 2048);
            if (both) {
#pragma unroll
              for (int i = 0; i < 4; i++) o[4 + i] = ld_relaxed4(po + 8 * xo::HEAD + i * 2048);
            }
          }
          KEEPALIVE(aV[0], zr);
        } while (warp_incomplete(max(max(umax4(o[0]), umax4(o[1])), max(umax4(o[2]), umax4(o[3])))) && ++tries < POLL_LIMIT);
#pragma unroll
        for (int i = 0; i < 4; i++) {
          mma16816(d[0][0], aO[2 * i], o[i].x, o[i].y); mma16816(d[1][0], aO[8 + 2 * i], o[i].x, o[i].y);
          mma16816(d[0][1], aO[2 * i + 1], o[i].z, o[i].w); mma16816(d[1][1], aO[9 + 2 * i], o[i].z, o[i].w);
        }
        tries = zr;
#pragma unroll 1
        do {
          if (tries) {
#pragma unroll
            for (int i = 0; i < 4; i++) o[4 + i] = ld_relaxed4(po + 8 * xo::HEAD + i * 2048);
          }
        } while (warp_incomplete(max(max(umax4(o[4]), umax4(o[5])), max(umax4(o[6]), umax4(o[7])))) && ++tries < POLL_LIMIT);
#pragma unroll
        for (int i = 0; i < 4; i++) {
          mma16816(d[0][0], rot[2 * i], o[4 + i].x, o[4 + i].y); mma16816(d[1][0], rot[8 + 2 * i], o[4 + i].x, o[4 + i].y);
          mma16816(d[0][1], rot[2 * i + 1], o[4 + i].z, o[4 + i].w); mma16816(d[1][1], rot[9 + 2 * i], o[4 + i].z, o[4 + i].w);
        }
        const uint32_t rd = sb + OFF_RED + (WG ^ 1) * 1024 + t16;
        sts128f(rd, make_float4(d[0][0][0] + d[0][1][0], d[0][0][1] + d[0][1][1], d[0][0][2] + d[0][1][2], d[0][0][3] + d[0][1][3]));
        sts128f(rd + 512, make_float4(d[1][0][0] + d[1][1][0], d[1][0][1] + d[1][1][1], d[1][0][2] + d[1][1][2], d[1][0][3] + d[1][1][3]));
        auto next_gather = [&](int id) {
          mbar_wait(sb + BAR_EX, s & 1);
#pragma unroll
          for (int ks = 0; ks < V_PRE; ks++) ldsm_x4_t(rot[ks], sb + a_wv + OFF_WVR + ks * 2048);
          gather_issue(sb + OFF_MEM + WG * 8192 + t16 + (rot[V_PRE - 1][3] & zr), gptr(xhi, xm + slot_off(s + 1)));
          SFENCE(id);
        };
        if (WG == 1 || wq >= 2) {
          named_bar_arrive(7, 256);
          fetch_pv();
          next_x();
          next_gather(30);
          token_pv();
        } else {
          uint32_t mp = lds32(sb + GRID_TGT + 4) + (lv >> 2);
          named_bar(7, 256);
          float4 p[8];
#pragma unroll
          for (int i = 0; i < 8; i++) p[i] = lds128f(sb + OFF_RED + lv + wq * 512 + i * 1024);
          float4 r;
          r.x = ((p[0].x + p[1].x) + (p[2].x + p[3].x)) + ((p[4].x + p[5].x) + (p[6].x + p[7].x));
          r.y = ((p[0].y + p[1].y) + (p[2].y + p[3].y)) + ((p[4].y + p[5].y) + (p[6].y + p[7].y));
          r.z = ((p[0].z + p[1].z) + (p[2].z + p[3].z)) + ((p[4].z + p[5].z) + (p[6].z + p[7].z));
          r.w = ((p[0].w + p[1].w) + (p[2].w + p[3].w)) + ((p[4].w + p[5].w) + (p[6].w + p[7].w));
          if (wq == 0) st_async4(rsb + OFF_RX + lv, __float_as_uint(r.x), __float_as_uint(r.y), __float_as_uint(r.z), __float_as_uint(r.w), rsb + BAR_EX);
          else {
            char* pp = gptr(xhi, mp + slot_off(s + 1));
            mbar_wait(sb + BAR_EX, s & 1);
            const float4 q = lds128f(sb + OFF_RX + l16);
            st_relaxed1(pp, pack_bf16(r.x + q.x, r.y + q.y)); st_relaxed1(pp + 128, pack_bf16(r.z + q.z, r.w + q.w));
            pp = gptr(xhi, mp + slot_off(s + 3));
            st_relaxed1(pp, EMPTY); st_relaxed1(pp + 128, EMPTY);
          }
          next_gather(31);
        }
#pragma unroll
        for (int ks = V_PRE; ks < 16; ks++) ldsm_x4_t(rot[ks], sb + a_wv + OFF_WVR + ks * 2048);
      } else {
        load_v();
        next_x();
        grid_wait(sb);
      }
    }
  }
}

__global__ void __launch_bounds__(256, 1) __cluster_dims__(2, 1, 1)
chain_kernel(const __grid_constant__ ChainMaps maps, const bf16* __restrict__ mem0, const uint64_t xbase) {
  using namespace chain;
  extern __shared__ uint8_t smem_raw[];
  uint32_t sb = smem_u32(smem_raw);
  PIN(sb);
  if ((sb & 0x3FFFF) != SB_LO) __trap();
  const int tid = threadIdx.x;
  const int h = blockIdx.x >> 2, role = (blockIdx.x >> 1) & 1, j = blockIdx.x & 1;
  if (tid == 0) {
    for (int i = 0; i < 9; i++) mbar_init(sb + OFF_BAR + 8 * i, 1);
    asm volatile("fence.mbarrier_init.release.cluster;" ::: "memory");
    if (role == 0) {
      const CUtensorMap* wm = j ? &maps.wk : &maps.wq;
      mbar_expect_tx(sb + BAR_P, 6 * 16384);
      for (int c = 0; c < 3; c++)
        for (int q = 0; q < 2; q++) tma_load_2d(sb + OFF_X + (q * 3 + c) * 16384, wm, h * DH + q * 64, q * 512 + c * 128, sb + BAR_P);
      mbar_expect_tx(sb + BAR_P + 8, 4 * 16384);
      for (int c = 0; c < 2; c++)
        for (int q = 0; q < 2; q++) tma_load_2d(sb + OFF_X + (6 + q * 2 + c) * 16384, wm, h * DH + (q ^ 1) * 64, q * 512 + c * 128, sb + BAR_P + 8);
      mbar_expect_tx(sb + BAR_P + 24, 4 * 16384);
      for (int q = 0; q < 2; q++)
        for (int o = 0; o < 2; o++) tma_load_2d(sb + OFF_WS + (q * 2 + o) * 16384, wm, h * DH + (q ^ o) * 64, q * 512 + 384, sb + BAR_P + 24);
    } else {
      mbar_expect_tx(sb + BAR_P, 8 * 16384);
      for (int q = 0; q < 4; q++) tma_load_2d(sb + OFF_X + q * 16384, &maps.wv, h * DH + j * 64, (q >> 1) * 512 + (q & 1) * 128, sb + BAR_P);
      for (int q = 0; q < 4; q++) tma_load_2d(sb + OFF_WOR + q * 16384, &maps.wo, h * 32, j * 2048 + q * 256, sb + BAR_P);
      mbar_expect_tx(sb + BAR_P + 8, 4 * 16384);
      for (int q = 0; q < 4; q++) tma_load_2d(sb + OFF_WVR + q * 16384, &maps.wv, h * DH + j * 64, (q >> 1) * 512 + 256 + (q & 1) * 128, sb + BAR_P + 8);
    }
  }
  for (int r = 0; r < RING; r++) {
    char* p = (char*)xbase + r * xo::SLOT;
    const int wq = (tid >> 5) & 3;
    if (role == 1) st_relaxed4(p + h * xo::HEAD + xo::VT + (8 * j + 2 * wq + (tid >> 7)) * 512 + (tid & 31) * 16, EMPTY, EMPTY, EMPTY, EMPTY);
    else if (j == 0) st_relaxed4(p + h * xo::HEAD + (tid >> 6) * 2048 + (tid & 63) * 16, EMPTY, EMPTY, EMPTY, EMPTY);
    else {
      st_relaxed4(p + h * xo::HEAD + (tid >> 6) * 2048 + 1024 + (tid & 63) * 16, EMPTY, EMPTY, EMPTY, EMPTY);
      if (tid < 32) st_relaxed4(p + xo::MEM + h * 512 + tid * 16, EMPTY, EMPTY, EMPTY, EMPTY);
    }
  }
  __syncthreads();
  if (tid == 0) {
    __threadfence();
    sts32(sb + GRID_TGT, (atomicAdd(&g_epoch, 1u) & ~127u) + 128u);
  }
  const uint32_t xlo = (uint32_t)xbase, xhi = (uint32_t)(xbase >> 32);
  const int wg = __shfl_sync(0xffffffffu, tid >> 7, 0);
  if (role == 0) {
    if (j == 0) { if (wg == 0) role_a<0, 0>(maps, mem0, sb, xlo, xhi); else role_a<0, 1>(maps, mem0, sb, xlo, xhi); }
    else { if (wg == 0) role_a<1, 0>(maps, mem0, sb, xlo, xhi); else role_a<1, 1>(maps, mem0, sb, xlo, xhi); }
  } else {
    if (wg == 0) role_v<0>(maps, mem0, sb, xlo, xhi); else role_v<1>(maps, mem0, sb, xlo, xhi);
  }
  asm volatile("griddepcontrol.launch_dependents;");
  __syncwarp();
  cluster_arrive();
  cluster_wait();
}

struct BMaps { CUtensorMap q, k, v, out, k8; };

#define B_PRAGMA2(x) _Pragma(#x)
#define B_PRAGMA(x) B_PRAGMA2(x)
#define B_UNROLL 4
#define B_SLEEP 200
namespace bp {
constexpr int U_PITCH = (2048 + 128) * 2 + 16;
constexpr int KR_WORDS = 1048;
constexpr int KR_PITCH = 8704;
constexpr int OFF_U = 0;
constexpr int OFF_KR = (8 * U_PITCH + 127) / 128 * 128;
constexpr int Q_OFF = 4352;
constexpr int OFF_BAR = OFF_KR + 8 * KR_PITCH;
constexpr int GROUP_BYTES = OFF_BAR + 128;
constexpr int SMEM = 2 * GROUP_BYTES + 128;
constexpr int NTASK = DM / 8;
static_assert(Q_OFF >= 4224 && Q_OFF + 4096 <= KR_PITCH, "staging does not fit");
}

__device__ __forceinline__ uint32_t bmul2(uint32_t a, uint32_t b) { uint32_t r; asm("mul.rn.bf16x2 %0, %1, %2;" : "=r"(r) : "r"(a), "r"(b)); return r; }
__device__ __forceinline__ uint32_t badd2(uint32_t a, uint32_t b) { uint32_t r; asm("add.rn.bf16x2 %0, %1, %2;" : "=r"(r) : "r"(a), "r"(b)); return r; }
__device__ __forceinline__ void stsm_x4_t(uint32_t addr, uint32_t r0, uint32_t r1, uint32_t r2, uint32_t r3) {
  asm volatile("stmatrix.sync.aligned.m8n8.x4.trans.shared.b16 [%0], {%1,%2,%3,%4};" ::"r"(addr), "r"(r0), "r"(r1), "r"(r2), "r"(r3) : "memory");
}

__device__ __forceinline__ void mbar_wait_sleep(uint32_t bar, uint32_t parity) {
  int guard = 0;
  while (!mbar_try(bar, parity)) { __nanosleep(B_SLEEP); if (++guard > (1 << 22)) __trap(); }
}

__device__ __forceinline__ void bpart_body(const BMaps& maps, const bf16* __restrict__ shift_k, const bf16* __restrict__ ssm_k,
                                           const bf16* __restrict__ ssm_D, int first, int stride, int end) {
  using namespace bp;
  extern __shared__ uint8_t smem_all[];
  const int grp = __shfl_sync(0xffffffffu, threadIdx.x >> 8, 0);
  const int tid = threadIdx.x & 255, lane = tid & 31, g = lane >> 2, t = lane & 3;
  const int w = __shfl_sync(0xffffffffu, tid >> 5, 0);
  const uint32_t sb = ((smem_u32(smem_all) + 127) & ~127u) + grp * GROUP_BYTES;
  const uint32_t bar_kv = sb + OFF_BAR + 8 * w, bar_q = sb + OFF_BAR + 64 + 8 * w;
  if (lane == 0) { mbar_init(bar_kv, 1); mbar_init(bar_q, 1); asm volatile("fence.mbarrier_init.release.cluster;" ::: "memory"); }
  named_bar(1 + grp, 256);
  if (grp == 1) named_bar_arrive(3, 512);
  const int lm = lane >> 3, lr = lane & 7;
  uint32_t ph = 0;
  for (int task = first + grp; task < end; task += stride, ph ^= 1) {
    const int d0 = task * 8;
    if (lane == 0) {
      const uint32_t kr = sb + OFF_KR + w * KR_PITCH;
      mbar_expect_tx(bar_kv, 2 * 4096 + 128);
      tma_load_2d(kr, &maps.k, d0, w * 256 - 8, bar_kv);
      tma_load_2d(kr + 4096, &maps.k8, d0, w * 256 + 248, bar_kv);
      bulk_wait_read<0>();
      tma_load_2d(kr + Q_OFF, &maps.v, d0, w * 256, bar_kv);
    }
    uint4 x[8];
    {
      const uint4* kf = (const uint4*)(ssm_k + (size_t)(d0 + w) * S_LEN);
#pragma unroll
      for (int it = 0; it < 8; it++) x[it] = __ldg(kf + it * 32 + lane);
    }
    uint32_t sk[4];
    {
      const uint4 a = __ldg((const uint4*)(shift_k + (d0 + 2 * t) * 4));
      sk[0] = __byte_perm(a.x, a.z, 0x5410); sk[1] = __byte_perm(a.x, a.z, 0x7632);
      sk[2] = __byte_perm(a.y, a.w, 0x5410); sk[3] = __byte_perm(a.y, a.w, 0x7632);
    }
    const uint32_t dpair = __ldg((const uint32_t*)(ssm_D + d0) + t);
    if (tid < 128) sts128(sb + OFF_U + (tid >> 4) * U_PITCH + (tid & 15) * 16, make_uint4(0, 0, 0, 0));
    mbar_wait_sleep(bar_kv, ph);
    {
      const uint32_t ka = sb + OFF_KR + w * KR_PITCH + (g + 8) * 16 + t * 4, va = sb + OFF_KR + w * KR_PITCH + Q_OFF + g * 16 + t * 4;
B_PRAGMA(unroll B_UNROLL)
      for (int i = 0; i < 8; i++) {
        uint32_t r[4];
#pragma unroll
        for (int b = 0; b < 4; b++) {
          const uint32_t o = (i * 32 + b * 8) * 16;
          uint32_t acc = bmul2(lds32(ka + o - 48), sk[3]);
          acc = badd2(acc, bmul2(lds32(ka + o - 32), sk[2]));
          acc = badd2(acc, bmul2(lds32(ka + o - 16), sk[1]));
          acc = badd2(acc, bmul2(lds32(ka + o), sk[0]));
          r[b] = bmul2(acc, lds32(va + o));
        }
        const int ch = 16 + w * 32 + i * 4 + lm;
        stsm_x4_t(sb + OFF_U + lr * U_PITCH + ((ch ^ ((ch >> 3) & 1)) << 4), r[0], r[1], r[2], r[3]);
      }
    }
    __syncwarp();
    {
      const uint32_t c0 = sb + OFF_KR + w * KR_PITCH, c1 = c0 + (KR_WORDS + 16) * 4;
      uint32_t carry = 0;
#pragma unroll
      for (int it = 0; it < 8; it++) {
        const int blk = it * 32 + lane;
        uint32_t prev = __shfl_up_sync(0xffffffffu, x[it].w, 1);
        if (lane == 0) prev = carry;
        carry = __shfl_sync(0xffffffffu, x[it].w, 31);
        sts128(c0 + (1028 - 4 * blk) * 4, make_uint4(__byte_perm(x[it].w, 0, 0x1032), __byte_perm(x[it].z, 0, 0x1032),
                                                     __byte_perm(x[it].y, 0, 0x1032), __byte_perm(x[it].x, 0, 0x1032)));
        sts128(c1 + (1028 - 4 * blk) * 4, make_uint4(__byte_perm(x[it].w, x[it].z, 0x7610), __byte_perm(x[it].z, x[it].y, 0x7610),
                                                     __byte_perm(x[it].y, x[it].x, 0x7610), __byte_perm(x[it].x, prev, 0x7610)));
      }
      if (lane < 4) { sts128(c0 + (1032 + 4 * lane) * 4, make_uint4(0, 0, 0, 0)); sts128(c1 + (1032 + 4 * lane) * 4, make_uint4(0, 0, 0, 0)); }
      __syncwarp();
    }
    named_bar(1 + grp, 256);
    named_bar(3 + grp, 512);
    float acc[16][4];
#pragma unroll
    for (int jn = 0; jn < 16; jn++) { acc[jn][0] = acc[jn][1] = acc[jn][2] = acc[jn][3] = 0.f; }
    {
      const uint32_t ub = sb + OFF_U + w * U_PITCH;
      const uint32_t kw = sb + OFF_KR + w * KR_PITCH + (((g & 1) ? 0 : KR_WORDS + 16) + ((((g & 1) ? 2063 : 2062) - (g - 2 * t)) >> 1)) * 4;
#pragma unroll 1
      for (int d0s = 0; d0s < 8; d0s++) {
        const int a0 = 8 - d0s + lr;
        const uint32_t uf = ub + (((2 * a0 + (lm & 1)) ^ ((a0 >> 2) & 1)) << 4);
        const uint32_t kd = kw - 32 * d0s;
        uint32_t A[3][4];
        A[0][0] = lds32v(kd); A[0][1] = lds32v(kd - 16); A[0][2] = lds32v(kd + 16); A[0][3] = lds32v(kd);
        uint32_t F[16][2];
#pragma unroll
        for (int m = 0; m < 16; m++) ldsm_x2(F[m][0], F[m][1], uf + m * 256);
#pragma unroll
        for (int i = 0; i < 16; i++) {
          if (i + 1 < 16) {
            A[(i + 1) % 3][0] = lds32v(kd - 256 * (i + 1)); A[(i + 1) % 3][1] = lds32v(kd - 256 * (i + 1) - 16);
            A[(i + 1) % 3][2] = lds32v(kd - 256 * (i + 1) + 16); A[(i + 1) % 3][3] = lds32v(kd - 256 * (i + 1));
          }
#pragma unroll
          for (int jn = 15; jn >= i; jn--) mma16816(acc[jn], A[i % 3], F[jn - i][0], F[jn - i][1]);
        }
      }
    }
    named_bar_arrive(3 + (grp ^ 1), 512);
    const uint32_t qs = sb + OFF_KR + w * KR_PITCH + Q_OFF;
    __syncwarp();
    fence_async_smem();
    __syncwarp();
    if (lane == 0) { mbar_expect_tx(bar_q, 4096); tma_load_2d(qs, &maps.q, d0, w * 256, bar_q); }
    {
      const uint32_t ya = sb + OFF_KR + w * (KR_PITCH + 16) + (((lm >> 1) * 8 + lr) * 32) + (lm & 1) * 16;
#pragma unroll
      for (int jn = 0; jn < 16; jn += 2)
        stsm_x4_t(ya + jn * 256, pack_bf16(acc[jn][0], acc[jn][1]), pack_bf16(acc[jn][2], acc[jn][3]),
                  pack_bf16(acc[jn + 1][0], acc[jn + 1][1]), pack_bf16(acc[jn + 1][2], acc[jn + 1][3]));
    }
    named_bar(1 + grp, 256);
    mbar_wait_sleep(bar_q, ph);
    {
      const uint32_t ya = sb + OFF_KR + lr * (KR_PITCH + 16) + (w * 256 + lm * 8) * 2;
      const uint32_t qa = qs + g * 16 + t * 4;
B_PRAGMA(unroll B_UNROLL)
      for (int i = 0; i < 8; i++) {
        uint32_t y[4], u[4];
        ldsm_x4_t(y, ya + i * 64);
        const int ch = 16 + w * 32 + i * 4 + lm;
        ldsm_x4_t(u, sb + OFF_U + lr * U_PITCH + ((ch ^ ((ch >> 3) & 1)) << 4));
#pragma unroll
        for (int b = 0; b < 4; b++) {
          const uint32_t a = qa + (i * 32 + b * 8) * 16;
          sts32(a, bmul2(lds32(a), badd2(y[b], bmul2(u[b], dpair))));
        }
      }
      fence_async_smem();
      __syncwarp();
      if (lane == 0) { tma_store_2d(&maps.out, qs, DM + d0, w * 256); bulk_commit(); }
    }
    named_bar(1 + grp, 256);
  }
  if (lane == 0) bulk_wait<0>();
}

__global__ void __launch_bounds__(512, 1) __cluster_dims__(2, 1, 1)
bpart_kernel(const __grid_constant__ BMaps maps, const bf16* __restrict__ shift_k, const bf16* __restrict__ ssm_k, const bf16* __restrict__ ssm_D, int end) {
  bpart_body(maps, shift_k, ssm_k, ssm_D, blockIdx.x * 2, gridDim.x * 2, end);
}

struct GemmMaps {
  CUtensorMap o;
  CUtensorMap w;
  CUtensorMap c;
};
namespace k3 {
constexpr int STAGES = 5;
constexpr int W_BYTES = 2 * 8192, O_BYTES = K3_N * 128, STAGE_BYTES = W_BYTES + O_BYTES;
constexpr int TT = (S_LEN + K3_N - 1) / K3_N, NGEMM = TT * (DM / 128), NB = 128 - NGEMM, KSTEPS = HD / 64;
constexpr int SMEM_G = STAGES * STAGE_BYTES + 1024 + 256;
constexpr int SMEM = SMEM_G > bp::SMEM ? SMEM_G : bp::SMEM;
static_assert(STAGE_BYTES % 1024 == 0, "swizzle atoms");
}

__global__ void __launch_bounds__(512, 1)
tail_kernel(const __grid_constant__ GemmMaps maps, const __grid_constant__ BMaps bmaps, const bf16* __restrict__ shift_k,
            const bf16* __restrict__ ssm_k, const bf16* __restrict__ ssm_D) {
  using namespace k3;
  if (blockIdx.x < NB) {
    bpart_body(bmaps, shift_k, ssm_k, ssm_D, bp::NTASK - 2 * NB + 2 * blockIdx.x, bp::NTASK, bp::NTASK);
    return;
  }
  extern __shared__ uint8_t smem_raw[];
  const uint32_t sbase = (smem_u32(smem_raw) + 1023) & ~1023u;
  const uint32_t bars = sbase + STAGES * STAGE_BYTES;
  const int tid = threadIdx.x, warp = tid >> 5;
  const int tt = (blockIdx.x - NB) % TT, ct = (blockIdx.x - NB) / TT;

  if (tid == 0) {
    for (int s = 0; s < STAGES; s++) { mbar_init(bars + 8 * s, 1); mbar_init(bars + 8 * (STAGES + s), 2); }
    asm volatile("fence.mbarrier_init.release.cluster;" ::: "memory");
  }
  __syncthreads();

  if (warp >= 8) {
    if (tid == 256) {
      tma_prefetch_desc(&maps.o);
      for (int k = 0; k < STAGES; k++) {
        const uint32_t full = bars + 8 * k, sa = sbase + k * STAGE_BYTES;
        mbar_expect_tx(full, STAGE_BYTES);
#pragma unroll
        for (int j = 0; j < 2; j++) tma_load_2d(sa + j * 8192, &maps.w, ct * 128 + j * 64, k * 64, full);
      }
      asm volatile("griddepcontrol.wait;" ::: "memory");
      int stage = 0; uint32_t ph = 1;
      for (int k = 0; k < KSTEPS; k++) {
        mbar_wait(bars + 8 * (STAGES + stage), ph);
        const uint32_t full = bars + 8 * stage, sa = sbase + stage * STAGE_BYTES;
        const bool pre = k < STAGES;
        if (!pre) mbar_expect_tx(full, STAGE_BYTES);
        tma_load_2d(sa + W_BYTES, &maps.o, k * 64, tt * K3_N, full);
        if (!pre) {
#pragma unroll
          for (int j = 0; j < 2; j++) tma_load_2d(sa + j * 8192, &maps.w, ct * 128 + j * 64, k * 64, full);
        }
        if (++stage == STAGES) { stage = 0; ph ^= 1; }
      }
    }
  } else {
    const int wg = warp >> 2, lane = tid & 31, wq = warp & 3;
    int stage = 0; uint32_t ph = 0;
    float acc[K3_N / 2];
    int prev = -1;
    for (int k = 0; k < KSTEPS; k++) {
      mbar_wait(bars + 8 * stage, ph);
      const uint32_t sa = sbase + stage * STAGE_BYTES;
      wg_fence();
#pragma unroll
      for (int kk = 0; kk < 4; kk++) {
        const uint64_t da = make_desc(sa + wg * 8192 + kk * 2048, 16, 1024, 1);
        const uint64_t db = make_desc(sa + W_BYTES + kk * 32, 16, 1024, 1);
        wgmma_k3_ss_ta(acc, da, db, (k | kk) != 0);
      }
      wg_commit();
      if (prev >= 0) { wg_wait<1>(); if ((tid & 127) == 0) mbar_arrive(bars + 8 * (STAGES + prev)); }
      prev = stage;
      if (++stage == STAGES) { stage = 0; ph ^= 1; }
    }
    wg_wait<0>();
#pragma unroll
    for (int i = 0; i < K3_N / 2; i++) asm volatile("" : "+f"(acc[i]) :: "memory");
    named_bar(1, 256);
    const uint32_t ebuf = sbase + wg * STAGE_BYTES;
    const uint32_t ea = ebuf + ((lane >> 4) * 8 + (lane & 7)) * 128 + (((2 * wq + ((lane >> 3) & 1)) ^ (lane & 7)) << 4);
#pragma unroll
    for (int i = 0; i < K3_N / 8; i += 2) {
      const int i1 = i + 1 < K3_N / 8 ? i + 1 : i;
      stsm_x4_t(ea + i * 1024, pack_bf16(acc[4 * i], acc[4 * i + 1]), pack_bf16(acc[4 * i + 2], acc[4 * i + 3]),
                pack_bf16(acc[4 * i1], acc[4 * i1 + 1]), pack_bf16(acc[4 * i1 + 2], acc[4 * i1 + 3]));
    }
    fence_async_smem();
    named_bar(2 + wg, 128);
    if ((tid & 127) == 0) {
      tma_store_2d(&maps.c, ebuf, ct * 128 + wg * 64, tt * K3_N);
      bulk_commit();
      bulk_wait<0>();
    }
  }
}

typedef CUresult (*EncodeFn)(CUtensorMap*, CUtensorMapDataType, cuuint32_t, void*, const cuuint64_t*, const cuuint64_t*,
                             const cuuint32_t*, const cuuint32_t*, CUtensorMapInterleave, CUtensorMapSwizzle,
                             CUtensorMapL2promotion, CUtensorMapFloatOOBfill);

void make_map(EncodeFn enc, CUtensorMap* m, const void* ptr, uint64_t cols, uint64_t rows, uint64_t pitch_elems,
              uint32_t box_cols, uint32_t box_rows, CUtensorMapSwizzle swz,
              CUtensorMapL2promotion promo = CU_TENSOR_MAP_L2_PROMOTION_L2_128B) {
  cuuint64_t dims[2] = {cols, rows};
  cuuint64_t strides[1] = {pitch_elems * 2};
  cuuint32_t box[2] = {box_cols, box_rows};
  cuuint32_t es[2] = {1, 1};
  enc(m, CU_TENSOR_MAP_DATA_TYPE_BFLOAT16, 2, const_cast<void*>(ptr), dims, strides, box, es, CU_TENSOR_MAP_INTERLEAVE_NONE, swz,
      promo, CU_TENSOR_MAP_FLOAT_OOB_FILL_NONE);
}

void make_map_nd(EncodeFn enc, CUtensorMap* m, const void* ptr, int rank, const uint64_t* dims, const uint64_t* strides_elems,
                 const uint32_t* box, CUtensorMapSwizzle swz) {
  cuuint64_t d[5], st[4]; cuuint32_t b[5], es[5];
  for (int i = 0; i < rank; i++) { d[i] = dims[i]; b[i] = box[i]; es[i] = 1; if (i) st[i - 1] = strides_elems[i] * 2; }
  enc(m, CU_TENSOR_MAP_DATA_TYPE_BFLOAT16, rank, const_cast<void*>(ptr), d, st, b, es, CU_TENSOR_MAP_INTERLEAVE_NONE, swz,
      CU_TENSOR_MAP_L2_PROMOTION_L2_128B, CU_TENSOR_MAP_FLOAT_OOB_FILL_NONE);
}

}

extern "C" void kernel_launch(void* const* d_in, const int* in_sizes, int n_in, void* d_out, int out_size) {
  (void)in_sizes; (void)n_in; (void)out_size;
  const bf16* x = (const bf16*)d_in[0];
  const bf16* mem0 = (const bf16*)d_in[1];
  const bf16* Wq = (const bf16*)d_in[2];
  const bf16* Wk = (const bf16*)d_in[3];
  const bf16* Wv = (const bf16*)d_in[4];
  const bf16* Wo = (const bf16*)d_in[5];
  const bf16* Bq = (const bf16*)d_in[7];
  const bf16* Bk = (const bf16*)d_in[8];
  const bf16* Bv = (const bf16*)d_in[9];
  const bf16* shift_k = (const bf16*)d_in[10];
  const bf16* ssm_k = (const bf16*)d_in[11];
  const bf16* ssm_D = (const bf16*)d_in[12];
  bf16* out = (bf16*)d_out;

  static EncodeFn enc = nullptr;
  static uint64_t xbase;
  static int nsm = 132;
  static cudaStream_t s1;
  static cudaEvent_t ev_fork, ev_join;
  if (!enc) {
    cudaDriverEntryPointQueryResult qr;
    void* fn = nullptr;
    cudaGetDriverEntryPoint("cuTensorMapEncodeTiled", &fn, cudaEnableDefault, &qr);
    enc = (EncodeFn)fn;
    void* ps = nullptr;
    cudaGetSymbolAddress(&ps, g_scratch);
    xbase = (uint64_t)ps;
    if ((xbase >> 32) != ((xbase + xo::BYTES - 1) >> 32)) xbase += xo::BYTES;
    cudaFuncSetAttribute(tail_kernel, cudaFuncAttributeMaxDynamicSharedMemorySize, k3::SMEM);
    cudaFuncSetAttribute(chain_kernel, cudaFuncAttributeMaxDynamicSharedMemorySize, chain::SMEM);
    cudaFuncSetAttribute(bpart_kernel, cudaFuncAttributeMaxDynamicSharedMemorySize, bp::SMEM);
    cudaStreamCreateWithFlags(&s1, cudaStreamNonBlocking);
    cudaEventCreateWithFlags(&ev_fork, cudaEventDisableTiming);
    cudaEventCreateWithFlags(&ev_join, cudaEventDisableTiming);
    int dev = 0; cudaGetDevice(&dev);
    cudaDeviceGetAttribute(&nsm, cudaDevAttrMultiProcessorCount, dev);
  }
  const CUtensorMapSwizzle SW128 = CU_TENSOR_MAP_SWIZZLE_128B, SW64 = CU_TENSOR_MAP_SWIZZLE_64B;
  GemmMaps m3; ChainMaps mc;
  make_map(enc, &m3.o, (void*)(xbase + xo::O), HD, S_LEN, HD, 64, K3_N, SW128);
  make_map(enc, &m3.w, Wo, DM, HD, DM, 64, 64, SW128);
  make_map(enc, &m3.c, out, DM, S_LEN, OUT_LD, 64, K3_N, SW128);
  const CUtensorMapL2promotion P256 = CU_TENSOR_MAP_L2_PROMOTION_L2_256B;
  make_map(enc, &mc.wq, Wq, HD, DM, HD, 64, 128, SW128, P256);
  make_map(enc, &mc.wk, Wk, HD, DM, HD, 64, 128, SW128, P256);
  make_map(enc, &mc.wv, Wv, HD, DM, HD, 64, 128, SW128, P256);
  make_map(enc, &mc.wo, Wo, DM, HD, DM, 32, 256, SW64, P256);
  {
    const uint64_t dx[3] = {64, S_LEN, DM / 64}, sx[3] = {1, DM, 64};
    const uint32_t bx[3] = {64, SEG, 8};
    make_map_nd(enc, &mc.x, x, 3, dx, sx, bx, SW128);
  }

  const int skip = 0;
  BMaps mb;
  const CUtensorMapSwizzle SWN = CU_TENSOR_MAP_SWIZZLE_NONE;
  make_map(enc, &mb.q, Bq, DM, S_LEN, DM, 8, 256, SWN);
  make_map(enc, &mb.k, Bk, DM, S_LEN, DM, 8, 256, SWN);
  make_map(enc, &mb.v, Bv, DM, S_LEN, DM, 8, 256, SWN);
  make_map(enc, &mb.out, out, OUT_LD, S_LEN, OUT_LD, 8, 256, SWN);
  make_map(enc, &mb.k8, Bk, DM, S_LEN, DM, 8, 8, SWN);
  cudaStream_t s0 = cudaStreamPerThread;
  const int nb = nsm >= 132 ? 4 : 2, ntask1 = bp::NTASK - 2 * k3::NB;
  const bool fork = nsm >= 130;
  if (fork) {
    cudaEventRecord(ev_fork, s0);
    cudaStreamWaitEvent(s1, ev_fork, 0);
    if (!(skip & 1)) bpart_kernel<<<nb, 512, bp::SMEM, s1>>>(mb, shift_k, ssm_k, ssm_D, ntask1);
    cudaEventRecord(ev_join, s1);
  } else {
    bpart_kernel<<<ntask1 / 2, 512, bp::SMEM, s0>>>(mb, shift_k, ssm_k, ssm_D, ntask1);
  }
  if (!(skip & 4)) chain_kernel<<<128, 256, chain::SMEM, s0>>>(mc, mem0, xbase);
  if (!(skip & 8)) {
    cudaLaunchAttribute pdl[1];
    pdl[0].id = cudaLaunchAttributeProgrammaticStreamSerialization;
    pdl[0].val.programmaticStreamSerializationAllowed = 1;
    cudaLaunchConfig_t cfg = {};
    cfg.gridDim = dim3(128); cfg.blockDim = dim3(512); cfg.dynamicSmemBytes = k3::SMEM; cfg.stream = s0;
    cfg.attrs = pdl; cfg.numAttrs = 1;
    cudaLaunchKernelEx(&cfg, tail_kernel, m3, mb, shift_k, ssm_k, ssm_D);
  }
  if (fork) cudaStreamWaitEvent(s0, ev_join, 0);
}
```

```cpp
#include <cuda_runtime.h>
#include <cuda_bf16.h>
#include <cuda.h>
#include <stdint.h>

namespace {

constexpr int S_LEN = 2048;
constexpr int DM = 1024;
constexpr int NH = 32;
constexpr int DH = 128;
constexpr int HD = NH * DH;
constexpr int SEG = 32;
constexpr int NSEG = S_LEN / SEG;
constexpr int OUT_LD = 2048;

typedef __nv_bfloat16 bf16;
#define K3_N 160

__device__ __forceinline__ uint32_t smem_u32(const void* p) { return (uint32_t)__cvta_generic_to_shared(p); }

__device__ __forceinline__ void mbar_init(uint32_t bar, uint32_t count) {
  asm volatile("mbarrier.init.shared::cta.b64 [%0], %1;" ::"r"(bar), "r"(count) : "memory");
}
__device__ __forceinline__ void mbar_expect_tx(uint32_t bar, uint32_t bytes) {
  asm volatile("mbarrier.arrive.expect_tx.shared::cta.b64 _, [%0], %1;" ::"r"(bar), "r"(bytes) : "memory");
}
__device__ __forceinline__ void mbar_arrive(uint32_t bar) {
  asm volatile("mbarrier.arrive.shared::cta.b64 _, [%0];" ::"r"(bar) : "memory");
}
__device__ __forceinline__ bool mbar_try(uint32_t bar, uint32_t parity) {
  uint32_t ok;
  asm volatile("{.reg .pred p; mbarrier.try_wait.parity.shared::cta.b64 p, [%1], %2; selp.u32 %0, 1, 0, p;}"
               : "=r"(ok) : "r"(bar), "r"(parity) : "memory");
  return ok;
}
template <int HINT = 1>
__device__ __forceinline__ void mbar_wait(uint32_t bar, uint32_t parity) {
  int guard = 0;
  while (__builtin_expect(!mbar_try(bar, parity), HINT)) { if (++guard > (1 << 22)) __trap(); }
}
__device__ __forceinline__ void tma_load_2d(uint32_t dst, const CUtensorMap* map, int c0, int c1, uint32_t bar) {
  asm volatile("cp.async.bulk.tensor.2d.shared::cluster.global.mbarrier::complete_tx::bytes [%0], [%1, {%3, %4}], [%2];"
               ::"r"(dst), "l"(map), "r"(bar), "r"(c0), "r"(c1) : "memory");
}
__device__ __forceinline__ void tma_load_3d(uint32_t dst, const CUtensorMap* map, int c0, int c1, int c2, uint32_t bar) {
  asm volatile("cp.async.bulk.tensor.3d.shared::cluster.global.mbarrier::complete_tx::bytes [%0], [%1, {%3, %4, %5}], [%2];"
               ::"r"(dst), "l"(map), "r"(bar), "r"(c0), "r"(c1), "r"(c2) : "memory");
}
__device__ __forceinline__ void tma_load_4d(uint32_t dst, const CUtensorMap* map, int c0, int c1, int c2, int c3, uint32_t bar) {
  asm volatile("cp.async.bulk.tensor.4d.shared::cluster.global.mbarrier::complete_tx::bytes [%0], [%1, {%3, %4, %5, %6}], [%2];"
               ::"r"(dst), "l"(map), "r"(bar), "r"(c0), "r"(c1), "r"(c2), "r"(c3) : "memory");
}
__device__ __forceinline__ void tma_store_2d(const CUtensorMap* map, uint32_t src, int c0, int c1) {
  asm volatile("cp.async.bulk.tensor.2d.global.shared::cta.bulk_group [%0, {%2, %3}], [%1];"
               ::"l"(map), "r"(src), "r"(c0), "r"(c1) : "memory");
}
__device__ __forceinline__ void tma_prefetch_desc(const CUtensorMap* map) {
  asm volatile("prefetch.tensormap [%0];" ::"l"(map) : "memory");
}
__device__ __forceinline__ void fence_async_smem() { asm volatile("fence.proxy.async.shared::cta;" ::: "memory"); }
__device__ __forceinline__ void bulk_commit() { asm volatile("cp.async.bulk.commit_group;" ::: "memory"); }
template <int N> __device__ __forceinline__ void bulk_wait_read() { asm volatile("cp.async.bulk.wait_group.read %0;" ::"n"(N) : "memory"); }
template <int N> __device__ __forceinline__ void bulk_wait() { asm volatile("cp.async.bulk.wait_group %0;" ::"n"(N) : "memory"); }
__device__ __forceinline__ void named_bar(int id, int n) { asm volatile("bar.sync %0, %1;" ::"r"(id), "r"(n) : "memory"); }

__device__ __forceinline__ void named_bar_arrive(int id, int n) { asm volatile("bar.arrive %0, %1;" ::"r"(id), "r"(n) : "memory"); }
__device__ __forceinline__ float ex2(float x) { float y; asm("ex2.approx.ftz.f32 %0, %1;" : "=f"(y) : "f"(x)); return y; }
__device__ __forceinline__ float rcp(float x) { float y; asm("rcp.approx.ftz.f32 %0, %1;" : "=f"(y) : "f"(x)); return y; }

__device__ __forceinline__ void sts32(uint32_t a, uint32_t x) { asm volatile("st.shared.b32 [%0], %1;" ::"r"(a), "r"(x) : "memory"); }
__device__ __forceinline__ uint32_t lds32(uint32_t a) { uint32_t x; asm volatile("ld.shared.b32 %0, [%1];" : "=r"(x) : "r"(a) : "memory"); return x; }
__device__ __forceinline__ uint32_t lds32v(uint32_t a) { uint32_t x; asm volatile("ld.volatile.shared.b32 %0, [%1];" : "=r"(x) : "r"(a) : "memory"); return x; }
__device__ __forceinline__ void sts128(uint32_t a, const uint4& v) { asm volatile("st.shared.v4.b32 [%0], {%1,%2,%3,%4};" ::"r"(a), "r"(v.x), "r"(v.y), "r"(v.z), "r"(v.w) : "memory"); }
__device__ __forceinline__ void sts128f(uint32_t a, const float4& v) { asm volatile("st.shared.v4.f32 [%0], {%1,%2,%3,%4};" ::"r"(a), "f"(v.x), "f"(v.y), "f"(v.z), "f"(v.w) : "memory"); }
__device__ __forceinline__ uint4 lds128(uint32_t a) { uint4 v; asm volatile("ld.shared.v4.b32 {%0,%1,%2,%3}, [%4];" : "=r"(v.x), "=r"(v.y), "=r"(v.z), "=r"(v.w) : "r"(a) : "memory"); return v; }
__device__ __forceinline__ float4 lds128f(uint32_t a) { float4 v; asm volatile("ld.shared.v4.f32 {%0,%1,%2,%3}, [%4];" : "=f"(v.x), "=f"(v.y), "=f"(v.z), "=f"(v.w) : "r"(a) : "memory"); return v; }

__device__ __forceinline__ void cp_async16(uint32_t dst, const void* src) { asm volatile("cp.async.cg.shared.global [%0], [%1], 16;" ::"r"(dst), "l"(src) : "memory"); }
__device__ __forceinline__ void cp_async_commit() { asm volatile("cp.async.commit_group;" ::: "memory"); }
template <int N> __device__ __forceinline__ void cp_async_wait_group() { asm volatile("cp.async.wait_group %0;" ::"n"(N) : "memory"); }

__device__ __forceinline__ void wg_fence() { asm volatile("wgmma.fence.sync.aligned;" ::: "memory"); }
__device__ __forceinline__ void wg_commit() { asm volatile("wgmma.commit_group.sync.aligned;" ::: "memory"); }
template <int N> __device__ __forceinline__ void wg_wait() { asm volatile("wgmma.wait_group.sync.aligned %0;" ::"n"(N) : "memory"); }
__device__ __forceinline__ uint64_t make_desc(uint32_t addr, uint32_t lbo, uint32_t sbo, uint32_t swz) {
  return (uint64_t)((addr & 0x3FFFF) >> 4) | ((uint64_t)(lbo >> 4) << 16) | ((uint64_t)(sbo >> 4) << 32) | ((uint64_t)swz << 62);
}

__device__ __forceinline__ void ldsm_x4(uint32_t (&r)[4], uint32_t addr) {
  asm volatile("ldmatrix.sync.aligned.m8n8.x4.shared.b16 {%0,%1,%2,%3}, [%4];"
               : "=r"(r[0]), "=r"(r[1]), "=r"(r[2]), "=r"(r[3]) : "r"(addr) : "memory");
}
__device__ __forceinline__ void ldsm_x4_t(uint32_t (&r)[4], uint32_t addr) {
  asm volatile("ldmatrix.sync.aligned.m8n8.x4.trans.shared.b16 {%0,%1,%2,%3}, [%4];"
               : "=r"(r[0]), "=r"(r[1]), "=r"(r[2]), "=r"(r[3]) : "r"(addr) : "memory");
}
__device__ __forceinline__ void ldsm_x2(uint32_t& r0, uint32_t& r1, uint32_t addr) {
  asm volatile("ldmatrix.sync.aligned.m8n8.x2.shared.b16 {%0,%1}, [%2];" : "=r"(r0), "=r"(r1) : "r"(addr) : "memory");
}
__device__ __forceinline__ void stsm_x4(uint32_t addr, uint32_t r0, uint32_t r1, uint32_t r2, uint32_t r3) {
  asm volatile("stmatrix.sync.aligned.m8n8.x4.shared.b16 [%0], {%1,%2,%3,%4};"
               ::"r"(addr), "r"(r0), "r"(r1), "r"(r2), "r"(r3) : "memory");
}
__device__ __forceinline__ void mma16816(float (&c)[4], const uint32_t (&a)[4], uint32_t b0, uint32_t b1) {
  asm volatile("mma.sync.aligned.m16n8k16.row.col.f32.bf16.bf16.f32 {%0,%1,%2,%3}, {%4,%5,%6,%7}, {%8,%9}, {%0,%1,%2,%3};"
               : "+f"(c[0]), "+f"(c[1]), "+f"(c[2]), "+f"(c[3])
               : "r"(a[0]), "r"(a[1]), "r"(a[2]), "r"(a[3]), "r"(b0), "r"(b1));
}
__device__ __forceinline__ void mma1688(float (&c)[4], uint32_t a0, uint32_t a1, uint32_t b0) {
  asm volatile("mma.sync.aligned.m16n8k8.row.col.f32.bf16.bf16.f32 {%0,%1,%2,%3}, {%4,%5}, {%6}, {%0,%1,%2,%3};"
               : "+f"(c[0]), "+f"(c[1]), "+f"(c[2]), "+f"(c[3]) : "r"(a0), "r"(a1), "r"(b0));
}
__device__ __forceinline__ uint32_t pack_bf16(float lo, float hi) {
  uint32_t r;
  asm("cvt.rn.bf16x2.f32 %0, %1, %2;" : "=r"(r) : "f"(hi), "f"(lo));
  return r;
}
__device__ __forceinline__ float bf_lo(uint32_t w) { return __uint_as_float(w << 16); }
__device__ __forceinline__ float bf_hi(uint32_t w) { return __uint_as_float(w & 0xFFFF0000u); }

__device__ __forceinline__ uint4 ld_relaxed4(const void* p) {
  uint4 v;
  asm volatile("ld.relaxed.gpu.global.v4.u32 {%0,%1,%2,%3}, [%4];" : "=r"(v.x), "=r"(v.y), "=r"(v.z), "=r"(v.w) : "l"(p) : "memory");
  return v;
}
__device__ __forceinline__ void st_relaxed4(void* p, uint32_t a, uint32_t b, uint32_t c, uint32_t d) {
  asm volatile("st.relaxed.gpu.global.v4.u32 [%0], {%1,%2,%3,%4};" ::"l"(p), "r"(a), "r"(b), "r"(c), "r"(d) : "memory");
}
__device__ __forceinline__ void st_relaxed2(void* p, uint32_t a, uint32_t b) {
  asm volatile("st.relaxed.gpu.global.v2.u32 [%0], {%1,%2};" ::"l"(p), "r"(a), "r"(b) : "memory");
}
__device__ __forceinline__ void st_relaxed1(void* p, uint32_t a) {
  asm volatile("st.relaxed.gpu.global.u32 [%0], %1;" ::"l"(p), "r"(a) : "memory");
}

__device__ __forceinline__ uint2 ld_relaxed2(const void* p) {
  uint2 v;
  asm volatile("ld.relaxed.gpu.global.v2.u32 {%0,%1}, [%2];" : "=r"(v.x), "=r"(v.y) : "l"(p) : "memory");
  return v;
}
__device__ __forceinline__ void sts64(uint32_t a, uint32_t x, uint32_t y) { asm volatile("st.shared.v2.b32 [%0], {%1,%2};" ::"r"(a), "r"(x), "r"(y) : "memory"); }
__device__ __forceinline__ uint2 lds64(uint32_t a) { uint2 v; asm volatile("ld.shared.v2.b32 {%0,%1}, [%2];" : "=r"(v.x), "=r"(v.y) : "r"(a) : "memory"); return v; }
__device__ __forceinline__ void lds128r(uint32_t (&r)[4], uint32_t a) {
  asm volatile("ld.shared.v4.b32 {%0,%1,%2,%3}, [%4];" : "=r"(r[0]), "=r"(r[1]), "=r"(r[2]), "=r"(r[3]) : "r"(a) : "memory");
}
__device__ __forceinline__ uint32_t movmat(uint32_t a) { uint32_t d; asm volatile("movmatrix.sync.aligned.m8n8.trans.b16 %0, %1;" : "=r"(d) : "r"(a)); return d; }
__device__ __forceinline__ uint32_t mapa(uint32_t addr, uint32_t rank) { uint32_t r; asm volatile("mapa.shared::cluster.u32 %0, %1, %2;" : "=r"(r) : "r"(addr), "r"(rank)); return r; }
__device__ __forceinline__ void st_async1(uint32_t dst, uint32_t a, uint32_t bar) {
  asm volatile("st.async.weak.shared::cluster.mbarrier::complete_tx::bytes.b32 [%0], %1, [%2];" ::"r"(dst), "r"(a), "r"(bar) : "memory");
}
__device__ __forceinline__ void st_async2(uint32_t dst, uint32_t a, uint32_t b, uint32_t bar) {
  asm volatile("st.async.weak.shared::cluster.mbarrier::complete_tx::bytes.v2.b32 [%0], {%1,%2}, [%3];" ::"r"(dst), "r"(a), "r"(b), "r"(bar) : "memory");
}
__device__ __forceinline__ void st_async4(uint32_t dst, uint32_t a, uint32_t b, uint32_t c, uint32_t d, uint32_t bar) {
  asm volatile("st.async.weak.shared::cluster.mbarrier::complete_tx::bytes.v4.b32 [%0], {%1,%2,%3,%4}, [%5];" ::"r"(dst), "r"(a), "r"(b), "r"(c), "r"(d), "r"(bar) : "memory");
}
__device__ __forceinline__ void cluster_arrive() { asm volatile("barrier.cluster.arrive.release.aligned;" ::: "memory"); }
__device__ __forceinline__ void cluster_wait() { asm volatile("barrier.cluster.wait.acquire.aligned;" ::: "memory"); }

__device__ __forceinline__ void wgmma_k3_ss_ta(float (&d)[80], uint64_t da, uint64_t db, int scale_d) {
  asm volatile("{.reg .pred p; setp.ne.b32 p, %82, 0;\n"
    "wgmma.mma_async.sync.aligned.m64n160k16.f32.bf16.bf16 {%0, %1, %2, %3, %4, %5, %6, %7, %8, %9, %10, %11, %12, %13, %14, %15, %16, %17, %18, %19, %20, %21, %22, %23, %24, %25, %26, %27, %28, %29, %30, %31, %32, %33, %34, %35, %36, %37, %38, %39, %40, %41, %42, %43, %44, %45, %46, %47, %48, %49, %50, %51, %52, %53, %54, %55, %56, %57, %58, %59, %60, %61, %62, %63, %64, %65, %66, %67, %68, %69, %70, %71, %72, %73, %74, %75, %76, %77, %78, %79}, %80, %81, p, 1, 1, 1, 0;}"
    : "+f"(d[0]), "+f"(d[1]), "+f"(d[2]), "+f"(d[3]), "+f"(d[4]), "+f"(d[5]), "+f"(d[6]), "+f"(d[7]), "+f"(d[8]), "+f"(d[9]), "+f"(d[10]), "+f"(d[11]), "+f"(d[12]), "+f"(d[13]), "+f"(d[14]), "+f"(d[15]), "+f"(d[16]), "+f"(d[17]), "+f"(d[18]), "+f"(d[19]), "+f"(d[20]), "+f"(d[21]), "+f"(d[22]), "+f"(d[23]), "+f"(d[24]), "+f"(d[25]), "+f"(d[26]), "+f"(d[27]), "+f"(d[28]), "+f"(d[29]), "+f"(d[30]), "+f"(d[31]), "+f"(d[32]), "+f"(d[33]), "+f"(d[34]), "+f"(d[35]), "+f"(d[36]), "+f"(d[37]), "+f"(d[38]), "+f"(d[39]), "+f"(d[40]), "+f"(d[41]), "+f"(d[42]), "+f"(d[43]), "+f"(d[44]), "+f"(d[45]), "+f"(d[46]), "+f"(d[47]), "+f"(d[48]), "+f"(d[49]), "+f"(d[50]), "+f"(d[51]), "+f"(d[52]), "+f"(d[53]), "+f"(d[54]), "+f"(d[55]), "+f"(d[56]), "+f"(d[57]), "+f"(d[58]), "+f"(d[59]), "+f"(d[60]), "+f"(d[61]), "+f"(d[62]), "+f"(d[63]), "+f"(d[64]), "+f"(d[65]), "+f"(d[66]), "+f"(d[67]), "+f"(d[68]), "+f"(d[69]), "+f"(d[70]), "+f"(d[71]), "+f"(d[72]), "+f"(d[73]), "+f"(d[74]), "+f"(d[75]), "+f"(d[76]), "+f"(d[77]), "+f"(d[78]), "+f"(d[79])
    : "l"(da), "l"(db), "r"(scale_d));
}
__device__ __forceinline__ void wgmma_m64n32_ss_ta(float (&d)[16], uint64_t da, uint64_t db, int scale_d) {
  asm volatile("{.reg .pred p; setp.ne.b32 p, %18, 0;\n"
    "wgmma.mma_async.sync.aligned.m64n32k16.f32.bf16.bf16 {%0, %1, %2, %3, %4, %5, %6, %7, %8, %9, %10, %11, %12, %13, %14, %15}, %16, %17, p, 1, 1, 1, 0;}"
    : "+f"(d[0]), "+f"(d[1]), "+f"(d[2]), "+f"(d[3]), "+f"(d[4]), "+f"(d[5]), "+f"(d[6]), "+f"(d[7]), "+f"(d[8]), "+f"(d[9]), "+f"(d[10]), "+f"(d[11]), "+f"(d[12]), "+f"(d[13]), "+f"(d[14]), "+f"(d[15])
    : "l"(da), "l"(db), "r"(scale_d));
}

__device__ __forceinline__ void wgmma_m64n32_rs(float (&d)[16], const uint32_t (&a)[4], uint64_t db, int scale_d) {
  asm volatile("{.reg .pred p; setp.ne.b32 p, %21, 0;\n"
    "wgmma.mma_async.sync.aligned.m64n32k16.f32.bf16.bf16 {%0, %1, %2, %3, %4, %5, %6, %7, %8, %9, %10, %11, %12, %13, %14, %15}, {%16, %17, %18, %19}, %20, p, 1, 1, 0;}"
    : "+f"(d[0]), "+f"(d[1]), "+f"(d[2]), "+f"(d[3]), "+f"(d[4]), "+f"(d[5]), "+f"(d[6]), "+f"(d[7]), "+f"(d[8]), "+f"(d[9]), "+f"(d[10]), "+f"(d[11]), "+f"(d[12]), "+f"(d[13]), "+f"(d[14]), "+f"(d[15])
    : "r"(a[0]), "r"(a[1]), "r"(a[2]), "r"(a[3]), "l"(db), "r"(scale_d));
}

#define X_POS 5
#define T_STEP 2944
#define T_PHASE 1856
#define T_LAG 32
#define T_TOL 192
#define T_SLIP 640
#define V_PRE 4
#define XV_EARLY 0
#define O_LATE 0
#define SFENCE(i) asm volatile("{.reg .pred p; setp.eq.u32 p, %0, %1; @p trap;}" ::"r"(n), "r"(4096 + (i)) : "memory")
constexpr int RING = 4;
constexpr uint32_t EMPTY = 0xFFFFFFFFu;
namespace xo {
constexpr uint32_t SLOT = 1u << 20, HEAD = 16384;
constexpr uint32_t VM = 512;
constexpr uint32_t PT = 1024;
constexpr uint32_t PM = 1536;
constexpr uint32_t VT = 8192;
constexpr uint32_t MEM = NH * HEAD;
constexpr uint32_t OM = MEM + 16384;
constexpr uint32_t O = RING * SLOT;
constexpr uint32_t BYTES = O + S_LEN * HD * 2;
}
__device__ __align__(1024) uint4 g_scratch[2 * (xo::BYTES / 16)];
__device__ unsigned g_epoch;

struct ChainMaps {
  CUtensorMap wq, wk, wv;
  CUtensorMap wo;
  CUtensorMap x;
  const char* xp;
  uint32_t t_step, t_phase;
};

namespace chain {
constexpr int OFF_X = 65536;
constexpr int OFF_MEM = 131072;
constexpr int OFF_WS = 0;
constexpr int OFF_FP = 147456;
constexpr int OFF_KT = 163840;
constexpr int OFF_QT = 180224;
constexpr int OFF_VT = 196608;
constexpr int OFF_PX = 204800;
constexpr int OFF_S4 = OFF_PX + 1536;
constexpr int OFF_QM = 212992;
constexpr int OFF_KM = 215040;
constexpr int OFF_S1 = 217088;
constexpr int OFF_WVR = 0;
constexpr int OFF_WOR = 147456;
constexpr int OFF_RED = 212992;
constexpr int OFF_VPX = 221184;
constexpr int OFF_RX = 223232;
constexpr int OFF_TR = 225280;
constexpr int OFF_BAR = 229376;
constexpr int BAR_X = OFF_BAR, BAR_TOK = OFF_BAR + 16, BAR_EX = OFF_BAR + 32, BAR_P = OFF_BAR + 40, GRID_TGT = OFF_BAR + 128;
constexpr int CT_BASE = GRID_TGT + 4, CT_HEAD = GRID_TGT + 8, CT_OM = GRID_TGT + 12, CT_MP = GRID_TGT + 16, CT_O = GRID_TGT + 20, CT_PF = GRID_TGT + 24;
constexpr int CT_T1 = GRID_TGT + 32, CT_T2 = GRID_TGT + 36;
constexpr uint32_t RANK_BIT = 1u << 24;
constexpr int SMEM = OFF_BAR + 256;
constexpr uint32_t SB_LO = 1024;
constexpr float SCALE = 0.08838834764831845f, L2E = 1.4426950408889634f;
}

__device__ __forceinline__ uint32_t umax4(uint32_t a, uint32_t b, uint32_t c, uint32_t d) { return max(max(a, b), max(c, d)); }
__device__ __forceinline__ bool warp_incomplete(uint32_t m) { return __any_sync(0xffffffffu, m == EMPTY); }
#define PIN(x) asm volatile("" : "+r"(x))
#define KEEPALIVE(a, z) do { float _d0, _d1, _d2, _d3; asm volatile("mma.sync.aligned.m16n8k16.row.col.f32.bf16.bf16.f32 {%0,%1,%2,%3}, {%4,%5,%6,%7}, {%4,%5}, {%8,%8,%8,%8};" \
    : "=f"(_d0), "=f"(_d1), "=f"(_d2), "=f"(_d3) : "r"(a[0]), "r"(a[1]), "r"(a[2]), "r"(a[3]), "f"(0.f)); \
      \
    asm volatile("{.reg .pred p; setp.ne.u32 p, %0, 0; @p st.shared.f32 [%0], %1;}" ::"r"(z), "f"(_d0 + _d3) : "memory"); } while (0)
constexpr int POLL_LIMIT = 1 << 17;

__device__ __forceinline__ uint32_t keep(uint32_t x) { return __shfl_sync(0xffffffffu, x, threadIdx.x & 31); }
__device__ __forceinline__ char* gptr(uint32_t hi, uint32_t lo) { return (char*)(((uint64_t)hi << 32) | lo); }
__device__ __forceinline__ uint32_t slot_off(int n) { return ((uint32_t)n & (RING - 1)) * xo::SLOT; }
__device__ __forceinline__ void acc_fence(float (&a)[16]) {
#pragma unroll
  for (int i = 0; i < 16; i++) asm volatile("" : "+f"(a[i]) :: "memory");
}
template <int NB = 1, int STRIDE = 0>
__device__ __forceinline__ void gather_issue(uint32_t dst, const char* src) {
#pragma unroll
  for (int b = 0; b < NB; b++)
#pragma unroll
    for (int i = 0; i < 4; i++) cp_async16(dst + b * STRIDE + i * 512, src + b * STRIDE + i * 512);
  cp_async_commit();
}
template <int NB, int STRIDE>
__device__ __forceinline__ bool gather_incomplete(uint32_t chk) {
  uint32_t m = 0;
#pragma unroll
  for (int b = 0; b < NB; b++) m = max(m, umax4(lds32(chk + b * STRIDE), lds32(chk + b * STRIDE + 512), lds32(chk + b * STRIDE + 1024), lds32(chk + b * STRIDE + 1536)));
  return warp_incomplete(m);
}
__device__ __forceinline__ uint32_t ld_relaxed1(const void* p) {
  uint32_t v;
  asm volatile("ld.relaxed.gpu.global.u32 %0, [%1];" : "=r"(v) : "l"(p) : "memory");
  return v;
}
__device__ __forceinline__ uint32_t gtime() { uint64_t g; asm volatile("mov.u64 %0, %%globaltimer;" : "=l"(g) :: "memory"); return (uint32_t)g; }
#define WAIT_UNTIL(t, ka, alive) do { \
    int _d = gtime() - (t); \
    if (__builtin_expect(_d > T_TOL, 0)) do { t += T_SLIP; _d -= T_SLIP; } while (_d > T_TOL); \
    if (alive) for (int _k = 64; _d < -96 && --_k; _d = gtime() - (t)) KEEPALIVE(ka, zr); \
    for (uint32_t _g = -128; (int)(_d & ++_g) < 0;) _d = gtime() - (t); } while (0)
__device__ __forceinline__ void issue_x(uint32_t sb, const CUtensorMap* map, int n, int part) {
  asm volatile("{.reg .pred p; elect.sync _|p, 0xffffffff;\n"
               "@p cp.async.bulk.tensor.3d.shared::cluster.global.mbarrier::complete_tx::bytes [%0], [%1, {%3, %4, %5}], [%2];}"
               ::"r"(sb + chain::OFF_X + part * 32768), "l"(map), "r"(sb + chain::BAR_X + 8 * part), "r"(0), "r"(n * SEG), "r"(part * 8) : "memory");
}
__device__ __forceinline__ void issue_x_if(uint32_t sb, const CUtensorMap* map, int n, int part, uint32_t on) {
  asm volatile("{.reg .pred p, q; elect.sync _|p, 0xffffffff; setp.ne.and.u32 q, %6, 0, p;\n"
               "@q cp.async.bulk.tensor.3d.shared::cluster.global.mbarrier::complete_tx::bytes [%0], [%1, {%3, %4, %5}], [%2];}"
               ::"r"(sb + chain::OFF_X + part * 32768), "l"(map), "r"(sb + chain::BAR_X + 8 * part), "r"(0), "r"(n * SEG), "r"(part * 8), "r"(on) : "memory");
}
__device__ __forceinline__ void prefetch_l2(const char* p, uint32_t bytes) {
  asm volatile("{.reg .pred p; elect.sync _|p, 0xffffffff; @p cp.async.bulk.prefetch.L2.global [%0], %1;}" ::"l"(p), "r"(bytes) : "memory");
}
__device__ __forceinline__ void expect_elect(uint32_t bar, uint32_t bytes) {
  asm volatile("{.reg .pred p; elect.sync _|p, 0xffffffff; @p mbarrier.arrive.expect_tx.shared::cta.b64 _, [%0], %1;}" ::"r"(bar), "r"(bytes) : "memory");
}
template <int WG> __device__ __forceinline__ constexpr uint64_t xdesc(int ks) {
  return (uint64_t)(((chain::SB_LO + chain::OFF_X + WG * 32768 + (ks >> 2) * 4096 + (ks & 3) * 32) >> 4) + (1u << 16)) |
         ((uint64_t)(64u | (1u << 30)) << 32);
}
template <int WG> __device__ __forceinline__ constexpr uint64_t wdesc(int o, int ks) {
  return (uint64_t)(((chain::SB_LO + chain::OFF_WS + WG * 32768 + o * 16384 + ks * 2048) >> 4) + (1u << 16)) | ((uint64_t)(64u | (1u << 30)) << 32);
}
__device__ __forceinline__ void load_mem0(uint32_t sb, const bf16* __restrict__ mem0) {
  uint2 m[8];
#pragma unroll
  for (int r = 0; r < 8; r++) m[r] = __ldg((const uint2*)(mem0 + r * DM) + threadIdx.x);
  const uint32_t d = sb + chain::OFF_MEM + threadIdx.x * 64;
  sts128(d, make_uint4(__byte_perm(m[0].x, m[1].x, 0x5410), __byte_perm(m[2].x, m[3].x, 0x5410), __byte_perm(m[4].x, m[5].x, 0x5410), __byte_perm(m[6].x, m[7].x, 0x5410)));
  sts128(d + 16, make_uint4(__byte_perm(m[0].x, m[1].x, 0x7632), __byte_perm(m[2].x, m[3].x, 0x7632), __byte_perm(m[4].x, m[5].x, 0x7632), __byte_perm(m[6].x, m[7].x, 0x7632)));
  sts128(d + 32, make_uint4(__byte_perm(m[0].y, m[1].y, 0x5410), __byte_perm(m[2].y, m[3].y, 0x5410), __byte_perm(m[4].y, m[5].y, 0x5410), __byte_perm(m[6].y, m[7].y, 0x5410)));
  sts128(d + 48, make_uint4(__byte_perm(m[0].y, m[1].y, 0x7632), __byte_perm(m[2].y, m[3].y, 0x7632), __byte_perm(m[4].y, m[5].y, 0x7632), __byte_perm(m[6].y, m[7].y, 0x7632)));
}
__device__ __forceinline__ void grid_wait(uint32_t sb) {
  if (threadIdx.x == 0) {
    const uint32_t target = lds32(sb + chain::GRID_TGT);
    uint32_t v; int guard = 0;
    do { asm volatile("ld.acquire.gpu.global.u32 %0, [%1];" : "=r"(v) : "l"(&g_epoch) : "memory"); } while ((int)(v - target) < 0 && ++guard < (1 << 20));
  }
  named_bar(0, 256);
}
template <int K> __device__ __forceinline__ uint32_t loop_zero(int n) { uint32_t z; asm volatile("shr.u32 %0, %1, %2;" : "=r"(z) : "r"(n), "n"(16 + K)); return z; }
#define NEWZ(k) zr = loop_zero<k>(n)

template <int WG>
__device__ __forceinline__ void role_a(const ChainMaps& maps, const bf16* __restrict__ mem0, const uint32_t sb, const uint32_t xbase_lo, const uint32_t xbase_hi) {
  using namespace chain;
  const int h = blockIdx.x >> 2;
  const bool J = sb >= RANK_BIT;
  const uint32_t u16 = (threadIdx.x & 96) * 64 + (threadIdx.x & 31) * 16;
  const uint32_t t16 = keep(u16), l16 = keep((threadIdx.x & 31) * 16);
  const uint32_t a_wl = keep((((threadIdx.x >> 4) & 1) * 8 + (threadIdx.x & 7)) * 128 + (((((threadIdx.x >> 4) & 6) + ((threadIdx.x >> 3) & 1)) ^ (threadIdx.x & 7)) << 4));
  const uint32_t xhi = keep(xbase_hi + (t16 >> 16)), xh = keep(xbase_lo + h * xo::HEAD + u16);
#define xm (lds32(sb + CT_BASE) + t16 + xo::MEM)
#define last_warp __any_sync(0xffffffffu, tv >= 6144)
#define tv (t16 ^ zr)
  const CUtensorMap* wm = J ? &maps.wk : &maps.wq;

  uint32_t aW[2][24][4];
  mbar_wait(sb + BAR_P, 0);
#pragma unroll
  for (int ks = 0; ks < 24; ks++) ldsm_x4_t(aW[0][ks], sb + a_wl + OFF_X + WG * 49152 + ks * 2048);
  named_bar(0, 256);
  if (WG == 1 && __any_sync(0xffffffffu, t16 >= 6144)) {
    fence_async_smem();
    if (l16 == 0) {
      mbar_expect_tx(sb + BAR_P + 16, 2 * 16384);
      for (int q = 0; q < 2; q++) tma_load_2d(sb + OFF_X + (4 + q) * 16384, wm, h * DH + (q ^ 1) * 64, q * 512 + 256, sb + BAR_P + 16);
    }
    __syncwarp();
    expect_elect(sb + BAR_X, 32768); expect_elect(sb + BAR_X + 8, 32768); expect_elect(sb + BAR_TOK, 8192);
    issue_x(sb, &maps.x, 0, 0); issue_x(sb, &maps.x, 0, 1);
  }
  mbar_wait(sb + BAR_P + 8, 0);
#pragma unroll
  for (int ks = 0; ks < 16; ks++) ldsm_x4_t(aW[1][ks], sb + a_wl + OFF_X + 6 * 16384 + WG * 32768 + ks * 2048);
  mbar_wait(sb + BAR_P + 16, 0);
#pragma unroll
  for (int ks = 0; ks < 8; ks++) ldsm_x4_t(aW[1][16 + ks], sb + a_wl + OFF_X + (4 + WG) * 16384 + ks * 2048);
  named_bar(0, 256);
  cluster_arrive();
  load_mem0(sb, mem0);
  mbar_wait(sb + BAR_P + 24, 0);
  cluster_wait();
  const uint32_t rsb = sb ^ RANK_BIT;
  const uint32_t a_ws = sb + a_wl + OFF_WS + WG * 32768;

  uint32_t ws[2][4][4];
  auto load_ws = [&]() {
#pragma unroll
    for (int q = 0; q < 2; q++) {
      const uint32_t a = a_ws + q * 4096;
      ldsm_x4_t(ws[q][0], a); ldsm_x4_t(ws[q][1], a + 16384); ldsm_x4_t(ws[q][2], a + 2048); ldsm_x4_t(ws[q][3], a + 16384 + 2048);
    }
  };
  uint32_t tref = 0;
#pragma unroll 1
  for (int n = 0; n <= (J ? NSEG : NSEG - 1); n++) {
#define s (n - 1)
#define sv ((int)(n ^ zr) - 1)
    const bool more = __builtin_expect(s + 1 < NSEG, 1);
    uint32_t zr = loop_zero<0>(n);
#define wq ((int)(tv >> 11))
#define lv (l16 ^ zr)
#define gh (xh + slot_off(sv))
    uint32_t tmp[4][4];
    auto load_tmp = [&](int o) {
#pragma unroll
      for (int ks = 0; ks < 4; ks++) ldsm_x4_t(tmp[ks], a_ws + o * 16384 + ks * 2048);
    };
    if (__builtin_expect(s < 0, 0)) load_tmp(1);
    else {
      if (__builtin_expect(s > 0, 1)) {
        if (WG == 1) {
          const uint32_t chk = sb + OFF_MEM + t16 + ((lv >> 5) & 12);
          uint32_t tries = zr;
#pragma unroll 1
          do {
            if (tries) {
              const char* src = gptr(xhi, xm + slot_off(sv));
              tref += T_SLIP;
              WAIT_UNTIL(tref, aW[0][0], 1);
              gather_issue<2, 8192>(sb + OFF_MEM + tv, src);
            }
            KEEPALIVE(aW[0][0], zr);
            cp_async_wait_group<0>();
          } while (gather_incomplete<2, 8192>(chk) && ++tries < POLL_LIMIT);
        } else {
          cp_async_wait_group<0>();
        }
        named_bar(1, 256);
      }
      float c[2][2][4];
#pragma unroll
      for (int i = 0; i < 4; i++) c[i >> 1][i & 1][0] = c[i >> 1][i & 1][1] = c[i >> 1][i & 1][2] = c[i >> 1][i & 1][3] = 0.f;
      {
        const uint32_t a_mem = sb + OFF_MEM + WG * 8192 + l16;
        uint32_t b[4][4];
        constexpr int PR[16] = {12, 13, 0, 1, 2, 3, 4, 14, 5, 6, 7, 8, 9, 15, 10, 11};
        ldsm_x4_t(b[0], a_mem + PR[0] * 512); ldsm_x4_t(b[1], a_mem + PR[1] * 512);
#pragma unroll
        for (int i = 0; i < 16; i++) {
          if ((i & 1) == 0 && i < 14) {
            ldsm_x4_t(b[(i + 2) & 3], a_mem + PR[i + 2] * 512); ldsm_x4_t(b[(i + 3) & 3], a_mem + PR[i + 3] * 512);
            if (i == 2 || i == 8) { ldsm_x4_t(ws[1][0], a_ws + (i == 2 ? 2 : 3) * 4096); ldsm_x4_t(ws[1][1], a_ws + (i == 2 ? 2 : 3) * 4096 + 16384); }
            if (i == 4 || i == 10) { ldsm_x4_t(ws[1][2], a_ws + (i == 4 ? 2 : 3) * 4096 + 2048); ldsm_x4_t(ws[1][3], a_ws + (i == 4 ? 2 : 3) * 4096 + 16384 + 2048); }
          }
          const int p = PR[i];
          if (p >= 12) {
            const int z = i != 0;
            mma16816(c[0][0], ws[z][0], b[i & 3][0], b[i & 3][1]); mma16816(c[1][0], ws[z][1], b[i & 3][0], b[i & 3][1]);
            mma16816(c[0][1], ws[z][2], b[i & 3][2], b[i & 3][3]); mma16816(c[1][1], ws[z][3], b[i & 3][2], b[i & 3][3]);
          } else {
            mma16816(c[1][0], aW[1][2 * p], b[i & 3][0], b[i & 3][1]); mma16816(c[1][1], aW[1][2 * p + 1], b[i & 3][2], b[i & 3][3]);
            mma16816(c[0][0], aW[0][2 * p], b[i & 3][0], b[i & 3][1]); mma16816(c[0][1], aW[0][2 * p + 1], b[i & 3][2], b[i & 3][3]);
          }
          if (i == 11 && WG == 1) mbar_wait<0>(sb + BAR_TOK + 8 * (s & 1), (s >> 1) & 1);
          if (i == 15) SFENCE(15);
          if (i == X_POS + 4 * (1 - WG)) { issue_x_if(sb, &maps.x, s + 1, WG, t16 >= 6144 && more); if (WG) __syncwarp(); }
        }
      }
      sts128f(sb + OFF_PX + WG * 512 + t16, make_float4(c[1][0][0] + c[1][1][0], c[1][0][1] + c[1][1][1], c[1][0][2] + c[1][1][2], c[1][0][3] + c[1][1][3]));
      const float4 own = make_float4(c[0][0][0] + c[0][1][0], c[0][0][1] + c[0][1][1], c[0][0][2] + c[0][1][2], c[0][0][3] + c[0][1][3]);
      NEWZ(1);
      uint32_t a = (J ? OFF_KM : OFF_QM) + WG * 1024 + wq * 256 + (lv >> 2);
      uint32_t ra = rsb + a, ra2 = ra + 128, rx = rsb + BAR_EX + zr;
      PIN(a); PIN(ra); PIN(ra2); PIN(rx);
      SFENCE(16);
      named_bar(3, 256);
      {
        const float4 o = lds128f(sb + OFF_PX + (WG ^ 1) * 512 + t16);
        const uint32_t lo = pack_bf16(own.x + o.x, own.y + o.y), hi = pack_bf16(own.z + o.z, own.w + o.w);
        if (J == 1 && more) { st_async1(ra, lo, rx); st_async1(ra2, hi, rx); }
        sts32(sb + a, lo); sts32(sb + a + 128, hi);
      }
      const uint32_t kt = sb + OFF_KT + (s & 1) * 8192;
      auto load_kb = [&](uint32_t (&d)[4], uint32_t a) { const uint2 u = lds64(a), v = lds64(a + 1024); d[0] = u.x; d[1] = u.y; d[2] = v.x; d[3] = v.y; };
      if (J == 0) {
        uint32_t am[4][4], kb[4][4];
        uint2 vm0, vm1;
        const char* pvm = gptr(xhi, gh - (lv >> 1)) + xo::VM;
        if (WG == 0) { vm0 = ld_relaxed2(pvm); vm1 = ld_relaxed2(pvm + 256); }
        if (WG == 1) {
#pragma unroll
          for (int p = 0; p < 4; p++) load_kb(kb[p], kt + wq * 256 + (lv >> 1) + p * 2048);
        }
        named_bar(7, 256);
#pragma unroll
        for (int p = 0; p < 4; p++) ldsm_x4_t(am[p], sb + OFF_QM + p * 512 + ((lv & 128) << 1) + ((lv & 256) >> 1) + (lv & 112));
        auto scores = [&]() {
          float c0[2][4], c1[2][4];
#pragma unroll
          for (int i = 0; i < 2; i++) { c0[i][0] = c0[i][1] = c0[i][2] = c0[i][3] = 0.f; c1[i][0] = c1[i][1] = c1[i][2] = c1[i][3] = 0.f; }
#pragma unroll
          for (int p = 0; p < 4; p++) { mma16816(c0[p & 1], am[p], kb[p][0], kb[p][1]); mma16816(c1[p & 1], am[p], kb[p][2], kb[p][3]); }
          const uint32_t r1 = pack_bf16((c0[0][0] + c0[1][0]) + (c1[0][2] + c1[1][2]), (c0[0][1] + c0[1][1]) + (c1[0][3] + c1[1][3]));
          return pack_bf16(bf_lo(r1) * SCALE, bf_hi(r1) * SCALE);
        };
        if (WG == 1) {
          sts32(sb + OFF_S4 + l16 + wq * 4, scores());
          named_bar_arrive(8, 256);
          load_tmp(1);
        } else {
          mbar_wait<0>(sb + BAR_EX, s & 1);
#pragma unroll
          for (int p = 0; p < 4; p++) ldsm_x4_t(kb[p], sb + OFF_KM + p * 512 + l16);
          named_bar(8, 256);
          const uint4 sc = lds128(sb + OFF_S4 + l16);
          const uint32_t sm = scores();
          float x[10] = {bf_lo(sm), bf_hi(sm), bf_lo(sc.x), bf_hi(sc.x), bf_lo(sc.y), bf_hi(sc.y), bf_lo(sc.z), bf_hi(sc.z), bf_lo(sc.w), bf_hi(sc.w)};
          float mx = fmaxf(fmaxf(fmaxf(x[2], x[3]), fmaxf(x[4], x[5])), fmaxf(fmaxf(x[6], x[7]), fmaxf(x[8], x[9])));
          mx = fmaxf(mx, fmaxf(x[0], x[1]));
          mx = fmaxf(mx, __shfl_xor_sync(~0u, mx, 1));
          mx = fmaxf(mx, __shfl_xor_sync(~0u, mx, 2));
          NEWZ(2);
          uint32_t vb[4][4];
          const uint32_t omb = lds32(sb + CT_OM);
#pragma unroll
          for (int e = 0; e < 4; e++) lds128r(vb[e], sb + OFF_VT + t16 + e * 512);
          const float mb = mx * L2E;
#pragma unroll
          for (int i = 0; i < 10; i++) x[i] = ex2(fmaf(x[i], L2E, -mb));
          uint32_t pa[4], pb[4], p4, p5;
          asm volatile("" : "=r"(pa[1]), "=r"(pa[3]), "=r"(pb[1]), "=r"(pb[3]), "=r"(p5));
          pa[0] = pack_bf16(x[2], x[3]); pa[2] = pack_bf16(x[4], x[5]);
          pb[0] = pack_bf16(x[6], x[7]); pb[2] = pack_bf16(x[8], x[9]);
          p4 = pack_bf16(x[0], x[1]);
          float sx = ((x[0] + x[1]) + (x[2] + x[3])) + ((x[4] + x[5]) + (x[6] + x[7])) + (x[8] + x[9]);
          asm volatile("" : "+r"(pa[0]), "+r"(pa[2]), "+r"(pb[0]), "+r"(pb[2]), "+r"(p4), "+f"(sx));
          if (__builtin_expect(warp_incomplete(max(umax4(vb[0][0], vb[1][0], vb[2][0], vb[3][0]), max(vm0.x, vm1.x))), 0)) {
            uint32_t tries = zr;
#pragma unroll 1
            do {
              const char* pv2 = gptr(xhi, gh - ((l16 + (tries >> 20)) >> 1)) + xo::VM;
              vm0 = ld_relaxed2(pv2); vm1 = ld_relaxed2(pv2 + 256);
#pragma unroll
              for (int e = 0; e < 4; e++) { const uint4 v = ld_relaxed4(gptr(xhi, gh) + xo::VT + e * 512); vb[e][0] = v.x; vb[e][1] = v.y; vb[e][2] = v.z; vb[e][3] = v.w; }
            } while (warp_incomplete(max(umax4(vb[0][0], vb[1][0], vb[2][0], vb[3][0]), max(vm0.x, vm1.x))) && ++tries < POLL_LIMIT);
          }
          float oa[4][4];
#pragma unroll
          for (int e = 0; e < 4; e++) oa[e][0] = oa[e][1] = oa[e][2] = oa[e][3] = 0.f;
          sx += __shfl_xor_sync(~0u, sx, 1);
          mma1688(oa[0], p4, p5, vm0.x); mma1688(oa[1], p4, p5, vm0.y); mma1688(oa[2], p4, p5, vm1.x); mma1688(oa[3], p4, p5, vm1.y);
#pragma unroll
          for (int e = 0; e < 4; e++) mma16816(oa[e], pa, vb[e][0], vb[e][1]);
          sx += __shfl_xor_sync(~0u, sx, 2);
#pragma unroll
          for (int e = 0; e < 4; e++) mma16816(oa[e], pb, vb[e][2], vb[e][3]);
          const float rx = rcp(sx);
          const uint32_t xo0 = omb + wq * 512 + l16;
          SFENCE(24);
          named_bar_arrive(10, 256);
          st_relaxed4(gptr(xhi, xo0 + slot_off(sv)), pack_bf16(oa[0][0] * rx, oa[0][1] * rx), pack_bf16(oa[1][0] * rx, oa[1][1] * rx),
                      pack_bf16(oa[2][0] * rx, oa[2][1] * rx), pack_bf16(oa[3][0] * rx, oa[3][1] * rx));
          st_relaxed4(gptr(xhi, xo0 + slot_off(sv + 3)), EMPTY, EMPTY, EMPTY, EMPTY);
          load_tmp(1);
        }
      } else {
        {
          const int mt = WG | (wq == 3), ktile = wq == 3 ? 2 + WG : wq - 1;
          const uint32_t qt = sb + OFF_QT + (s & 1) * 8192 + mt * 512 + l16;
          uint32_t kb[4][4], q[8][4];
          if (WG == 0) mbar_wait<0>(sb + BAR_TOK + 8 * (s & 1), (s >> 1) & 1);
          if (__any_sync(0xffffffffu, tv < 2048)) {
            named_bar(7, 256);
#pragma unroll
            for (int p = 0; p < 4; p++) ldsm_x4_t(kb[p], sb + OFF_KM + p * 512 + l16);
          } else {
            named_bar_arrive(7, 256);
#pragma unroll
            for (int p = 0; p < 4; p++) load_kb(kb[p], kt + (lv >> 1) + ktile * 256 + p * 2048);
          }
#pragma unroll
          for (int i = 0; i < 8; i++) lds128r(q[i], qt + i * 1024);
          __syncwarp();
          float c0[4][4];
#pragma unroll
          for (int i = 0; i < 4; i++) { c0[i][0] = c0[i][1] = c0[i][2] = c0[i][3] = 0.f; mma16816(c0[i], q[i], kb[i >> 1][(i & 1) * 2], kb[i >> 1][(i & 1) * 2 + 1]); }
#pragma unroll
          for (int i = 0; i < 4; i++) mma16816(c0[i], q[4 + i], kb[2 + (i >> 1)][(i & 1) * 2], kb[2 + (i >> 1)][(i & 1) * 2 + 1]);
          NEWZ(3);
          const uint32_t r0 = pack_bf16((c0[0][0] + c0[1][0]) + (c0[2][0] + c0[3][0]), (c0[0][1] + c0[1][1]) + (c0[2][1] + c0[3][1]));
          const uint32_t r1 = pack_bf16((c0[0][2] + c0[1][2]) + (c0[2][2] + c0[3][2]), (c0[0][3] + c0[1][3]) + (c0[2][3] + c0[3][3]));
          const uint32_t sa = wq == 0 ? sb + OFF_S1 + (lv >> 2) + mt * 256 : sb + OFF_S4 + l16 + mt * 4096 + ktile * 4;
          sts32(sa, pack_bf16(bf_lo(r0) * SCALE, bf_hi(r0) * SCALE));
          sts32(sa + (wq == 0 ? 128 : 2048), pack_bf16(bf_lo(r1) * SCALE, bf_hi(r1) * SCALE));
        }
        if (WG == 1) { named_bar_arrive(8, 256); load_tmp(1); }
        else {
          if (more) named_bar_arrive(10, 256);
          load_tmp(1);
          named_bar(8, 256);
          const uint4 sc = lds128(sb + OFF_S4 + t16); const uint32_t s1 = lds32(sb + OFF_S1 + wq * 128 + (lv >> 2));
          float y[10] = {bf_lo(s1), bf_hi(s1), bf_lo(sc.x), bf_hi(sc.x), bf_lo(sc.y), bf_hi(sc.y), bf_lo(sc.z), bf_hi(sc.z), bf_lo(sc.w), bf_hi(sc.w)};
          const int rel = wq * 8 + (int)(lv >> 6) - (int)((lv >> 3) & 6);
          const float NEG = -999292928.f;
#pragma unroll
          for (int e = 0; e < 4; e++) {
            if (e * 8 > rel) y[2 * e + 2] = NEG;
            if (e * 8 + 1 > rel) y[2 * e + 3] = NEG;
          }
          float my = fmaxf(fmaxf(fmaxf(y[0], y[1]), fmaxf(y[2], y[3])), fmaxf(fmaxf(y[4], y[5]), fmaxf(y[6], y[7])));
          my = fmaxf(my, fmaxf(y[8], y[9]));
          my = fmaxf(my, __shfl_xor_sync(~0u, my, 1));
          my = fmaxf(my, __shfl_xor_sync(~0u, my, 2));
#pragma unroll
          for (int i = 0; i < 10; i++) y[i] = ex2((y[i] - my) * L2E);
          float sy = ((y[0] + y[1]) + (y[2] + y[3])) + ((y[4] + y[5]) + (y[6] + y[7])) + (y[8] + y[9]);
          sy += __shfl_xor_sync(~0u, sy, 1);
          sy += __shfl_xor_sync(~0u, sy, 2);
          const float ry = rcp(sy);
          st_relaxed4(gptr(xhi, gh) + xo::PT, pack_bf16(y[2] * ry, y[3] * ry), pack_bf16(y[4] * ry, y[5] * ry), pack_bf16(y[6] * ry, y[7] * ry), pack_bf16(y[8] * ry, y[9] * ry));
          const uint32_t l12 = lv - (lv >> 2);
          st_relaxed1(gptr(xhi, gh - l12) + xo::PM, pack_bf16(y[0] * ry, y[1] * ry));
        }
      }
    }
    if (more) {
      float acc[16];
      const uint32_t xph = (s + 1) & 1;
      auto batch = [&](const uint32_t (&a)[24][4], int o) {
        wg_fence();
#pragma unroll
        for (int ks = 4; ks < 8; ks++) wgmma_m64n32_ss_ta(acc, wdesc<WG>(o, ks), xdesc<WG>(24 + ks), ks != 4);
#pragma unroll
        for (int ks = 0; ks < 4; ks++) wgmma_m64n32_rs(acc, tmp[ks], xdesc<WG>(24 + ks), 1);
#pragma unroll
        for (int ks = 0; ks < 24; ks++) wgmma_m64n32_rs(acc, a[ks], xdesc<WG>(ks), 1);
        wg_commit();
      };
      mbar_wait<0>(sb + BAR_X + 8 * WG, xph);
      if (WG == 0) named_bar(12, 256);
      else if (__builtin_expect(s >= 0, 1)) named_bar(10, 256);
      batch(aW[1], 1);
      named_bar_arrive(WG ? 12 : 13, 256);
      wg_wait<0>();
      acc_fence(acc);
      load_tmp(0);
#pragma unroll
      for (int i = 0; i < 4; i++) sts128f(sb + OFF_FP + WG * 8192 + t16 + i * 512, make_float4(acc[4 * i], acc[4 * i + 1], acc[4 * i + 2], acc[4 * i + 3]));
      NEWZ(4);
      if (WG == 0 && s >= 0) {
        if (J == 0) gather_issue(sb + OFF_VT + tv, gptr(xhi, xh + slot_off(sv + 1)) + xo::VT);
        else {
          st_relaxed4(gptr(xhi, xh + slot_off(sv + 1)) + xo::PT, EMPTY, EMPTY, EMPTY, EMPTY);
          st_relaxed1(gptr(xhi, xh + slot_off(sv + 1) - lv + (lv >> 2)) + xo::PM, EMPTY);
        }
      }
      uint32_t esrc = 0;
      if (WG == 1) { esrc = xm + slot_off(sv + 1); tref += lds32(sb + CT_T1); }
      named_bar(WG ? 13 : 14, 256);
      batch(aW[0], 0);
      NEWZ(5);
      if (WG == 1) {
        named_bar(14, 256);
        if (last_warp && s + 2 < NSEG) {
          expect_elect(sb + BAR_TOK + 8 * (xph ^ 1), 8192); expect_elect(sb + BAR_X, 32768); expect_elect(sb + BAR_X + 8, 32768);
          if (J == 0) expect_elect(sb + BAR_EX, 2048);
        }
      }
      float4 oth[4];
#pragma unroll
      for (int i = 0; i < 4; i++) oth[i] = lds128f(sb + OFF_FP + (WG ^ 1) * 8192 + t16 + i * 512);
      if (WG == 1 && __builtin_expect(s >= 0, 1)) {
        WAIT_UNTIL(tref, aW[0][0], 0);
        gather_issue<2, 8192>(sb + OFF_MEM + tv, gptr(xhi, esrc));
      }
      wg_wait<0>();
      acc_fence(acc);
      uint32_t lt[4], ht[4];
#pragma unroll
      for (int i = 0; i < 4; i++) {
        const float4 o = oth[i];
        lt[i] = movmat(pack_bf16(acc[4 * i] + o.x, acc[4 * i + 1] + o.y)); ht[i] = movmat(pack_bf16(acc[4 * i + 2] + o.z, acc[4 * i + 3] + o.w));
      }
      NEWZ(6);
      uint32_t tb = xph * 8192 + WG * 4096 + wq * 1024;
      if (J == 0) {
        tb += OFF_QT;
        sts128(sb + tb + l16, make_uint4(lt[0], lt[1], ht[0], ht[1])); sts128(sb + tb + 512 + l16, make_uint4(lt[2], lt[3], ht[2], ht[3]));
      } else {
        tb += OFF_KT;
#pragma unroll
        for (int i = 0; i < 4; i++) sts64(sb + tb + (lv >> 1) + i * 256, lt[i], ht[i]);
      }
      if (WG == 0 && last_warp) {
        load_ws();
        named_bar(11, 256);
        fence_async_smem();
        const uint32_t tt = (J ? OFF_KT : OFF_QT) + xph * 8192;
        asm volatile("{.reg .pred p; elect.sync _|p, 0xffffffff;\n"
                     "@p cp.async.bulk.shared::cluster.shared::cta.mbarrier::complete_tx::bytes [%0], [%1], 8192, [%2];}"
                     ::"r"(rsb + tt), "r"(sb + tt), "r"(rsb + BAR_TOK + 8 * xph) : "memory");
      } else {
        named_bar_arrive(11, 256);
        load_ws();
      }
    }
    if (!more) break;
    if (__builtin_expect(s < 0, 0)) {
      grid_wait(sb);
      if (WG == 0) { gather_issue(sb + OFF_VT + tv, gptr(xhi, xh) + xo::VT); cp_async_wait_group<0>(); }
      tref = gtime() / T_SLIP * T_SLIP - T_SLIP;
    }
  }
  cp_async_wait_group<0>();
  if (J == 0) mbar_wait(sb + BAR_TOK + 8, 1);
}

template <int WG>
__device__ __forceinline__ void role_v(const ChainMaps& maps, const bf16* __restrict__ mem0, const uint32_t sb, const uint32_t xbase_lo, const uint32_t xbase_hi) {
  using namespace chain;
  const int h = blockIdx.x >> 2;
  const uint32_t u16 = (threadIdx.x & 96) * 64 + (threadIdx.x & 31) * 16;
  const uint32_t t16 = keep(u16), l16 = keep((threadIdx.x & 31) * 16);
  const uint32_t xhi = keep(xbase_hi + (t16 >> 16));
#define j (sb >> 24)
  auto wv_addr = [&](uint32_t t) { return WG * 32768 + ((t & 256) << 2) + ((t & 112) << 3) + ((((t >> 6) & 96) + ((t >> 3) & 16)) ^ (t & 112)); };
  auto wo_addr = [&](uint32_t t) { return OFF_WOR + WG * 32768 + ((t & 6144) << 2) + ((t & 256) << 1) + ((t & 112) << 2) + ((((j ^ 1) << 5) + ((t >> 3) & 16)) ^ ((t >> 1) & 48)); };
#define ovt (((tv + l16) >> 1) + (xo::VT + WG * 512 + j * 4096))
#define ovm (((tv & 4096) >> 1) + ((tv & 2048) >> 3) + (lv >> 1) + (xo::VM + j * 4096))
#define xvt (lds32(sb + CT_HEAD) + ovt)
#define xvm (lds32(sb + CT_HEAD) + ovm)
#define xom (lds32(sb + CT_OM) + t16 + WG * 8192)
#define warp_is(q) __any_sync(0xffffffffu, (tv >> 11) == (q))
#define upper_warps (WG == 1 || __any_sync(0xffffffffu, tv >= 4096))

  uint32_t aV[16][4];
  uint32_t aO[16][4];
  uint32_t rot[16][4];
  mbar_wait(sb + BAR_P, 0);
#pragma unroll
  for (int ks = 0; ks < 16; ks++) ldsm_x4_t(aV[ks], sb + wv_addr(t16) + OFF_X + ks * 2048);
#pragma unroll
  for (int ks = 0; ks < 8; ks++) { ldsm_x4_t(aO[ks], sb + wo_addr(t16) + ks * 1024); ldsm_x4_t(aO[8 + ks], sb + (wo_addr(t16) ^ 32) + ks * 1024); }
  named_bar(0, 256);
  if (WG == 1 && __any_sync(0xffffffffu, t16 >= 6144)) {
    fence_async_smem();
    expect_elect(sb + BAR_X, 32768); expect_elect(sb + BAR_X + 8, 32768);
    issue_x(sb, &maps.x, 0, 0); issue_x(sb, &maps.x, 0, 1);
    prefetch_l2(maps.xp + 65536 + (h * 2 + j) * 3072, 3072);
    if (l16 == 0) {
      mbar_expect_tx(sb + BAR_P + 16, 4 * 16384);
      for (int q = 0; q < 4; q++) tma_load_2d(sb + OFF_WOR + q * 16384, &maps.wo, h * 32, j * 2048 + 1024 + q * 256, sb + BAR_P + 16);
    }
    __syncwarp();
  }
  cluster_arrive();
  load_mem0(sb, mem0);
  mbar_wait(sb + BAR_P + 8, 0);
  auto load_v = [&](uint32_t t) {
#pragma unroll
    for (int ks = 0; ks < 16; ks++) ldsm_x4_t(rot[ks], sb + wv_addr(t) + OFF_WVR + ks * 2048);
  };
  load_v(t16);
  cluster_wait();
  const uint32_t rsb = sb ^ RANK_BIT;

  uint32_t tref = 0;
#pragma unroll 1
  for (int n = 0; n <= NSEG; n++) {
    const bool more = __builtin_expect(s + 1 < NSEG, 1);
    uint32_t zr = loop_zero<0>(n);
    if (__builtin_expect(s >= 0, 1)) {
      if (__builtin_expect(s > 0, 1)) {
        const uint32_t dst = sb + OFF_MEM + WG * 8192 + t16 + ((lv >> 5) & 12);
        uint32_t tries = zr;
#pragma unroll 1
        do {
          if (tries) { const char* src = gptr(xhi, xm + WG * 8192 + slot_off(sv)); tref += T_SLIP; WAIT_UNTIL(tref, aV[0], 1); gather_issue(sb + OFF_MEM + WG * 8192 + tv, src); }
          KEEPALIVE(aV[0], zr);
          cp_async_wait_group<0>();
        } while (gather_incomplete<1, 0>(dst) && ++tries < POLL_LIMIT);
        named_bar(1 + WG, 128);
      }
      const uint32_t a_mem = sb + OFF_MEM + WG * 8192 + l16;
      float c[4][4];
#pragma unroll
      for (int i = 0; i < 4; i++) c[i][0] = c[i][1] = c[i][2] = c[i][3] = 0.f;
      uint32_t b[8][4];
#pragma unroll
      for (int p = 0; p < 4; p++) ldsm_x4_t(b[p], a_mem + p * 512);
#pragma unroll
      for (int p = 0; p < 16; p++) {
        if (p + 4 < 16) ldsm_x4_t(b[(p + 4) & 7], a_mem + (p + 4) * 512);
        if (p < 8) { mma16816(c[2 * (p & 1)], aV[2 * p], b[p & 7][0], b[p & 7][1]); mma16816(c[2 * (p & 1) + 1], aV[2 * p + 1], b[p & 7][2], b[p & 7][3]); }
        else { mma16816(c[2 * (p & 1)], rot[2 * p - 16], b[p & 7][0], b[p & 7][1]); mma16816(c[2 * (p & 1) + 1], rot[2 * p - 15], b[p & 7][2], b[p & 7][3]); }
        if (p == 15) SFENCE(15);
      }
      const float4 own = make_float4((c[0][0] + c[1][0]) + (c[2][0] + c[3][0]), (c[0][1] + c[1][1]) + (c[2][1] + c[3][1]),
                                     (c[0][2] + c[1][2]) + (c[2][2] + c[3][2]), (c[0][3] + c[1][3]) + (c[2][3] + c[3][3]));
      NEWZ(1);
      const uint32_t pvm = WG == 0 ? xvm + slot_off(sv) : 0;
      if (WG == 1) sts128f(sb + OFF_VPX + wq * 512 + l16, own);
      named_bar(3, 256);
      if (WG == 0) {
        const float4 o = lds128f(sb + OFF_VPX + wq * 512 + l16);
        st_relaxed2(gptr(xhi, pvm), pack_bf16(own.x + o.x, own.y + o.y), pack_bf16(own.z + o.z, own.w + o.w));
      }
    }
    auto token_pv = [&](int seg, bool staged) {
      constexpr int NU = 2 - WG;
      uint4 pt0, pt1, v0[NU], v1[NU]; uint32_t pm0, pm1; uint2 vm[NU];
      const uint32_t ap = l16 + WG * 4096 + xo::PT, am = (lv >> 2) + WG * 4096 + xo::PM;
      const uint32_t at = ovt - WG * 512;
      if (staged) {
        const uint32_t b = sb + OFF_MEM;
        pt0 = lds128(b + ap); pt1 = lds128(b + ap + 2048); pm0 = lds32(b + am); pm1 = lds32(b + am + 2048);
#pragma unroll
        for (int u = 0; u < NU; u++) { v0[u] = lds128(b + at - u * 2048); v1[u] = lds128(b + at + 512 - u * 2048); vm[u] = lds64(b + ovm - u * 2048); }
      } else {
        const uint32_t b = lds32(sb + CT_HEAD) + slot_off(seg);
        pt0.x = EMPTY;
#pragma unroll
        for (int u = 0; u < NU; u++) {
          v0[u] = ld_relaxed4(gptr(xhi, b + at) - u * 2048); v1[u] = ld_relaxed4(gptr(xhi, b + at) + 512 - u * 2048);
          vm[u] = ld_relaxed2(gptr(xhi, b + ovm) - u * 2048);
        }
      }
      const bool odd = lv & 16;
      char* op = gptr(xhi, lds32(sb + CT_O) + (seg * SEG + WG * 16 + (lv >> 6)) * (HD * 2) + wq * 32 + (lv & 16) + ((lv >> 2) & 8));
      if (!staged || __builtin_expect(warp_incomplete(umax4(pt0.x, pt1.x, pm0, pm1)), 0)) {
        const uint32_t b = lds32(sb + CT_HEAD) + slot_off(seg);
        uint32_t tries = zr;
#pragma unroll 1
        do {
          pt0 = ld_relaxed4(gptr(xhi, b + ap)); pt1 = ld_relaxed4(gptr(xhi, b + ap) + 2048);
          pm0 = ld_relaxed1(gptr(xhi, b + am)); pm1 = ld_relaxed1(gptr(xhi, b + am) + 2048);
        } while (warp_incomplete(umax4(pt0.x, pt1.x, pm0, pm1)) && ++tries < POLL_LIMIT);
      }
      const uint32_t pa[4] = {pt0.x, pt1.x, pt0.y, pt1.y}, pb[4] = {pt0.z, pt1.z, pt0.w, pt1.w};
#pragma unroll
      for (int u = 0; u < NU; u++) {
        float o0[4] = {0.f, 0.f, 0.f, 0.f}, o1[4] = {0.f, 0.f, 0.f, 0.f};
        mma1688(o0, pm0, pm1, vm[u].x); mma1688(o1, pm0, pm1, vm[u].y);
        mma16816(o0, pa, v0[u].x, v0[u].y); mma16816(o1, pa, v1[u].x, v1[u].y);
        if (WG) { mma16816(o0, pb, v0[u].z, v0[u].w); mma16816(o1, pb, v1[u].z, v1[u].w); }
#pragma unroll
        for (int r = 0; r < 2; r++) {
          const uint32_t w0 = pack_bf16(o0[2 * r], o0[2 * r + 1]), w1 = pack_bf16(o1[2 * r], o1[2 * r + 1]);
          const uint32_t rv = __shfl_xor_sync(~0u, odd ? w0 : w1, 1);
          *(uint2*)(op + r * 8 * HD * 2 - u * 64) = odd ? make_uint2(rv, w1) : make_uint2(w0, rv);
        }
      }
    };
    if (!more) {
      named_bar(3, 256);
      if (upper_warps) {
#pragma unroll 1
        for (int seg = NSEG - 2; seg < NSEG; seg++) token_pv(seg, false);
      }
      break;
    }
    {
      if (__builtin_expect(s > 0, 1)) {
        const uint32_t o = WG ? ovt - 512 : tv + 512;
        const char* src = gptr(xhi, lds32(sb + CT_HEAD) + slot_off(sv - 1) + o);
#pragma unroll
        for (int i = 0; i < 3 - WG; i++) cp_async16(sb + OFF_MEM + o + i * 512, src + i * 512);
        cp_async_commit();
      }
      const bool xw = warp_is(3) && s + 2 < NSEG;
      {
        float acc[16];
        mbar_wait<0>(sb + BAR_X + 8 * WG, (s + 1) & 1);
        wg_fence();
#pragma unroll
        for (int ks = 0; ks < 16; ks++) wgmma_m64n32_rs(acc, rot[ks], xdesc<WG>(16 + ks), ks != 0);
        wg_commit();
#pragma unroll
        for (int ks = 0; ks < 16; ks++) wgmma_m64n32_rs(acc, aV[ks], xdesc<WG>(ks), 1);
        wg_commit();
        NEWZ(2);
        const uint32_t pvt = xvt + slot_off(sv + 1), awo = sb + wo_addr(tv);
        if (WG == 0 && warp_is(1) && s >= 0) expect_elect(sb + BAR_EX, 512);
        if (xw) {
          expect_elect(sb + BAR_X + 8 * WG, 32768);
          if (WG == 1 && s + 5 < NSEG) prefetch_l2(maps.xp + (s + 5) * 65536 + lds32(sb + CT_PF), 1024);
        }
        if (__builtin_expect(s < 0, 0)) mbar_wait(sb + BAR_P + 16, 0);
        wg_wait<1>();
#pragma unroll
        for (int ks = 0; ks < 8; ks++) ldsm_x4_t(rot[ks], awo + ks * 1024);
        wg_wait<0>();
        acc_fence(acc);
        constexpr int K = WG * 2, G = 2 - K;
        sts128f(sb + OFF_RED + WG * 1024 + t16, make_float4(acc[G], acc[G + 1], acc[4 + G], acc[5 + G]));
        sts128f(sb + OFF_RED + WG * 1024 + 512 + t16, make_float4(acc[8 + G], acc[9 + G], acc[12 + G], acc[13 + G]));
        cp_async_wait_group<0>();
        named_bar(3, 256);
        const float4 o0 = lds128f(sb + OFF_RED + (WG ^ 1) * 1024 + t16), o1 = lds128f(sb + OFF_RED + (WG ^ 1) * 1024 + 512 + t16);
        if (WG == 1 && xw) issue_x(sb, &maps.x, s + 2, 1);
        st_relaxed4(gptr(xhi, pvt),
                    pack_bf16(acc[K] + o0.x, acc[K + 1] + o0.y), pack_bf16(acc[4 + K] + o0.z, acc[5 + K] + o0.w),
                    pack_bf16(acc[8 + K] + o1.x, acc[9 + K] + o1.y), pack_bf16(acc[12 + K] + o1.z, acc[13 + K] + o1.w));
      }
      if (__builtin_expect(s >= 0, 1)) {
#pragma unroll
        for (int ks = 8; ks < 16 - O_LATE; ks++) ldsm_x4_t(rot[ks], sb + (wo_addr(tv) ^ 32) + (ks & 7) * 1024);
        uint32_t tries = 0;
#pragma unroll
        for (int ks = 0; ks < 16 - O_LATE; ks++) tries |= rot[ks][0];
        tries = __shfl_sync(0xffffffffu, tries & zr, 0);
        tref += lds32(sb + CT_T1) + (WG * T_LAG - T_SLIP);
        float d[2][2][4];
        uint32_t mx;
#pragma unroll 1
        do {
          NEWZ(5);
          const char* po = gptr(xhi, xom + slot_off(sv));
          const uint32_t awo = sb + (wo_addr(tv) ^ 32);
          tref += T_SLIP;
          WAIT_UNTIL(tref, aV[0], 1);
          uint4 o[8];
#pragma unroll
          for (int i = 0; i < 4; i++) o[i] = ld_relaxed4(po + i * 512);
#pragma unroll
          for (int i = 0; i < 4; i++) o[4 + i] = ld_relaxed4(po + 16384 + i * 512);
#pragma unroll
          for (int ks = 8 - O_LATE; ks < 8; ks++) ldsm_x4_t(rot[8 + ks], awo + ks * 1024);
          if (XV_EARLY && WG == 0) issue_x_if(sb, &maps.x, s + 2, 0, xw && tries == 0);
          __syncwarp();
#pragma unroll
          for (int i = 0; i < 2; i++)
#pragma unroll
            for (int q = 0; q < 2; q++) { d[i][q][0] = d[i][q][1] = d[i][q][2] = d[i][q][3] = 0.f; }
#pragma unroll
          for (int i = 0; i < 4; i++) {
            mma16816(d[0][0], aO[2 * i], o[i].x, o[i].y); mma16816(d[1][0], aO[8 + 2 * i], o[i].x, o[i].y);
            mma16816(d[0][1], aO[2 * i + 1], o[i].z, o[i].w); mma16816(d[1][1], aO[9 + 2 * i], o[i].z, o[i].w);
          }
          mx = umax4(o[0].w, o[1].w, o[2].w, o[3].w);
          SFENCE(33 + tries);
#pragma unroll
          for (int i = 0; i < 4; i++) {
            mma16816(d[0][0], rot[2 * i], o[4 + i].x, o[4 + i].y); mma16816(d[1][0], rot[8 + 2 * i], o[4 + i].x, o[4 + i].y);
            mma16816(d[0][1], rot[2 * i + 1], o[4 + i].z, o[4 + i].w); mma16816(d[1][1], rot[9 + 2 * i], o[4 + i].z, o[4 + i].w);
          }
          mx = max(mx, umax4(o[4].w, o[5].w, o[6].w, o[7].w));
        } while (warp_incomplete(mx) && ++tries < POLL_LIMIT);
        NEWZ(3);
        const uint32_t rd = sb + OFF_RED + (WG ^ 1) * 1024 + t16;
        sts128f(rd, make_float4(d[0][0][0] + d[0][1][0], d[0][0][1] + d[0][1][1], d[0][0][2] + d[0][1][2], d[0][0][3] + d[0][1][3]));
        sts128f(rd + 512, make_float4(d[1][0][0] + d[1][1][0], d[1][0][1] + d[1][1][1], d[1][0][2] + d[1][1][2], d[1][0][3] + d[1][1][3]));
        if (upper_warps) {
          named_bar_arrive(7, 256);
          if (!XV_EARLY && WG == 0 && xw) issue_x(sb, &maps.x, s + 2, 0);
          if (__builtin_expect(s > 0, 1)) token_pv(sv - 1, true);
        } else {
          uint32_t mp = lds32(sb + CT_MP) + (lv >> 2);
          named_bar(7, 256);
          float4 p[8];
#pragma unroll
          for (int i = 0; i < 8; i++) p[i] = lds128f(sb + OFF_RED + lv + wq * 512 + i * 1024);
          float4 r;
          r.x = ((p[0].x + p[1].x) + (p[2].x + p[3].x)) + ((p[4].x + p[5].x) + (p[6].x + p[7].x));
          r.y = ((p[0].y + p[1].y) + (p[2].y + p[3].y)) + ((p[4].y + p[5].y) + (p[6].y + p[7].y));
          r.z = ((p[0].z + p[1].z) + (p[2].z + p[3].z)) + ((p[4].z + p[5].z) + (p[6].z + p[7].z));
          r.w = ((p[0].w + p[1].w) + (p[2].w + p[3].w)) + ((p[4].w + p[5].w) + (p[6].w + p[7].w));
          if (warp_is(0)) st_async4(rsb + OFF_RX + lv, __float_as_uint(r.x), __float_as_uint(r.y), __float_as_uint(r.z), __float_as_uint(r.w), rsb + BAR_EX);
          else {
            char* pp = gptr(xhi, mp + slot_off(sv + 1));
            mbar_wait(sb + BAR_EX, s & 1);
            const float4 q = lds128f(sb + OFF_RX + l16);
            st_relaxed1(pp, pack_bf16(r.x + q.x, r.y + q.y)); st_relaxed1(pp + 128, pack_bf16(r.z + q.z, r.w + q.w));
            pp = gptr(xhi, mp + slot_off(sv + 3));
            st_relaxed1(pp, EMPTY); st_relaxed1(pp + 128, EMPTY);
          }
        }
        NEWZ(4);
        const char* src = gptr(xhi, xm + WG * 8192 + slot_off(sv + 1));
        const uint32_t awv = sb + wv_addr(tv) + OFF_WVR;
        tref += lds32(sb + CT_T2) - WG * T_LAG;
        named_bar(8, 256);
#pragma unroll
        for (int ks = 0; ks < V_PRE; ks++) ldsm_x4_t(rot[ks], awv + ks * 2048);
        WAIT_UNTIL(tref, aV[0], 1);
        gather_issue(sb + OFF_MEM + WG * 8192 + tv, src);
#pragma unroll
        for (int ks = V_PRE; ks < 16; ks++) ldsm_x4_t(rot[ks], awv + ks * 2048);
        NEWZ(6);
        st_relaxed4(gptr(xhi, xvt + slot_off(sv + 2)), EMPTY, EMPTY, EMPTY, EMPTY);
        if (WG == 0) st_relaxed2(gptr(xhi, xvm + slot_off(sv + 2)), EMPTY, EMPTY);
      } else {
        load_v(tv);
        if (WG == 0 && xw) issue_x(sb, &maps.x, s + 2, 0);
        grid_wait(sb);
        tref = gtime() / T_SLIP * T_SLIP - T_SLIP;
      }
    }
  }
}

#undef j
#undef s
#undef sv
#undef xm
#undef wq

__global__ void __launch_bounds__(256, 1) __cluster_dims__(2, 1, 1)
chain_kernel(const __grid_constant__ ChainMaps maps, const bf16* __restrict__ mem0, const uint64_t xbase) {
  using namespace chain;
  extern __shared__ uint8_t smem_raw[];
  uint32_t sb = smem_u32(smem_raw);
  PIN(sb);
  if (sb != SB_LO + (blockIdx.x & 1) * RANK_BIT || mapa(sb, (blockIdx.x & 1) ^ 1) != (sb ^ RANK_BIT)) __trap();
  const int tid = threadIdx.x;
  const int h = blockIdx.x >> 2, role = (blockIdx.x >> 1) & 1, j = blockIdx.x & 1;
  if (tid == 0) {
    for (int i = 0; i < 9; i++) mbar_init(sb + OFF_BAR + 8 * i, 1);
    asm volatile("fence.mbarrier_init.release.cluster;" ::: "memory");
    const uint32_t xl = (uint32_t)xbase;
    sts32(sb + CT_BASE, xl); sts32(sb + CT_HEAD, xl + h * xo::HEAD); sts32(sb + CT_OM, xl + xo::OM + (role ? j * 32768 : h * 2048));
    sts32(sb + CT_MP, xl + xo::MEM + (h * 2 + j) * 256); sts32(sb + CT_O, xl + xo::O + (h * 2 + j) * 128); sts32(sb + CT_PF, (h * 2 + j) * 1024);
    sts32(sb + CT_T1, role ? maps.t_phase : maps.t_step); sts32(sb + CT_T2, maps.t_step - maps.t_phase);
    if (role == 0) {
      const CUtensorMap* wm = j ? &maps.wk : &maps.wq;
      mbar_expect_tx(sb + BAR_P, 6 * 16384);
      for (int c = 0; c < 3; c++)
        for (int q = 0; q < 2; q++) tma_load_2d(sb + OFF_X + (q * 3 + c) * 16384, wm, h * DH + q * 64, q * 512 + c * 128, sb + BAR_P);
      mbar_expect_tx(sb + BAR_P + 8, 4 * 16384);
      for (int c = 0; c < 2; c++)
        for (int q = 0; q < 2; q++) tma_load_2d(sb + OFF_X + (6 + q * 2 + c) * 16384, wm, h * DH + (q ^ 1) * 64, q * 512 + c * 128, sb + BAR_P + 8);
      mbar_expect_tx(sb + BAR_P + 24, 4 * 16384);
      for (int q = 0; q < 2; q++)
        for (int o = 0; o < 2; o++) tma_load_2d(sb + OFF_WS + (q * 2 + o) * 16384, wm, h * DH + (q ^ o) * 64, q * 512 + 384, sb + BAR_P + 24);
    } else {
      mbar_expect_tx(sb + BAR_P, 8 * 16384);
      for (int q = 0; q < 4; q++) tma_load_2d(sb + OFF_X + q * 16384, &maps.wv, h * DH + j * 64, (q >> 1) * 512 + (q & 1) * 128, sb + BAR_P);
      for (int q = 0; q < 4; q++) tma_load_2d(sb + OFF_WOR + q * 16384, &maps.wo, h * 32, j * 2048 + q * 256, sb + BAR_P);
      mbar_expect_tx(sb + BAR_P + 8, 4 * 16384);
      for (int q = 0; q < 4; q++) tma_load_2d(sb + OFF_WVR + q * 16384, &maps.wv, h * DH + j * 64, (q >> 1) * 512 + 256 + (q & 1) * 128, sb + BAR_P + 8);
    }
  }
  for (int r = 0; r < RING; r++) {
    char* p = (char*)xbase + r * xo::SLOT;
    const int wq = (tid >> 5) & 3;
    if (role == 1) st_relaxed4(p + h * xo::HEAD + xo::VT + (8 * j + 2 * wq + (tid >> 7)) * 512 + (tid & 31) * 16, EMPTY, EMPTY, EMPTY, EMPTY);
    else if (j == 0) st_relaxed4(p + (tid < 128 ? xo::OM + h * 2048 + tid * 16 : h * xo::HEAD + wq * 2048 + xo::VM + (tid & 31) * 16), EMPTY, EMPTY, EMPTY, EMPTY);
    else {
      st_relaxed4(p + h * xo::HEAD + (tid >> 6) * 2048 + 1024 + (tid & 63) * 16, EMPTY, EMPTY, EMPTY, EMPTY);
      if (tid < 32) st_relaxed4(p + xo::MEM + h * 512 + tid * 16, EMPTY, EMPTY, EMPTY, EMPTY);
    }
  }
  __syncthreads();
  if (tid == 0) {
    __threadfence();
    sts32(sb + GRID_TGT, (atomicAdd(&g_epoch, 1u) & ~127u) + 128u);
  }
  const uint32_t xlo = (uint32_t)xbase, xhi = (uint32_t)(xbase >> 32);
  const int wg = __shfl_sync(0xffffffffu, tid >> 7, 0);
  if (role == 0) {
    if (wg == 0) role_a<0>(maps, mem0, sb, xlo, xhi); else role_a<1>(maps, mem0, sb, xlo, xhi);
  } else {
    if (wg == 0) role_v<0>(maps, mem0, sb, xlo, xhi); else role_v<1>(maps, mem0, sb, xlo, xhi);
  }
  asm volatile("griddepcontrol.launch_dependents;");
  __syncwarp();
  cluster_arrive();
  cluster_wait();
}

struct BMaps { CUtensorMap q, k, v, out, k8; };

#define B_PRAGMA2(x) _Pragma(#x)
#define B_PRAGMA(x) B_PRAGMA2(x)
#define B_UNROLL 4
#define B_SLEEP 200
namespace bp {
constexpr int U_PITCH = (2048 + 128) * 2 + 16;
constexpr int KR_WORDS = 1048;
constexpr int KR_PITCH = 8704;
constexpr int OFF_U = 0;
constexpr int OFF_KR = (8 * U_PITCH + 127) / 128 * 128;
constexpr int Q_OFF = 4352;
constexpr int OFF_BAR = OFF_KR + 8 * KR_PITCH;
constexpr int GROUP_BYTES = OFF_BAR + 128;
constexpr int SMEM = 2 * GROUP_BYTES + 128;
constexpr int NTASK = DM / 8;
static_assert(Q_OFF >= 4224 && Q_OFF + 4096 <= KR_PITCH, "staging does not fit");
}

__device__ __forceinline__ uint32_t bmul2(uint32_t a, uint32_t b) { uint32_t r; asm("mul.rn.bf16x2 %0, %1, %2;" : "=r"(r) : "r"(a), "r"(b)); return r; }
__device__ __forceinline__ uint32_t badd2(uint32_t a, uint32_t b) { uint32_t r; asm("add.rn.bf16x2 %0, %1, %2;" : "=r"(r) : "r"(a), "r"(b)); return r; }
__device__ __forceinline__ void stsm_x4_t(uint32_t addr, uint32_t r0, uint32_t r1, uint32_t r2, uint32_t r3) {
  asm volatile("stmatrix.sync.aligned.m8n8.x4.trans.shared.b16 [%0], {%1,%2,%3,%4};" ::"r"(addr), "r"(r0), "r"(r1), "r"(r2), "r"(r3) : "memory");
}

__device__ __forceinline__ void mbar_wait_sleep(uint32_t bar, uint32_t parity) {
  int guard = 0;
  while (!mbar_try(bar, parity)) { __nanosleep(B_SLEEP); if (++guard > (1 << 22)) __trap(); }
}

__device__ __forceinline__ void bpart_body(const BMaps& maps, const bf16* __restrict__ shift_k, const bf16* __restrict__ ssm_k,
                                           const bf16* __restrict__ ssm_D, int first, int stride, int end) {
  using namespace bp;
  extern __shared__ uint8_t smem_all[];
  const int grp = __shfl_sync(0xffffffffu, threadIdx.x >> 8, 0);
  const int tid = threadIdx.x & 255, lane = tid & 31, g = lane >> 2, t = lane & 3;
  const int w = __shfl_sync(0xffffffffu, tid >> 5, 0);
  const uint32_t sb = ((smem_u32(smem_all) + 127) & ~127u) + grp * GROUP_BYTES;
  const uint32_t bar_kv = sb + OFF_BAR + 8 * w, bar_q = sb + OFF_BAR + 64 + 8 * w;
  if (lane == 0) { mbar_init(bar_kv, 1); mbar_init(bar_q, 1); asm volatile("fence.mbarrier_init.release.cluster;" ::: "memory"); }
  named_bar(1 + grp, 256);
  if (grp == 1) named_bar_arrive(3, 512);
  const int lm = lane >> 3, lr = lane & 7;
  uint32_t ph = 0;
  for (int task = first + grp; task < end; task += stride, ph ^= 1) {
    const int d0 = task * 8;
    if (lane == 0) {
      const uint32_t kr = sb + OFF_KR + w * KR_PITCH;
      mbar_expect_tx(bar_kv, 2 * 4096 + 128);
      tma_load_2d(kr, &maps.k, d0, w * 256 - 8, bar_kv);
      tma_load_2d(kr + 4096, &maps.k8, d0, w * 256 + 248, bar_kv);
      bulk_wait_read<0>();
      tma_load_2d(kr + Q_OFF, &maps.v, d0, w * 256, bar_kv);
    }
    uint4 x[8];
    {
      const uint4* kf = (const uint4*)(ssm_k + (size_t)(d0 + w) * S_LEN);
#pragma unroll
      for (int it = 0; it < 8; it++) x[it] = __ldg(kf + it * 32 + lane);
    }
    uint32_t sk[4];
    {
      const uint4 a = __ldg((const uint4*)(shift_k + (d0 + 2 * t) * 4));
      sk[0] = __byte_perm(a.x, a.z, 0x5410); sk[1] = __byte_perm(a.x, a.z, 0x7632);
      sk[2] = __byte_perm(a.y, a.w, 0x5410); sk[3] = __byte_perm(a.y, a.w, 0x7632);
    }
    const uint32_t dpair = __ldg((const uint32_t*)(ssm_D + d0) + t);
    if (tid < 128) sts128(sb + OFF_U + (tid >> 4) * U_PITCH + (tid & 15) * 16, make_uint4(0, 0, 0, 0));
    mbar_wait_sleep(bar_kv, ph);
    {
      const uint32_t ka = sb + OFF_KR + w * KR_PITCH + (g + 8) * 16 + t * 4, va = sb + OFF_KR + w * KR_PITCH + Q_OFF + g * 16 + t * 4;
B_PRAGMA(unroll B_UNROLL)
      for (int i = 0; i < 8; i++) {
        uint32_t r[4];
#pragma unroll
        for (int b = 0; b < 4; b++) {
          const uint32_t o = (i * 32 + b * 8) * 16;
          uint32_t acc = bmul2(lds32(ka + o - 48), sk[3]);
          acc = badd2(acc, bmul2(lds32(ka + o - 32), sk[2]));
          acc = badd2(acc, bmul2(lds32(ka + o - 16), sk[1]));
          acc = badd2(acc, bmul2(lds32(ka + o), sk[0]));
          r[b] = bmul2(acc, lds32(va + o));
        }
        const int ch = 16 + w * 32 + i * 4 + lm;
        stsm_x4_t(sb + OFF_U + lr * U_PITCH + ((ch ^ ((ch >> 3) & 1)) << 4), r[0], r[1], r[2], r[3]);
      }
    }
    __syncwarp();
    {
      const uint32_t c0 = sb + OFF_KR + w * KR_PITCH, c1 = c0 + (KR_WORDS + 16) * 4;
      uint32_t carry = 0;
#pragma unroll
      for (int it = 0; it < 8; it++) {
        const int blk = it * 32 + lane;
        uint32_t prev = __shfl_up_sync(0xffffffffu, x[it].w, 1);
        if (lane == 0) prev = carry;
        carry = __shfl_sync(0xffffffffu, x[it].w, 31);
        sts128(c0 + (1028 - 4 * blk) * 4, make_uint4(__byte_perm(x[it].w, 0, 0x1032), __byte_perm(x[it].z, 0, 0x1032),
                                                     __byte_perm(x[it].y, 0, 0x1032), __byte_perm(x[it].x, 0, 0x1032)));
        sts128(c1 + (1028 - 4 * blk) * 4, make_uint4(__byte_perm(x[it].w, x[it].z, 0x7610), __byte_perm(x[it].z, x[it].y, 0x7610),
                                                     __byte_perm(x[it].y, x[it].x, 0x7610), __byte_perm(x[it].x, prev, 0x7610)));
      }
      if (lane < 4) { sts128(c0 + (1032 + 4 * lane) * 4, make_uint4(0, 0, 0, 0)); sts128(c1 + (1032 + 4 * lane) * 4, make_uint4(0, 0, 0, 0)); }
      __syncwarp();
    }
    named_bar(1 + grp, 256);
    named_bar(3 + grp, 512);
    float acc[16][4];
#pragma unroll
    for (int jn = 0; jn < 16; jn++) { acc[jn][0] = acc[jn][1] = acc[jn][2] = acc[jn][3] = 0.f; }
    {
      const uint32_t ub = sb + OFF_U + w * U_PITCH;
      const uint32_t kw = sb + OFF_KR + w * KR_PITCH + (((g & 1) ? 0 : KR_WORDS + 16) + ((((g & 1) ? 2063 : 2062) - (g - 2 * t)) >> 1)) * 4;
#pragma unroll 1
      for (int d0s = 0; d0s < 8; d0s++) {
        const int a0 = 8 - d0s + lr;
        const uint32_t uf = ub + (((2 * a0 + (lm & 1)) ^ ((a0 >> 2) & 1)) << 4);
        const uint32_t kd = kw - 32 * d0s;
        uint32_t A[3][4];
        A[0][0] = lds32v(kd); A[0][1] = lds32v(kd - 16); A[0][2] = lds32v(kd + 16); A[0][3] = lds32v(kd);
        uint32_t F[16][2];
#pragma unroll
        for (int m = 0; m < 16; m++) ldsm_x2(F[m][0], F[m][1], uf + m * 256);
#pragma unroll
        for (int i = 0; i < 16; i++) {
          if (i + 1 < 16) {
            A[(i + 1) % 3][0] = lds32v(kd - 256 * (i + 1)); A[(i + 1) % 3][1] = lds32v(kd - 256 * (i + 1) - 16);
            A[(i + 1) % 3][2] = lds32v(kd - 256 * (i + 1) + 16); A[(i + 1) % 3][3] = lds32v(kd - 256 * (i + 1));
          }
#pragma unroll
          for (int jn = 15; jn >= i; jn--) mma16816(acc[jn], A[i % 3], F[jn - i][0], F[jn - i][1]);
        }
      }
    }
    named_bar_arrive(3 + (grp ^ 1), 512);
    const uint32_t qs = sb + OFF_KR + w * KR_PITCH + Q_OFF;
    __syncwarp();
    fence_async_smem();
    __syncwarp();
    if (lane == 0) { mbar_expect_tx(bar_q, 4096); tma_load_2d(qs, &maps.q, d0, w * 256, bar_q); }
    {
      const uint32_t ya = sb + OFF_KR + w * (KR_PITCH + 16) + (((lm >> 1) * 8 + lr) * 32) + (lm & 1) * 16;
#pragma unroll
      for (int jn = 0; jn < 16; jn += 2)
        stsm_x4_t(ya + jn * 256, pack_bf16(acc[jn][0], acc[jn][1]), pack_bf16(acc[jn][2], acc[jn][3]),
                  pack_bf16(acc[jn + 1][0], acc[jn + 1][1]), pack_bf16(acc[jn + 1][2], acc[jn + 1][3]));
    }
    named_bar(1 + grp, 256);
    mbar_wait_sleep(bar_q, ph);
    {
      const uint32_t ya = sb + OFF_KR + lr * (KR_PITCH + 16) + (w * 256 + lm * 8) * 2;
      const uint32_t qa = qs + g * 16 + t * 4;
B_PRAGMA(unroll B_UNROLL)
      for (int i = 0; i < 8; i++) {
        uint32_t y[4], u[4];
        ldsm_x4_t(y, ya + i * 64);
        const int ch = 16 + w * 32 + i * 4 + lm;
        ldsm_x4_t(u, sb + OFF_U + lr * U_PITCH + ((ch ^ ((ch >> 3) & 1)) << 4));
#pragma unroll
        for (int b = 0; b < 4; b++) {
          const uint32_t a = qa + (i * 32 + b * 8) * 16;
          sts32(a, bmul2(lds32(a), badd2(y[b], bmul2(u[b], dpair))));
        }
      }
      fence_async_smem();
      __syncwarp();
      if (lane == 0) { tma_store_2d(&maps.out, qs, DM + d0, w * 256); bulk_commit(); }
    }
    named_bar(1 + grp, 256);
  }
  if (lane == 0) bulk_wait<0>();
}

__global__ void __launch_bounds__(512, 1) __cluster_dims__(2, 1, 1)
bpart_kernel(const __grid_constant__ BMaps maps, const bf16* __restrict__ shift_k, const bf16* __restrict__ ssm_k, const bf16* __restrict__ ssm_D, int end) {
  bpart_body(maps, shift_k, ssm_k, ssm_D, blockIdx.x * 2, gridDim.x * 2, end);
}

struct GemmMaps {
  CUtensorMap o;
  CUtensorMap w;
  CUtensorMap c;
};
namespace k3 {
constexpr int STAGES = 5;
constexpr int W_BYTES = 2 * 8192, O_BYTES = K3_N * 128, STAGE_BYTES = W_BYTES + O_BYTES;
constexpr int TT = (S_LEN + K3_N - 1) / K3_N, NGEMM = TT * (DM / 128), NB = 128 - NGEMM, KSTEPS = HD / 64;
constexpr int SMEM_G = STAGES * STAGE_BYTES + 1024 + 256;
constexpr int SMEM = SMEM_G > bp::SMEM ? SMEM_G : bp::SMEM;
static_assert(STAGE_BYTES % 1024 == 0, "swizzle atoms");
}

__global__ void __launch_bounds__(512, 1)
tail_kernel(const __grid_constant__ GemmMaps maps, const __grid_constant__ BMaps bmaps, const bf16* __restrict__ shift_k,
            const bf16* __restrict__ ssm_k, const bf16* __restrict__ ssm_D) {
  using namespace k3;
  if (blockIdx.x < NB) {
    bpart_body(bmaps, shift_k, ssm_k, ssm_D, bp::NTASK - 2 * NB + 2 * blockIdx.x, bp::NTASK, bp::NTASK);
    return;
  }
  extern __shared__ uint8_t smem_raw[];
  const uint32_t sbase = (smem_u32(smem_raw) + 1023) & ~1023u;
  const uint32_t bars = sbase + STAGES * STAGE_BYTES;
  const int tid = threadIdx.x, warp = tid >> 5;
  const int tt = (blockIdx.x - NB) % TT, ct = (blockIdx.x - NB) / TT;

  if (tid == 0) {
    for (int s = 0; s < STAGES; s++) { mbar_init(bars + 8 * s, 1); mbar_init(bars + 8 * (STAGES + s), 2); }
    asm volatile("fence.mbarrier_init.release.cluster;" ::: "memory");
  }
  __syncthreads();

  if (warp >= 8) {
    if (tid == 256) {
      tma_prefetch_desc(&maps.o);
      for (int k = 0; k < STAGES; k++) {
        const uint32_t full = bars + 8 * k, sa = sbase + k * STAGE_BYTES;
        mbar_expect_tx(full, STAGE_BYTES);
#pragma unroll
        for (int j = 0; j < 2; j++) tma_load_2d(sa + j * 8192, &maps.w, ct * 128 + j * 64, k * 64, full);
      }
      asm volatile("griddepcontrol.wait;" ::: "memory");
      int stage = 0; uint32_t ph = 1;
      for (int k = 0; k < KSTEPS; k++) {
        mbar_wait(bars + 8 * (STAGES + stage), ph);
        const uint32_t full = bars + 8 * stage, sa = sbase + stage * STAGE_BYTES;
        const bool pre = k < STAGES;
        if (!pre) mbar_expect_tx(full, STAGE_BYTES);
        tma_load_2d(sa + W_BYTES, &maps.o, k * 64, tt * K3_N, full);
        if (!pre) {
#pragma unroll
          for (int j = 0; j < 2; j++) tma_load_2d(sa + j * 8192, &maps.w, ct * 128 + j * 64, k * 64, full);
        }
        if (++stage == STAGES) { stage = 0; ph ^= 1; }
      }
    }
  } else {
    const int wg = warp >> 2, lane = tid & 31, wq = warp & 3;
    int stage = 0; uint32_t ph = 0;
    float acc[K3_N / 2];
    int prev = -1;
    for (int k = 0; k < KSTEPS; k++) {
      mbar_wait(bars + 8 * stage, ph);
      const uint32_t sa = sbase + stage * STAGE_BYTES;
      wg_fence();
#pragma unroll
      for (int kk = 0; kk < 4; kk++) {
        const uint64_t da = make_desc(sa + wg * 8192 + kk * 2048, 16, 1024, 1);
        const uint64_t db = make_desc(sa + W_BYTES + kk * 32, 16, 1024, 1);
        wgmma_k3_ss_ta(acc, da, db, (k | kk) != 0);
      }
      wg_commit();
      if (prev >= 0) { wg_wait<1>(); if ((tid & 127) == 0) mbar_arrive(bars + 8 * (STAGES + prev)); }
      prev = stage;
      if (++stage == STAGES) { stage = 0; ph ^= 1; }
    }
    wg_wait<0>();
#pragma unroll
    for (int i = 0; i < K3_N / 2; i++) asm volatile("" : "+f"(acc[i]) :: "memory");
    named_bar(1, 256);
    const uint32_t ebuf = sbase + wg * STAGE_BYTES;
    const uint32_t ea = ebuf + ((lane >> 4) * 8 + (lane & 7)) * 128 + (((2 * wq + ((lane >> 3) & 1)) ^ (lane & 7)) << 4);
#pragma unroll
    for (int i = 0; i < K3_N / 8; i += 2) {
      const int i1 = i + 1 < K3_N / 8 ? i + 1 : i;
      stsm_x4_t(ea + i * 1024, pack_bf16(acc[4 * i], acc[4 * i + 1]), pack_bf16(acc[4 * i + 2], acc[4 * i + 3]),
                pack_bf16(acc[4 * i1], acc[4 * i1 + 1]), pack_bf16(acc[4 * i1 + 2], acc[4 * i1 + 3]));
    }
    fence_async_smem();
    named_bar(2 + wg, 128);
    if ((tid & 127) == 0) {
      tma_store_2d(&maps.c, ebuf, ct * 128 + wg * 64, tt * K3_N);
      bulk_commit();
      bulk_wait<0>();
    }
  }
}

typedef CUresult (*EncodeFn)(CUtensorMap*, CUtensorMapDataType, cuuint32_t, void*, const cuuint64_t*, const cuuint64_t*,
                             const cuuint32_t*, const cuuint32_t*, CUtensorMapInterleave, CUtensorMapSwizzle,
                             CUtensorMapL2promotion, CUtensorMapFloatOOBfill);

void make_map(EncodeFn enc, CUtensorMap* m, const void* ptr, uint64_t cols, uint64_t rows, uint64_t pitch_elems,
              uint32_t box_cols, uint32_t box_rows, CUtensorMapSwizzle swz,
              CUtensorMapL2promotion promo = CU_TENSOR_MAP_L2_PROMOTION_L2_128B) {
  cuuint64_t dims[2] = {cols, rows};
  cuuint64_t strides[1] = {pitch_elems * 2};
  cuuint32_t box[2] = {box_cols, box_rows};
  cuuint32_t es[2] = {1, 1};
  enc(m, CU_TENSOR_MAP_DATA_TYPE_BFLOAT16, 2, const_cast<void*>(ptr), dims, strides, box, es, CU_TENSOR_MAP_INTERLEAVE_NONE, swz,
      promo, CU_TENSOR_MAP_FLOAT_OOB_FILL_NONE);
}

void make_map_nd(EncodeFn enc, CUtensorMap* m, const void* ptr, int rank, const uint64_t* dims, const uint64_t* strides_elems,
                 const uint32_t* box, CUtensorMapSwizzle swz) {
  cuuint64_t d[5], st[4]; cuuint32_t b[5], es[5];
  for (int i = 0; i < rank; i++) { d[i] = dims[i]; b[i] = box[i]; es[i] = 1; if (i) st[i - 1] = strides_elems[i] * 2; }
  enc(m, CU_TENSOR_MAP_DATA_TYPE_BFLOAT16, rank, const_cast<void*>(ptr), d, st, b, es, CU_TENSOR_MAP_INTERLEAVE_NONE, swz,
      CU_TENSOR_MAP_L2_PROMOTION_L2_128B, CU_TENSOR_MAP_FLOAT_OOB_FILL_NONE);
}

}

extern "C" void kernel_launch(void* const* d_in, const int* in_sizes, int n_in, void* d_out, int out_size) {
  (void)in_sizes; (void)n_in; (void)out_size;
  const bf16* x = (const bf16*)d_in[0];
  const bf16* mem0 = (const bf16*)d_in[1];
  const bf16* Wq = (const bf16*)d_in[2];
  const bf16* Wk = (const bf16*)d_in[3];
  const bf16* Wv = (const bf16*)d_in[4];
  const bf16* Wo = (const bf16*)d_in[5];
  const bf16* Bq = (const bf16*)d_in[7];
  const bf16* Bk = (const bf16*)d_in[8];
  const bf16* Bv = (const bf16*)d_in[9];
  const bf16* shift_k = (const bf16*)d_in[10];
  const bf16* ssm_k = (const bf16*)d_in[11];
  const bf16* ssm_D = (const bf16*)d_in[12];
  bf16* out = (bf16*)d_out;

  static EncodeFn enc = nullptr;
  static uint64_t xbase;
  static int nsm = 132;
  static cudaStream_t s1;
  static cudaEvent_t ev_fork, ev_join;
  if (!enc) {
    cudaDriverEntryPointQueryResult qr;
    void* fn = nullptr;
    cudaGetDriverEntryPoint("cuTensorMapEncodeTiled", &fn, cudaEnableDefault, &qr);
    enc = (EncodeFn)fn;
    void* ps = nullptr;
    cudaGetSymbolAddress(&ps, g_scratch);
    xbase = (uint64_t)ps;
    if ((xbase >> 32) != ((xbase + xo::BYTES - 1) >> 32)) xbase += xo::BYTES;
    cudaFuncSetAttribute(tail_kernel, cudaFuncAttributeMaxDynamicSharedMemorySize, k3::SMEM);
    cudaFuncSetAttribute(chain_kernel, cudaFuncAttributeMaxDynamicSharedMemorySize, chain::SMEM);
    cudaFuncSetAttribute(bpart_kernel, cudaFuncAttributeMaxDynamicSharedMemorySize, bp::SMEM);
    cudaStreamCreateWithFlags(&s1, cudaStreamNonBlocking);
    cudaEventCreateWithFlags(&ev_fork, cudaEventDisableTiming);
    cudaEventCreateWithFlags(&ev_join, cudaEventDisableTiming);
    int dev = 0; cudaGetDevice(&dev);
    cudaDeviceGetAttribute(&nsm, cudaDevAttrMultiProcessorCount, dev);
  }
  const CUtensorMapSwizzle SW128 = CU_TENSOR_MAP_SWIZZLE_128B, SW64 = CU_TENSOR_MAP_SWIZZLE_64B;
  GemmMaps m3; ChainMaps mc;
  make_map(enc, &m3.o, (void*)(xbase + xo::O), HD, S_LEN, HD, 64, K3_N, SW128);
  make_map(enc, &m3.w, Wo, DM, HD, DM, 64, 64, SW128);
  make_map(enc, &m3.c, out, DM, S_LEN, OUT_LD, 64, K3_N, SW128);
  const CUtensorMapL2promotion P256 = CU_TENSOR_MAP_L2_PROMOTION_L2_256B;
  make_map(enc, &mc.wq, Wq, HD, DM, HD, 64, 128, SW128, P256);
  make_map(enc, &mc.wk, Wk, HD, DM, HD, 64, 128, SW128, P256);
  make_map(enc, &mc.wv, Wv, HD, DM, HD, 64, 128, SW128, P256);
  make_map(enc, &mc.wo, Wo, DM, HD, DM, 32, 256, SW64, P256);
  {
    const uint64_t dx[3] = {64, S_LEN, DM / 64}, sx[3] = {1, DM, 64};
    const uint32_t bx[3] = {64, SEG, 8};
    make_map_nd(enc, &mc.x, x, 3, dx, sx, bx, SW128);
    mc.xp = (const char*)x;
  }

  const int skip = 0;
  mc.t_step = T_STEP; mc.t_phase = T_PHASE;
  BMaps mb;
  const CUtensorMapSwizzle SWN = CU_TENSOR_MAP_SWIZZLE_NONE;
  make_map(enc, &mb.q, Bq, DM, S_LEN, DM, 8, 256, SWN);
  make_map(enc, &mb.k, Bk, DM, S_LEN, DM, 8, 256, SWN);
  make_map(enc, &mb.v, Bv, DM, S_LEN, DM, 8, 256, SWN);
  make_map(enc, &mb.out, out, OUT_LD, S_LEN, OUT_LD, 8, 256, SWN);
  make_map(enc, &mb.k8, Bk, DM, S_LEN, DM, 8, 8, SWN);
  cudaStream_t s0 = cudaStreamPerThread;
  const int nb = nsm >= 132 ? 4 : 2, ntask1 = bp::NTASK - 2 * k3::NB;
  const bool fork = nsm >= 130;
  if (fork) {
    cudaEventRecord(ev_fork, s0);
    cudaStreamWaitEvent(s1, ev_fork, 0);
    if (!(skip & 1)) bpart_kernel<<<nb, 512, bp::SMEM, s1>>>(mb, shift_k, ssm_k, ssm_D, ntask1);
    cudaEventRecord(ev_join, s1);
  } else {
    bpart_kernel<<<ntask1 / 2, 512, bp::SMEM, s0>>>(mb, shift_k, ssm_k, ssm_D, ntask1);
  }
  if (!(skip & 4)) chain_kernel<<<128, 256, chain::SMEM, s0>>>(mc, mem0, xbase);
  if (!(skip & 8)) {
    cudaLaunchAttribute pdl[1];
    pdl[0].id = cudaLaunchAttributeProgrammaticStreamSerialization;
    pdl[0].val.programmaticStreamSerializationAllowed = 1;
    cudaLaunchConfig_t cfg = {};
    cfg.gridDim = dim3(128); cfg.blockDim = dim3(512); cfg.dynamicSmemBytes = k3::SMEM; cfg.stream = s0;
    cfg.attrs = pdl; cfg.numAttrs = 1;
    cudaLaunchKernelEx(&cfg, tail_kernel, m3, mb, shift_k, ssm_k, ssm_D);
  }
  if (fork) cudaStreamWaitEvent(s0, ev_join, 0);
}
```

```cpp
#include <cuda_runtime.h>
#include <cuda_bf16.h>
#include <cuda.h>
#include <stdint.h>

namespace {

constexpr int S_LEN = 2048;
constexpr int DM = 1024;
constexpr int NH = 32;
constexpr int DH = 128;
constexpr int HD = NH * DH;
constexpr int SEG = 32;
constexpr int NSEG = S_LEN / SEG;
constexpr int OUT_LD = 2048;

typedef __nv_bfloat16 bf16;
#define K3_N 160

__device__ __forceinline__ uint32_t smem_u32(const void* p) { return (uint32_t)__cvta_generic_to_shared(p); }

__device__ __forceinline__ void mbar_init(uint32_t bar, uint32_t count) {
  asm volatile("mbarrier.init.shared::cta.b64 [%0], %1;" ::"r"(bar), "r"(count) : "memory");
}
__device__ __forceinline__ void mbar_expect_tx(uint32_t bar, uint32_t bytes) {
  asm volatile("mbarrier.arrive.expect_tx.shared::cta.b64 _, [%0], %1;" ::"r"(bar), "r"(bytes) : "memory");
}
__device__ __forceinline__ void mbar_arrive(uint32_t bar) {
  asm volatile("mbarrier.arrive.shared::cta.b64 _, [%0];" ::"r"(bar) : "memory");
}
__device__ __forceinline__ bool mbar_try(uint32_t bar, uint32_t parity) {
  uint32_t ok;
  asm volatile("{.reg .pred p; mbarrier.try_wait.parity.shared::cta.b64 p, [%1], %2; selp.u32 %0, 1, 0, p;}"
               : "=r"(ok) : "r"(bar), "r"(parity) : "memory");
  return ok;
}
__device__ __forceinline__ bool mbar_test(uint32_t bar, uint32_t parity) {
  uint32_t ok;
  asm volatile("{.reg .pred p; mbarrier.test_wait.parity.shared::cta.b64 p, [%1], %2; selp.u32 %0, 1, 0, p;}"
               : "=r"(ok) : "r"(bar), "r"(parity) : "memory");
  return ok;
}
template <int HINT = 1>
__device__ __forceinline__ void mbar_wait(uint32_t bar, uint32_t parity) {
  int guard = 0;
  while (__builtin_expect(!mbar_try(bar, parity), HINT)) { if (++guard > (1 << 22)) __trap(); }
}
__device__ __forceinline__ void tma_load_2d(uint32_t dst, const CUtensorMap* map, int c0, int c1, uint32_t bar) {
  asm volatile("cp.async.bulk.tensor.2d.shared::cluster.global.mbarrier::complete_tx::bytes [%0], [%1, {%3, %4}], [%2];"
               ::"r"(dst), "l"(map), "r"(bar), "r"(c0), "r"(c1) : "memory");
}
__device__ __forceinline__ void tma_load_3d(uint32_t dst, const CUtensorMap* map, int c0, int c1, int c2, uint32_t bar) {
  asm volatile("cp.async.bulk.tensor.3d.shared::cluster.global.mbarrier::complete_tx::bytes [%0], [%1, {%3, %4, %5}], [%2];"
               ::"r"(dst), "l"(map), "r"(bar), "r"(c0), "r"(c1), "r"(c2) : "memory");
}
__device__ __forceinline__ void tma_load_4d(uint32_t dst, const CUtensorMap* map, int c0, int c1, int c2, int c3, uint32_t bar) {
  asm volatile("cp.async.bulk.tensor.4d.shared::cluster.global.mbarrier::complete_tx::bytes [%0], [%1, {%3, %4, %5, %6}], [%2];"
               ::"r"(dst), "l"(map), "r"(bar), "r"(c0), "r"(c1), "r"(c2), "r"(c3) : "memory");
}
__device__ __forceinline__ void tma_store_2d(const CUtensorMap* map, uint32_t src, int c0, int c1) {
  asm volatile("cp.async.bulk.tensor.2d.global.shared::cta.bulk_group [%0, {%2, %3}], [%1];"
               ::"l"(map), "r"(src), "r"(c0), "r"(c1) : "memory");
}
__device__ __forceinline__ void tma_prefetch_2d(const CUtensorMap* map, int c0, int c1) {
  asm volatile("cp.async.bulk.prefetch.tensor.2d.L2.global [%0, {%1, %2}];" ::"l"(map), "r"(c0), "r"(c1) : "memory");
}
__device__ __forceinline__ void tma_prefetch_desc(const CUtensorMap* map) {
  asm volatile("prefetch.tensormap [%0];" ::"l"(map) : "memory");
}
__device__ __forceinline__ void fence_async_smem() { asm volatile("fence.proxy.async.shared::cta;" ::: "memory"); }
__device__ __forceinline__ void bulk_commit() { asm volatile("cp.async.bulk.commit_group;" ::: "memory"); }
template <int N> __device__ __forceinline__ void bulk_wait_read() { asm volatile("cp.async.bulk.wait_group.read %0;" ::"n"(N) : "memory"); }
template <int N> __device__ __forceinline__ void bulk_wait() { asm volatile("cp.async.bulk.wait_group %0;" ::"n"(N) : "memory"); }
__device__ __forceinline__ void named_bar(int id, int n) { asm volatile("bar.sync %0, %1;" ::"r"(id), "r"(n) : "memory"); }

__device__ __forceinline__ void named_bar_arrive(int id, int n) { asm volatile("bar.arrive %0, %1;" ::"r"(id), "r"(n) : "memory"); }
__device__ __forceinline__ float ex2(float x) { float y; asm("ex2.approx.ftz.f32 %0, %1;" : "=f"(y) : "f"(x)); return y; }
__device__ __forceinline__ float rcp(float x) { float y; asm("rcp.approx.ftz.f32 %0, %1;" : "=f"(y) : "f"(x)); return y; }

__device__ __forceinline__ void sts32(uint32_t a, uint32_t x) { asm volatile("st.shared.b32 [%0], %1;" ::"r"(a), "r"(x) : "memory"); }
__device__ __forceinline__ uint32_t lds32(uint32_t a) { uint32_t x; asm volatile("ld.shared.b32 %0, [%1];" : "=r"(x) : "r"(a) : "memory"); return x; }
__device__ __forceinline__ uint32_t lds32v(uint32_t a) { uint32_t x; asm volatile("ld.volatile.shared.b32 %0, [%1];" : "=r"(x) : "r"(a) : "memory"); return x; }
__device__ __forceinline__ void sts128(uint32_t a, const uint4& v) { asm volatile("st.shared.v4.b32 [%0], {%1,%2,%3,%4};" ::"r"(a), "r"(v.x), "r"(v.y), "r"(v.z), "r"(v.w) : "memory"); }
__device__ __forceinline__ void sts128f(uint32_t a, const float4& v) { asm volatile("st.shared.v4.f32 [%0], {%1,%2,%3,%4};" ::"r"(a), "f"(v.x), "f"(v.y), "f"(v.z), "f"(v.w) : "memory"); }
__device__ __forceinline__ uint4 lds128(uint32_t a) { uint4 v; asm volatile("ld.shared.v4.b32 {%0,%1,%2,%3}, [%4];" : "=r"(v.x), "=r"(v.y), "=r"(v.z), "=r"(v.w) : "r"(a) : "memory"); return v; }
__device__ __forceinline__ float4 lds128f(uint32_t a) { float4 v; asm volatile("ld.shared.v4.f32 {%0,%1,%2,%3}, [%4];" : "=f"(v.x), "=f"(v.y), "=f"(v.z), "=f"(v.w) : "r"(a) : "memory"); return v; }

__device__ __forceinline__ void cp_async16(uint32_t dst, const void* src) { asm volatile("cp.async.cg.shared.global [%0], [%1], 16;" ::"r"(dst), "l"(src) : "memory"); }
__device__ __forceinline__ void cp_async_commit() { asm volatile("cp.async.commit_group;" ::: "memory"); }
template <int N> __device__ __forceinline__ void cp_async_wait_group() { asm volatile("cp.async.wait_group %0;" ::"n"(N) : "memory"); }

__device__ __forceinline__ void wg_fence() { asm volatile("wgmma.fence.sync.aligned;" ::: "memory"); }
__device__ __forceinline__ void wg_commit() { asm volatile("wgmma.commit_group.sync.aligned;" ::: "memory"); }
template <int N> __device__ __forceinline__ void wg_wait() { asm volatile("wgmma.wait_group.sync.aligned %0;" ::"n"(N) : "memory"); }
__device__ __forceinline__ uint64_t make_desc(uint32_t addr, uint32_t lbo, uint32_t sbo, uint32_t swz) {
  return (uint64_t)((addr & 0x3FFFF) >> 4) | ((uint64_t)(lbo >> 4) << 16) | ((uint64_t)(sbo >> 4) << 32) | ((uint64_t)swz << 62);
}

__device__ __forceinline__ void ldsm_x4(uint32_t (&r)[4], uint32_t addr) {
  asm volatile("ldmatrix.sync.aligned.m8n8.x4.shared.b16 {%0,%1,%2,%3}, [%4];"
               : "=r"(r[0]), "=r"(r[1]), "=r"(r[2]), "=r"(r[3]) : "r"(addr) : "memory");
}
__device__ __forceinline__ void ldsm_x4_t(uint32_t (&r)[4], uint32_t addr) {
  asm volatile("ldmatrix.sync.aligned.m8n8.x4.trans.shared.b16 {%0,%1,%2,%3}, [%4];"
               : "=r"(r[0]), "=r"(r[1]), "=r"(r[2]), "=r"(r[3]) : "r"(addr) : "memory");
}
__device__ __forceinline__ void ldsm_x2(uint32_t& r0, uint32_t& r1, uint32_t addr) {
  asm volatile("ldmatrix.sync.aligned.m8n8.x2.shared.b16 {%0,%1}, [%2];" : "=r"(r0), "=r"(r1) : "r"(addr) : "memory");
}
__device__ __forceinline__ void stsm_x4(uint32_t addr, uint32_t r0, uint32_t r1, uint32_t r2, uint32_t r3) {
  asm volatile("stmatrix.sync.aligned.m8n8.x4.shared.b16 [%0], {%1,%2,%3,%4};"
               ::"r"(addr), "r"(r0), "r"(r1), "r"(r2), "r"(r3) : "memory");
}
__device__ __forceinline__ void mma16816(float (&c)[4], const uint32_t (&a)[4], uint32_t b0, uint32_t b1) {
  asm volatile("mma.sync.aligned.m16n8k16.row.col.f32.bf16.bf16.f32 {%0,%1,%2,%3}, {%4,%5,%6,%7}, {%8,%9}, {%0,%1,%2,%3};"
               : "+f"(c[0]), "+f"(c[1]), "+f"(c[2]), "+f"(c[3])
               : "r"(a[0]), "r"(a[1]), "r"(a[2]), "r"(a[3]), "r"(b0), "r"(b1));
}
__device__ __forceinline__ void mma1688(float (&c)[4], uint32_t a0, uint32_t a1, uint32_t b0) {
  asm volatile("mma.sync.aligned.m16n8k8.row.col.f32.bf16.bf16.f32 {%0,%1,%2,%3}, {%4,%5}, {%6}, {%0,%1,%2,%3};"
               : "+f"(c[0]), "+f"(c[1]), "+f"(c[2]), "+f"(c[3]) : "r"(a0), "r"(a1), "r"(b0));
}
__device__ __forceinline__ uint32_t pack_bf16(float lo, float hi) {
  uint32_t r;
  asm("cvt.rn.bf16x2.f32 %0, %1, %2;" : "=r"(r) : "f"(hi), "f"(lo));
  return r;
}
__device__ __forceinline__ float bf_lo(uint32_t w) { return __uint_as_float(w << 16); }
__device__ __forceinline__ float bf_hi(uint32_t w) { return __uint_as_float(w & 0xFFFF0000u); }

__device__ __forceinline__ uint4 ld_relaxed4(const void* p) {
  uint4 v;
  asm volatile("ld.relaxed.gpu.global.v4.u32 {%0,%1,%2,%3}, [%4];" : "=r"(v.x), "=r"(v.y), "=r"(v.z), "=r"(v.w) : "l"(p) : "memory");
  return v;
}
__device__ __forceinline__ void st_relaxed4(void* p, uint32_t a, uint32_t b, uint32_t c, uint32_t d) {
  asm volatile("st.relaxed.gpu.global.v4.u32 [%0], {%1,%2,%3,%4};" ::"l"(p), "r"(a), "r"(b), "r"(c), "r"(d) : "memory");
}
__device__ __forceinline__ void st_relaxed2(void* p, uint32_t a, uint32_t b) {
  asm volatile("st.relaxed.gpu.global.v2.u32 [%0], {%1,%2};" ::"l"(p), "r"(a), "r"(b) : "memory");
}
__device__ __forceinline__ void st_relaxed1(void* p, uint32_t a) {
  asm volatile("st.relaxed.gpu.global.u32 [%0], %1;" ::"l"(p), "r"(a) : "memory");
}

__device__ __forceinline__ uint2 ld_relaxed2(const void* p) {
  uint2 v;
  asm volatile("ld.relaxed.gpu.global.v2.u32 {%0,%1}, [%2];" : "=r"(v.x), "=r"(v.y) : "l"(p) : "memory");
  return v;
}
__device__ __forceinline__ void sts64(uint32_t a, uint32_t x, uint32_t y) { asm volatile("st.shared.v2.b32 [%0], {%1,%2};" ::"r"(a), "r"(x), "r"(y) : "memory"); }
__device__ __forceinline__ uint2 lds64(uint32_t a) { uint2 v; asm volatile("ld.shared.v2.b32 {%0,%1}, [%2];" : "=r"(v.x), "=r"(v.y) : "r"(a) : "memory"); return v; }
__device__ __forceinline__ void lds128r(uint32_t (&r)[4], uint32_t a) {
  asm volatile("ld.shared.v4.b32 {%0,%1,%2,%3}, [%4];" : "=r"(r[0]), "=r"(r[1]), "=r"(r[2]), "=r"(r[3]) : "r"(a) : "memory");
}
__device__ __forceinline__ uint32_t movmat(uint32_t a) { uint32_t d; asm volatile("movmatrix.sync.aligned.m8n8.trans.b16 %0, %1;" : "=r"(d) : "r"(a)); return d; }
__device__ __forceinline__ uint32_t mapa(uint32_t addr, uint32_t rank) { uint32_t r; asm volatile("mapa.shared::cluster.u32 %0, %1, %2;" : "=r"(r) : "r"(addr), "r"(rank)); return r; }
__device__ __forceinline__ void st_async1(uint32_t dst, uint32_t a, uint32_t bar) {
  asm volatile("st.async.weak.shared::cluster.mbarrier::complete_tx::bytes.b32 [%0], %1, [%2];" ::"r"(dst), "r"(a), "r"(bar) : "memory");
}
__device__ __forceinline__ void st_async2(uint32_t dst, uint32_t a, uint32_t b, uint32_t bar) {
  asm volatile("st.async.weak.shared::cluster.mbarrier::complete_tx::bytes.v2.b32 [%0], {%1,%2}, [%3];" ::"r"(dst), "r"(a), "r"(b), "r"(bar) : "memory");
}
__device__ __forceinline__ void st_async4(uint32_t dst, uint32_t a, uint32_t b, uint32_t c, uint32_t d, uint32_t bar) {
  asm volatile("st.async.weak.shared::cluster.mbarrier::complete_tx::bytes.v4.b32 [%0], {%1,%2,%3,%4}, [%5];" ::"r"(dst), "r"(a), "r"(b), "r"(c), "r"(d), "r"(bar) : "memory");
}
__device__ __forceinline__ void cluster_arrive() { asm volatile("barrier.cluster.arrive.relaxed.aligned;" ::: "memory"); }
__device__ __forceinline__ void cluster_wait() { asm volatile("barrier.cluster.wait.acquire.aligned;" ::: "memory"); }

__device__ __forceinline__ void wgmma_k3_ss_ta(float (&d)[80], uint64_t da, uint64_t db, int scale_d) {
  asm volatile("{.reg .pred p; setp.ne.b32 p, %82, 0;\n"
    "wgmma.mma_async.sync.aligned.m64n160k16.f32.bf16.bf16 {%0, %1, %2, %3, %4, %5, %6, %7, %8, %9, %10, %11, %12, %13, %14, %15, %16, %17, %18, %19, %20, %21, %22, %23, %24, %25, %26, %27, %28, %29, %30, %31, %32, %33, %34, %35, %36, %37, %38, %39, %40, %41, %42, %43, %44, %45, %46, %47, %48, %49, %50, %51, %52, %53, %54, %55, %56, %57, %58, %59, %60, %61, %62, %63, %64, %65, %66, %67, %68, %69, %70, %71, %72, %73, %74, %75, %76, %77, %78, %79}, %80, %81, p, 1, 1, 1, 0;}"
    : "+f"(d[0]), "+f"(d[1]), "+f"(d[2]), "+f"(d[3]), "+f"(d[4]), "+f"(d[5]), "+f"(d[6]), "+f"(d[7]), "+f"(d[8]), "+f"(d[9]), "+f"(d[10]), "+f"(d[11]), "+f"(d[12]), "+f"(d[13]), "+f"(d[14]), "+f"(d[15]), "+f"(d[16]), "+f"(d[17]), "+f"(d[18]), "+f"(d[19]), "+f"(d[20]), "+f"(d[21]), "+f"(d[22]), "+f"(d[23]), "+f"(d[24]), "+f"(d[25]), "+f"(d[26]), "+f"(d[27]), "+f"(d[28]), "+f"(d[29]), "+f"(d[30]), "+f"(d[31]), "+f"(d[32]), "+f"(d[33]), "+f"(d[34]), "+f"(d[35]), "+f"(d[36]), "+f"(d[37]), "+f"(d[38]), "+f"(d[39]), "+f"(d[40]), "+f"(d[41]), "+f"(d[42]), "+f"(d[43]), "+f"(d[44]), "+f"(d[45]), "+f"(d[46]), "+f"(d[47]), "+f"(d[48]), "+f"(d[49]), "+f"(d[50]), "+f"(d[51]), "+f"(d[52]), "+f"(d[53]), "+f"(d[54]), "+f"(d[55]), "+f"(d[56]), "+f"(d[57]), "+f"(d[58]), "+f"(d[59]), "+f"(d[60]), "+f"(d[61]), "+f"(d[62]), "+f"(d[63]), "+f"(d[64]), "+f"(d[65]), "+f"(d[66]), "+f"(d[67]), "+f"(d[68]), "+f"(d[69]), "+f"(d[70]), "+f"(d[71]), "+f"(d[72]), "+f"(d[73]), "+f"(d[74]), "+f"(d[75]), "+f"(d[76]), "+f"(d[77]), "+f"(d[78]), "+f"(d[79])
    : "l"(da), "l"(db), "r"(scale_d));
}
__device__ __forceinline__ void wgmma_m64n32_ss_ta(float (&d)[16], uint64_t da, uint64_t db, int scale_d) {
  asm volatile("{.reg .pred p; setp.ne.b32 p, %18, 0;\n"
    "wgmma.mma_async.sync.aligned.m64n32k16.f32.bf16.bf16 {%0, %1, %2, %3, %4, %5, %6, %7, %8, %9, %10, %11, %12, %13, %14, %15}, %16, %17, p, 1, 1, 1, 0;}"
    : "+f"(d[0]), "+f"(d[1]), "+f"(d[2]), "+f"(d[3]), "+f"(d[4]), "+f"(d[5]), "+f"(d[6]), "+f"(d[7]), "+f"(d[8]), "+f"(d[9]), "+f"(d[10]), "+f"(d[11]), "+f"(d[12]), "+f"(d[13]), "+f"(d[14]), "+f"(d[15])
    : "l"(da), "l"(db), "r"(scale_d));
}

__device__ __forceinline__ void wgmma_m64n32_rs(float (&d)[16], const uint32_t (&a)[4], uint64_t db, int scale_d) {
  asm volatile("{.reg .pred p; setp.ne.b32 p, %21, 0;\n"
    "wgmma.mma_async.sync.aligned.m64n32k16.f32.bf16.bf16 {%0, %1, %2, %3, %4, %5, %6, %7, %8, %9, %10, %11, %12, %13, %14, %15}, {%16, %17, %18, %19}, %20, p, 1, 1, 0;}"
    : "+f"(d[0]), "+f"(d[1]), "+f"(d[2]), "+f"(d[3]), "+f"(d[4]), "+f"(d[5]), "+f"(d[6]), "+f"(d[7]), "+f"(d[8]), "+f"(d[9]), "+f"(d[10]), "+f"(d[11]), "+f"(d[12]), "+f"(d[13]), "+f"(d[14]), "+f"(d[15])
    : "r"(a[0]), "r"(a[1]), "r"(a[2]), "r"(a[3]), "l"(db), "r"(scale_d));
}

#define X_POS 5
#define T_STEP 2880
#define T_PHASE 1824
#define T_LAG 32
#define T_TOL 192
#define T_SLIP 640
#define O_FIX 5
#define VM_POS 2
#define V_PRE 6
#define SFENCE(i) asm volatile("{.reg .pred p; setp.eq.u32 p, %0, %1; @p trap;}" ::"r"(n), "r"(4096 + (i)) : "memory")
constexpr int RING = 4;
constexpr uint32_t EMPTY = 0xFFFFFFFFu;
namespace xo {
constexpr uint32_t SLOT = 1u << 20, HEAD = 16384;
constexpr uint32_t VM = 512;
constexpr uint32_t PT = 1024;
constexpr uint32_t PM = 1536;
constexpr uint32_t VT = 8192;
constexpr uint32_t MEM = NH * HEAD;
constexpr uint32_t OM = MEM + 16384;
constexpr uint32_t O = RING * SLOT;
constexpr uint32_t BYTES = O + S_LEN * HD * 2;
}
__device__ __align__(1024) uint4 g_scratch[2 * (xo::BYTES / 16)];
__device__ unsigned g_epoch;

struct ChainMaps {
  CUtensorMap wq, wk, wv;
  CUtensorMap wo;
  CUtensorMap x, xq;
  const char* xp;
  uint32_t t_step, t_phase;
};

namespace chain {
constexpr int OFF_X = 65536;
constexpr int OFF_MEM = 131072;
constexpr int OFF_WS = 0;
constexpr int OFF_FP = 147456;
constexpr int OFF_KT = 163840;
constexpr int OFF_QT = 180224;
constexpr int OFF_VT = 196608;
constexpr int OFF_PX = 204800;
constexpr int OFF_S4 = OFF_PX + 1536;
constexpr int OFF_QM = 212992;
constexpr int OFF_KM = 215040;
constexpr int OFF_S1 = 217088;
constexpr int OFF_WVR = 0;
constexpr int OFF_WOR = 147456;
constexpr int OFF_RED = 212992;
constexpr int OFF_VPX = 221184;
constexpr int OFF_RX = 223232;
constexpr int OFF_TR = 225280;
constexpr int OFF_BAR = 229376;
constexpr int BAR_X = OFF_BAR, BAR_TOK = OFF_BAR + 16, BAR_EX = OFF_BAR + 32, BAR_P = OFF_BAR + 40, GRID_TGT = OFF_BAR + 128;
constexpr int CT_BASE = GRID_TGT + 4, CT_HEAD = GRID_TGT + 8, CT_OM = GRID_TGT + 12, CT_MP = GRID_TGT + 16, CT_O = GRID_TGT + 20, CT_PF = GRID_TGT + 24;
constexpr int CT_T1 = GRID_TGT + 32, CT_T2 = GRID_TGT + 36;
constexpr uint32_t RANK_BIT = 1u << 24;
constexpr int SMEM = OFF_BAR + 256;
constexpr uint32_t SB_LO = 1024;
constexpr float SCALE = 0.08838834764831845f, L2E = 1.4426950408889634f;
}

__device__ __forceinline__ uint32_t umax4(uint32_t a, uint32_t b, uint32_t c, uint32_t d) { return max(max(a, b), max(c, d)); }
__device__ __forceinline__ bool warp_incomplete(uint32_t m) { return __any_sync(0xffffffffu, m == EMPTY); }
#define PIN(x) asm volatile("" : "+r"(x))
#define KEEPALIVE(a, z) do { float _d0, _d1, _d2, _d3; asm volatile("mma.sync.aligned.m16n8k16.row.col.f32.bf16.bf16.f32 {%0,%1,%2,%3}, {%4,%5,%6,%7}, {%4,%5}, {%8,%8,%8,%8};" \
    : "=f"(_d0), "=f"(_d1), "=f"(_d2), "=f"(_d3) : "r"(a[0]), "r"(a[1]), "r"(a[2]), "r"(a[3]), "f"(0.f)); \
      \
    asm volatile("{.reg .pred p; setp.ne.u32 p, %0, 0; @p st.shared.f32 [%0], %1;}" ::"r"(z), "f"(_d0 + _d3) : "memory"); } while (0)
constexpr int POLL_LIMIT = 1 << 17;

__device__ __forceinline__ uint32_t keep(uint32_t x) { return __shfl_sync(0xffffffffu, x, threadIdx.x & 31); }
__device__ __forceinline__ char* gptr(uint32_t hi, uint32_t lo) { return (char*)(((uint64_t)hi << 32) | lo); }
__device__ __forceinline__ uint32_t slot_off(int n) { return ((uint32_t)n & (RING - 1)) * xo::SLOT; }
__device__ __forceinline__ float quad_max(float x) {
  const float a = __shfl_xor_sync(~0u, x, 1), b = __shfl_xor_sync(~0u, x, 2), c = __shfl_xor_sync(~0u, x, 3);
  return fmaxf(fmaxf(x, a), fmaxf(b, c));
}
__device__ __forceinline__ void acc_fence(float (&a)[16]) {
#pragma unroll
  for (int i = 0; i < 16; i++) asm volatile("" : "+f"(a[i]) :: "memory");
}
template <int NB = 1, int STRIDE = 0>
__device__ __forceinline__ void gather_issue(uint32_t dst, const char* src) {
#pragma unroll
  for (int b = 0; b < NB; b++)
#pragma unroll
    for (int i = 0; i < 4; i++) cp_async16(dst + b * STRIDE + i * 512, src + b * STRIDE + i * 512);
  cp_async_commit();
}
template <int NB, int STRIDE>
__device__ __forceinline__ bool gather_incomplete(uint32_t chk) {
  uint32_t m = 0;
#pragma unroll
  for (int b = 0; b < NB; b++) m = max(m, umax4(lds32(chk + b * STRIDE), lds32(chk + b * STRIDE + 512), lds32(chk + b * STRIDE + 1024), lds32(chk + b * STRIDE + 1536)));
  return warp_incomplete(m);
}
__device__ __forceinline__ uint32_t ld_relaxed1(const void* p) {
  uint32_t v;
  asm volatile("ld.relaxed.gpu.global.u32 %0, [%1];" : "=r"(v) : "l"(p) : "memory");
  return v;
}
__device__ __forceinline__ uint32_t gtime() { uint64_t g; asm volatile("mov.u64 %0, %%globaltimer;" : "=l"(g) :: "memory"); return (uint32_t)g; }
#define WAIT_UNTIL(t, ka, alive, id) do { \
    int _d = gtime() - (t); \
    if (__builtin_expect(_d > T_TOL, 0)) do { t += T_SLIP; _d -= T_SLIP; } while (_d > T_TOL); \
    if (alive) for (int _k = 64; _d < -96 && --_k; _d = gtime() - (t)) KEEPALIVE(ka, zr); \
    for (uint32_t _g = -128; (int)(_d & ++_g) < 0;) _d = gtime() - (t); } while (0)
__device__ __forceinline__ void issue_x(uint32_t sb, const CUtensorMap* map, int n, int part, int q = 0) {
  asm volatile("{.reg .pred p; elect.sync _|p, 0xffffffff;\n"
               "@p cp.async.bulk.tensor.3d.shared::cluster.global.mbarrier::complete_tx::bytes [%0], [%1, {%3, %4, %5}], [%2];}"
               ::"r"(sb + chain::OFF_X + part * 32768 + q * 16384), "l"(map), "r"(sb + chain::BAR_X + 8 * part), "r"(0), "r"(n * SEG), "r"(part * 8 + q * 4) : "memory");
}
__device__ __forceinline__ void issue_x_if(uint32_t sb, const CUtensorMap* map, int n, int part, uint32_t on) {
  asm volatile("{.reg .pred p, q; elect.sync _|p, 0xffffffff; setp.ne.and.u32 q, %6, 0, p;\n"
               "@q cp.async.bulk.tensor.3d.shared::cluster.global.mbarrier::complete_tx::bytes [%0], [%1, {%3, %4, %5}], [%2];}"
               ::"r"(sb + chain::OFF_X + part * 32768), "l"(map), "r"(sb + chain::BAR_X + 8 * part), "r"(0), "r"(n * SEG), "r"(part * 8), "r"(on) : "memory");
}
__device__ __forceinline__ void prefetch_l2(const char* p, uint32_t bytes) {
  asm volatile("{.reg .pred p; elect.sync _|p, 0xffffffff; @p cp.async.bulk.prefetch.L2.global [%0], %1;}" ::"l"(p), "r"(bytes) : "memory");
}
__device__ __forceinline__ void expect_elect(uint32_t bar, uint32_t bytes) {
  asm volatile("{.reg .pred p; elect.sync _|p, 0xffffffff; @p mbarrier.arrive.expect_tx.shared::cta.b64 _, [%0], %1;}" ::"r"(bar), "r"(bytes) : "memory");
}
template <int WG> __device__ __forceinline__ constexpr uint64_t xdesc(int ks) {
  return (uint64_t)(((chain::SB_LO + chain::OFF_X + WG * 32768 + (ks >> 2) * 4096 + (ks & 3) * 32) >> 4) + (1u << 16)) |
         ((uint64_t)(64u | (1u << 30)) << 32);
}
template <int WG> __device__ __forceinline__ constexpr uint64_t wdesc(int o, int ks) {
  return (uint64_t)(((chain::SB_LO + chain::OFF_WS + WG * 32768 + o * 16384 + ks * 2048) >> 4) + (1u << 16)) | ((uint64_t)(64u | (1u << 30)) << 32);
}
__device__ __forceinline__ void load_mem0(uint2 (&m)[8], const bf16* __restrict__ mem0) {
#pragma unroll
  for (int r = 0; r < 8; r++) m[r] = ld_relaxed2((const uint2*)(mem0 + r * DM) + threadIdx.x);
}
__device__ __forceinline__ void store_mem0(uint32_t sb, const uint2 (&m)[8]) {
  const uint32_t d = sb + chain::OFF_MEM + threadIdx.x * 64;
  sts128(d, make_uint4(__byte_perm(m[0].x, m[1].x, 0x5410), __byte_perm(m[2].x, m[3].x, 0x5410), __byte_perm(m[4].x, m[5].x, 0x5410), __byte_perm(m[6].x, m[7].x, 0x5410)));
  sts128(d + 16, make_uint4(__byte_perm(m[0].x, m[1].x, 0x7632), __byte_perm(m[2].x, m[3].x, 0x7632), __byte_perm(m[4].x, m[5].x, 0x7632), __byte_perm(m[6].x, m[7].x, 0x7632)));
  sts128(d + 32, make_uint4(__byte_perm(m[0].y, m[1].y, 0x5410), __byte_perm(m[2].y, m[3].y, 0x5410), __byte_perm(m[4].y, m[5].y, 0x5410), __byte_perm(m[6].y, m[7].y, 0x5410)));
  sts128(d + 48, make_uint4(__byte_perm(m[0].y, m[1].y, 0x7632), __byte_perm(m[2].y, m[3].y, 0x7632), __byte_perm(m[4].y, m[5].y, 0x7632), __byte_perm(m[6].y, m[7].y, 0x7632)));
}
template <int K> __device__ __forceinline__ uint32_t loop_zero(int n) { uint32_t z; asm volatile("shr.u32 %0, %1, %2;" : "=r"(z) : "r"(n), "n"(16 + K)); return z; }
#define NEWZ(k) zr = loop_zero<k>(n)

template <int WG>
__device__ __forceinline__ void role_a(const ChainMaps& maps, const bf16* __restrict__ mem0, const uint32_t sb, const uint32_t xbase_hi) {
  using namespace chain;
  const int h = blockIdx.x >> 2;
  const bool J = sb >= RANK_BIT;
  const uint32_t u16 = (threadIdx.x & 96) * 64 + (threadIdx.x & 31) * 16;
  const uint32_t t16 = keep(u16), l16 = keep((threadIdx.x & 31) * 16);
  const uint32_t a_wl = keep((((threadIdx.x >> 4) & 1) * 8 + (threadIdx.x & 7)) * 128 + (((((threadIdx.x >> 4) & 6) + ((threadIdx.x >> 3) & 1)) ^ (threadIdx.x & 7)) << 4));
  const uint32_t xhi = keep(xbase_hi + (t16 >> 16));
#define xh (lds32(sb + CT_HEAD) + t16)
#define xm (lds32(sb + CT_BASE) + t16 + xo::MEM)
#define last_warp __any_sync(0xffffffffu, tv >= 6144)
#define tv (t16 ^ zr)
  const CUtensorMap* wm = J ? &maps.wk : &maps.wq;

  uint32_t aW[2][24][4];
  uint2 m0[8];
  load_mem0(m0, mem0);
  mbar_wait(sb + BAR_P, 0);
#pragma unroll
  for (int ks = 0; ks < 24; ks++) ldsm_x4_t(aW[0][ks], sb + a_wl + OFF_X + WG * 49152 + ks * 2048);
  named_bar(0, 256);
  if (WG == 1 && __any_sync(0xffffffffu, t16 >= 6144)) {
    fence_async_smem();
    if (l16 == 0) {
      mbar_expect_tx(sb + BAR_P + 16, 2 * 16384);
      for (int q = 0; q < 2; q++) tma_load_2d(sb + OFF_X + (4 + q) * 16384, wm, h * DH + (q ^ 1) * 64, q * 512 + 256, sb + BAR_P + 16);
    }
    __syncwarp();
    expect_elect(sb + BAR_X, 32768); expect_elect(sb + BAR_X + 8, 32768); expect_elect(sb + BAR_TOK, 8192);
    issue_x(sb, &maps.x, 0, 0); issue_x(sb, &maps.x, 0, 1);
  }
  mbar_wait(sb + BAR_P + 8, 0);
#pragma unroll
  for (int ks = 0; ks < 16; ks++) ldsm_x4_t(aW[1][ks], sb + a_wl + OFF_X + 6 * 16384 + WG * 32768 + ks * 2048);
  mbar_wait(sb + BAR_P + 16, 0);
#pragma unroll
  for (int ks = 0; ks < 8; ks++) ldsm_x4_t(aW[1][16 + ks], sb + a_wl + OFF_X + (4 + WG) * 16384 + ks * 2048);
  named_bar(0, 256);
  cluster_arrive();
  store_mem0(sb, m0);
  mbar_wait(sb + BAR_P + 24, 0);
  cluster_wait();
  const uint32_t rsb = sb ^ RANK_BIT;
  const uint32_t a_ws = sb + a_wl + OFF_WS + WG * 32768;

  uint32_t ws[2][4][4];
  auto load_ws = [&]() {
#pragma unroll
    for (int q = 0; q < 2; q++) {
      const uint32_t a = a_ws + q * 4096;
      ldsm_x4_t(ws[q][0], a); ldsm_x4_t(ws[q][1], a + 16384); ldsm_x4_t(ws[q][2], a + 2048); ldsm_x4_t(ws[q][3], a + 16384 + 2048);
    }
  };
  uint32_t tref = 0;
#pragma unroll 1
  for (int n = 0; n <= (J ? NSEG : NSEG - 1); n++) {
#define s (n - 1)
#define sv ((int)(n ^ zr) - 1)
    const bool more = __builtin_expect(s + 1 < NSEG, 1);
    uint32_t zr = loop_zero<0>(n);
#define wq ((int)(tv >> 11))
#define lv (l16 ^ zr)
#define gh (xh + slot_off(sv))
    uint32_t tmp[4][4];
    auto load_tmp = [&](int o) {
#pragma unroll
      for (int ks = 0; ks < 4; ks++) ldsm_x4_t(tmp[ks], a_ws + o * 16384 + ks * 2048);
    };
    auto wait_x = [&]() { mbar_wait<0>(sb + BAR_X + 8 * WG, n & 1); };
    if (__builtin_expect(s < 0, 0)) { load_tmp(1); wait_x(); }
    else {
      {
        if (WG == 1) { if (__builtin_expect(s > 0, 1)) {
          const uint32_t chk = sb + OFF_MEM + t16 + ((lv >> 5) & 12);
          uint32_t tries = zr;
#pragma unroll 1
          do {
            if (tries) {
              const char* src = gptr(xhi, xm + slot_off(sv));
              tref += T_SLIP;
              WAIT_UNTIL(tref, aW[0][0], 1, -1);
              gather_issue<2, 8192>(sb + OFF_MEM + tv, src);
            }
            KEEPALIVE(aW[0][0], zr);
            cp_async_wait_group<0>();
          } while (gather_incomplete<2, 8192>(chk) && ++tries < POLL_LIMIT);
        } } else if (J == 0) {
          uint32_t tries = s == 0;
#pragma unroll 1
          do {
            if (tries) gather_issue(sb + OFF_VT + tv, gptr(xhi, gh) + xo::VT);
            cp_async_wait_group<0>();
          } while (gather_incomplete<1, 0>(sb + OFF_VT + t16 + ((lv >> 5) & 12)) && ++tries < POLL_LIMIT);
        }
        named_bar(1, 256);
      }
      float c[2][2][4];
#pragma unroll
      for (int i = 0; i < 4; i++) c[i >> 1][i & 1][0] = c[i >> 1][i & 1][1] = c[i >> 1][i & 1][2] = c[i >> 1][i & 1][3] = 0.f;
      {
        const uint32_t a_mem = sb + OFF_MEM + WG * 8192 + l16;
        uint32_t b[4][4];
        bool tok;
        constexpr int PR[16] = {12, 13, 0, 1, 2, 3, 4, 14, 5, 6, 7, 8, 9, 15, 10, 11};
        ldsm_x4_t(b[0], a_mem + PR[0] * 512); ldsm_x4_t(b[1], a_mem + PR[1] * 512);
#pragma unroll
        for (int i = 0; i < 16; i++) {
          if ((i & 1) == 0 && i < 14) {
            ldsm_x4_t(b[(i + 2) & 3], a_mem + PR[i + 2] * 512); ldsm_x4_t(b[(i + 3) & 3], a_mem + PR[i + 3] * 512);
            if (i == 2 || i == 8) { ldsm_x4_t(ws[1][0], a_ws + (i == 2 ? 2 : 3) * 4096); ldsm_x4_t(ws[1][1], a_ws + (i == 2 ? 2 : 3) * 4096 + 16384); }
            if (i == 4 || i == 10) { ldsm_x4_t(ws[1][2], a_ws + (i == 4 ? 2 : 3) * 4096 + 2048); ldsm_x4_t(ws[1][3], a_ws + (i == 4 ? 2 : 3) * 4096 + 16384 + 2048); }
          }
          const int p = PR[i];
          if (p >= 12) {
            const int z = i != 0;
            mma16816(c[0][0], ws[z][0], b[i & 3][0], b[i & 3][1]); mma16816(c[1][0], ws[z][1], b[i & 3][0], b[i & 3][1]);
            mma16816(c[0][1], ws[z][2], b[i & 3][2], b[i & 3][3]); mma16816(c[1][1], ws[z][3], b[i & 3][2], b[i & 3][3]);
          } else {
            mma16816(c[1][0], aW[1][2 * p], b[i & 3][0], b[i & 3][1]); mma16816(c[1][1], aW[1][2 * p + 1], b[i & 3][2], b[i & 3][3]);
            mma16816(c[0][0], aW[0][2 * p], b[i & 3][0], b[i & 3][1]); mma16816(c[0][1], aW[0][2 * p + 1], b[i & 3][2], b[i & 3][3]);
          }
          if (i == 12) tok = mbar_test(sb + BAR_TOK + 8 * (s & 1), (s >> 1) & 1);
          if (i == 15 && __builtin_expect(!tok, 0)) mbar_wait(sb + BAR_TOK + 8 * (s & 1), (s >> 1) & 1);
          if (i == X_POS + 4 * (1 - WG)) { issue_x_if(sb, &maps.x, s + 1, WG, t16 >= 6144 && more); if (WG) __syncwarp(); }
        }
      }
      sts128f(sb + OFF_PX + WG * 512 + t16, make_float4(c[1][0][0] + c[1][1][0], c[1][0][1] + c[1][1][1], c[1][0][2] + c[1][1][2], c[1][0][3] + c[1][1][3]));
      const float4 own = make_float4(c[0][0][0] + c[0][1][0], c[0][0][1] + c[0][1][1], c[0][0][2] + c[0][1][2], c[0][0][3] + c[0][1][3]);
      NEWZ(1);
      uint32_t a = (J ? OFF_KM : OFF_QM) + WG * 1024 + wq * 256 + (lv >> 2);
      uint32_t ra = rsb + a, ra2 = ra + 128, rx = rsb + BAR_EX + zr;
      PIN(a); PIN(ra); PIN(ra2); PIN(rx);
      SFENCE(16);
      named_bar(3, 256);
      {
        const float4 o = lds128f(sb + OFF_PX + (WG ^ 1) * 512 + t16);
        const uint32_t lo = pack_bf16(own.x + o.x, own.y + o.y), hi = pack_bf16(own.z + o.z, own.w + o.w);
        if (J == 1 && more) { st_async1(ra, lo, rx); st_async1(ra2, hi, rx); }
        sts32(sb + a, lo); sts32(sb + a + 128, hi);
      }
      const uint32_t kt = sb + OFF_KT + (s & 1) * 8192;
      auto load_kb = [&](uint32_t (&d)[4], uint32_t a) { const uint2 u = lds64(a), v = lds64(a + 1024); d[0] = u.x; d[1] = u.y; d[2] = v.x; d[3] = v.y; };
      if (J == 0) {
        uint32_t am[4][4], kb[4][4];
        uint2 vm0, vm1;
        const char* pvm = WG == 0 ? gptr(xhi, gh - (lv >> 1)) + xo::VM : nullptr;
        if (WG == 0 && VM_POS == 0) { vm0 = ld_relaxed2(pvm); vm1 = ld_relaxed2(pvm + 256); }
        if (WG == 1) {
#pragma unroll
          for (int p = 0; p < 4; p++) load_kb(kb[p], kt + wq * 256 + (lv >> 1) + p * 2048);
        }
        named_bar(7, 256);
#pragma unroll
        for (int p = 0; p < 4; p++) ldsm_x4_t(am[p], sb + OFF_QM + p * 512 + ((lv & 128) << 1) + ((lv & 256) >> 1) + (lv & 112));
        auto scores = [&]() {
          float c0[2][4], c1[2][4];
#pragma unroll
          for (int i = 0; i < 2; i++) { c0[i][0] = c0[i][1] = c0[i][2] = c0[i][3] = 0.f; c1[i][0] = c1[i][1] = c1[i][2] = c1[i][3] = 0.f; }
#pragma unroll
          for (int p = 0; p < 4; p++) { mma16816(c0[p & 1], am[p], kb[p][0], kb[p][1]); mma16816(c1[p & 1], am[p], kb[p][2], kb[p][3]); }
          const uint32_t r1 = pack_bf16((c0[0][0] + c0[1][0]) + (c1[0][2] + c1[1][2]), (c0[0][1] + c0[1][1]) + (c1[0][3] + c1[1][3]));
          return pack_bf16(bf_lo(r1) * SCALE, bf_hi(r1) * SCALE);
        };
        if (WG == 1) {
          const uint32_t st = scores();
          uint32_t vb[4][4];
#pragma unroll
          for (int e = 0; e < 4; e++) lds128r(vb[e], sb + OFF_VT + t16 + e * 512);
          __syncwarp();
          sts32(sb + OFF_S4 + l16 + wq * 4, st);
          named_bar(8, 128);
          const uint4 sc = lds128(sb + OFF_S4 + l16);
          float x[8] = {bf_lo(sc.x), bf_hi(sc.x), bf_lo(sc.y), bf_hi(sc.y), bf_lo(sc.z), bf_hi(sc.z), bf_lo(sc.w), bf_hi(sc.w)};
          float mx = fmaxf(fmaxf(fmaxf(x[0], x[1]), fmaxf(x[2], x[3])), fmaxf(fmaxf(x[4], x[5]), fmaxf(x[6], x[7])));
          mx = quad_max(mx);
          const float mb = mx * L2E;
#pragma unroll
          for (int i = 0; i < 8; i++) x[i] = ex2(fmaf(x[i], L2E, -mb));
          uint32_t pa[4], pb[4];
          asm volatile("" : "=r"(pa[1]), "=r"(pa[3]), "=r"(pb[1]), "=r"(pb[3]));
          pa[0] = pack_bf16(x[0], x[1]); pa[2] = pack_bf16(x[2], x[3]);
          pb[0] = pack_bf16(x[4], x[5]); pb[2] = pack_bf16(x[6], x[7]);
          float oa[4][4];
#pragma unroll
          for (int e = 0; e < 4; e++) { oa[e][0] = oa[e][1] = oa[e][2] = oa[e][3] = 0.f; mma16816(oa[e], pa, vb[e][0], vb[e][1]); }
#pragma unroll
          for (int e = 0; e < 4; e++) mma16816(oa[e], pb, vb[e][2], vb[e][3]);
          sts64(sb + OFF_PX + 1024 + t16, __float_as_uint(mx), __float_as_uint(((x[0] + x[1]) + (x[2] + x[3])) + ((x[4] + x[5]) + (x[6] + x[7]))));
          sts128f(sb + OFF_PX + t16, make_float4(oa[0][0], oa[0][1], oa[1][0], oa[1][1]));
          sts128f(sb + OFF_PX + 512 + t16, make_float4(oa[2][0], oa[2][1], oa[3][0], oa[3][1]));
          named_bar_arrive(9, 256);
          wait_x();
          load_tmp(1);
        } else {
          if (VM_POS == 1) { pvm += am[3][0] & zr; vm0 = ld_relaxed2(pvm); vm1 = ld_relaxed2(pvm + 256); }
          const uint32_t xo0 = lds32(sb + CT_OM) + wq * 512 + l16;
          mbar_wait<0>(sb + BAR_EX, s & 1);
          if (VM_POS == 2) { vm0 = ld_relaxed2(pvm); vm1 = ld_relaxed2(pvm + 256); }
#pragma unroll
          for (int p = 0; p < 4; p++) ldsm_x4_t(kb[p], sb + OFF_KM + p * 512 + l16);
          const uint32_t sm = scores();
          float mx = quad_max(fmaxf(bf_lo(sm), bf_hi(sm)));
          SFENCE(25);
          named_bar(9, 256);
          const uint2 ms = lds64(sb + OFF_PX + 1024 + t16);
          const float4 t0 = lds128f(sb + OFF_PX + t16), t1 = lds128f(sb + OFF_PX + 512 + t16);
          mx = fmaxf(mx, __uint_as_float(ms.x));
          const float mb = mx * L2E;
          const float e0 = ex2(fmaf(bf_lo(sm), L2E, -mb)), e1 = ex2(fmaf(bf_hi(sm), L2E, -mb)), ct = ex2(fmaf(__uint_as_float(ms.x), L2E, -mb));
          uint32_t p4 = pack_bf16(e0, e1), p5;
          asm volatile("" : "=r"(p5));
          float sx = fmaf(ct, __uint_as_float(ms.y), e0 + e1);
          float oa[4][4] = {{t0.x * ct, t0.y * ct, 0.f, 0.f}, {t0.z * ct, t0.w * ct, 0.f, 0.f}, {t1.x * ct, t1.y * ct, 0.f, 0.f}, {t1.z * ct, t1.w * ct, 0.f, 0.f}};
          const float s1 = __shfl_xor_sync(~0u, sx, 1), s2 = __shfl_xor_sync(~0u, sx, 2), s3 = __shfl_xor_sync(~0u, sx, 3);
          if (__builtin_expect(warp_incomplete(max(vm0.x, vm1.x)), 0)) {
            uint32_t tries = zr;
#pragma unroll 1
            do { vm0 = ld_relaxed2(pvm); vm1 = ld_relaxed2(pvm + 256); } while (warp_incomplete(max(vm0.x, vm1.x)) && ++tries < POLL_LIMIT);
          }
          mma1688(oa[0], p4, p5, vm0.x); mma1688(oa[1], p4, p5, vm0.y); mma1688(oa[2], p4, p5, vm1.x); mma1688(oa[3], p4, p5, vm1.y);
          const float rx = rcp((sx + s1) + (s2 + s3));
          st_relaxed4(gptr(xhi, xo0 + slot_off(sv)), pack_bf16(oa[0][0] * rx, oa[0][1] * rx), pack_bf16(oa[1][0] * rx, oa[1][1] * rx),
                      pack_bf16(oa[2][0] * rx, oa[2][1] * rx), pack_bf16(oa[3][0] * rx, oa[3][1] * rx));
          SFENCE(24);
          named_bar_arrive(10, 256);
          st_relaxed4(gptr(xhi, xo0 + slot_off(sv + 3)), EMPTY, EMPTY, EMPTY, EMPTY);
          load_tmp(1);
          wait_x();
        }
      } else {
        bool xok;
        {
          const int mt = WG | (wq == 3), ktile = wq == 3 ? 2 + WG : wq - 1;
          const uint32_t qt = sb + OFF_QT + (s & 1) * 8192 + mt * 512 + l16;
          uint32_t kb[4][4], q[8][4];
          if (__any_sync(0xffffffffu, tv < 2048)) {
            named_bar(7, 256);
#pragma unroll
            for (int p = 0; p < 4; p++) ldsm_x4_t(kb[p], sb + OFF_KM + p * 512 + l16);
          } else {
            named_bar_arrive(7, 256);
#pragma unroll
            for (int p = 0; p < 4; p++) load_kb(kb[p], kt + (lv >> 1) + ktile * 256 + p * 2048);
          }
#pragma unroll
          for (int i = 0; i < 8; i++) lds128r(q[i], qt + i * 1024);
          __syncwarp();
          float c0[4][4];
#pragma unroll
          for (int i = 0; i < 4; i++) { c0[i][0] = c0[i][1] = c0[i][2] = c0[i][3] = 0.f; mma16816(c0[i], q[i], kb[i >> 1][(i & 1) * 2], kb[i >> 1][(i & 1) * 2 + 1]); }
#pragma unroll
          for (int i = 0; i < 4; i++) mma16816(c0[i], q[4 + i], kb[2 + (i >> 1)][(i & 1) * 2], kb[2 + (i >> 1)][(i & 1) * 2 + 1]);
          load_tmp(1);
          xok = mbar_test(sb + BAR_X + 8 * WG, n & 1);
          NEWZ(3);
          const uint32_t r0 = pack_bf16((c0[0][0] + c0[1][0]) + (c0[2][0] + c0[3][0]), (c0[0][1] + c0[1][1]) + (c0[2][1] + c0[3][1]));
          const uint32_t r1 = pack_bf16((c0[0][2] + c0[1][2]) + (c0[2][2] + c0[3][2]), (c0[0][3] + c0[1][3]) + (c0[2][3] + c0[3][3]));
          const uint32_t sa = wq == 0 ? sb + OFF_S1 + (lv >> 2) + mt * 256 : sb + OFF_S4 + l16 + mt * 4096 + ktile * 4;
          sts32(sa, pack_bf16(bf_lo(r0) * SCALE, bf_hi(r0) * SCALE));
          sts32(sa + (wq == 0 ? 128 : 2048), pack_bf16(bf_lo(r1) * SCALE, bf_hi(r1) * SCALE));
        }
        if (WG == 1) named_bar_arrive(8, 256);
        else {
          if (more) named_bar_arrive(10, 256);
          const uint32_t gp = gh;
          named_bar(8, 256);
          const uint4 sc = lds128(sb + OFF_S4 + t16); const uint32_t s1 = lds32(sb + OFF_S1 + wq * 128 + (lv >> 2));
          float y[10] = {bf_lo(s1), bf_hi(s1), bf_lo(sc.x), bf_hi(sc.x), bf_lo(sc.y), bf_hi(sc.y), bf_lo(sc.z), bf_hi(sc.z), bf_lo(sc.w), bf_hi(sc.w)};
          const int rel = wq * 8 + (int)(lv >> 6) - (int)((lv >> 3) & 6);
          const float NEG = -999292928.f;
#pragma unroll
          for (int e = 0; e < 4; e++) {
            if (e * 8 > rel) y[2 * e + 2] = NEG;
            if (e * 8 + 1 > rel) y[2 * e + 3] = NEG;
          }
          float my = fmaxf(fmaxf(fmaxf(y[0], y[1]), fmaxf(y[2], y[3])), fmaxf(fmaxf(y[4], y[5]), fmaxf(y[6], y[7])));
          my = quad_max(fmaxf(my, fmaxf(y[8], y[9])));
#pragma unroll
          for (int i = 0; i < 10; i++) y[i] = ex2((y[i] - my) * L2E);
          float sy = ((y[0] + y[1]) + (y[2] + y[3])) + ((y[4] + y[5]) + (y[6] + y[7])) + (y[8] + y[9]);
          const float ry = rcp((sy + __shfl_xor_sync(~0u, sy, 1)) + (__shfl_xor_sync(~0u, sy, 2) + __shfl_xor_sync(~0u, sy, 3)));
          st_relaxed4(gptr(xhi, gp) + xo::PT, pack_bf16(y[2] * ry, y[3] * ry), pack_bf16(y[4] * ry, y[5] * ry), pack_bf16(y[6] * ry, y[7] * ry), pack_bf16(y[8] * ry, y[9] * ry));
          const uint32_t l12 = lv - (lv >> 2);
          st_relaxed1(gptr(xhi, gp - l12) + xo::PM, pack_bf16(y[0] * ry, y[1] * ry));
        }
        if (!xok && more) wait_x();
      }
    }
    if (more) {
      float acc[16];
      const uint32_t xph = (s + 1) & 1;
      auto batch = [&](const uint32_t (&a)[24][4], int o) {
        wg_fence();
#pragma unroll
        for (int ks = 4; ks < 8; ks++) wgmma_m64n32_ss_ta(acc, wdesc<WG>(o, ks), xdesc<WG>(24 + ks), ks != 4);
#pragma unroll
        for (int ks = 0; ks < 4; ks++) wgmma_m64n32_rs(acc, tmp[ks], xdesc<WG>(24 + ks), 1);
#pragma unroll
        for (int ks = 0; ks < 24; ks++) wgmma_m64n32_rs(acc, a[ks], xdesc<WG>(ks), 1);
        wg_commit();
      };
      if (WG == 0) named_bar(12, 256);
      else if (__builtin_expect(s >= 0, 1)) named_bar(10, 256);
      batch(aW[1], 1);
      named_bar_arrive(WG ? 12 : 13, 256);
      wg_wait<0>();
      acc_fence(acc);
      load_tmp(0);
#pragma unroll
      for (int i = 0; i < 4; i++) sts128f(sb + OFF_FP + WG * 8192 + t16 + i * 512, make_float4(acc[4 * i], acc[4 * i + 1], acc[4 * i + 2], acc[4 * i + 3]));
      NEWZ(4);
      if (WG == 0 && s >= 0) {
        const uint32_t g1 = xh + slot_off(sv + 1);
        if (J == 0) gather_issue(sb + OFF_VT + tv, gptr(xhi, g1) + xo::VT);
        else {
          st_relaxed4(gptr(xhi, g1) + xo::PT, EMPTY, EMPTY, EMPTY, EMPTY);
          st_relaxed1(gptr(xhi, g1 - lv + (lv >> 2)) + xo::PM, EMPTY);
        }
      }
      uint32_t esrc = 0;
      if (WG == 1) { esrc = xm + slot_off(sv + 1); tref += lds32(sb + CT_T1); }
      named_bar(WG ? 13 : 14, 256);
      batch(aW[0], 0);
      NEWZ(5);
      if (WG == 1) {
        named_bar(14, 256);
        if (last_warp && s + 2 < NSEG) {
          expect_elect(sb + BAR_TOK + 8 * (xph ^ 1), 8192); expect_elect(sb + BAR_X, 32768); expect_elect(sb + BAR_X + 8, 32768);
          if (J == 0) expect_elect(sb + BAR_EX, 2048);
        }
      }
      float4 oth[4];
#pragma unroll
      for (int i = 0; i < 4; i++) oth[i] = lds128f(sb + OFF_FP + (WG ^ 1) * 8192 + t16 + i * 512);
      if (WG == 1 && __builtin_expect(s >= 0, 1)) {
        WAIT_UNTIL(tref, aW[0][0], 0, 0);
        gather_issue<2, 8192>(sb + OFF_MEM + tv, gptr(xhi, esrc));
      }
      wg_wait<0>();
      acc_fence(acc);
      uint32_t lt[4], ht[4];
#pragma unroll
      for (int i = 0; i < 4; i++) {
        const float4 o = oth[i];
        lt[i] = movmat(pack_bf16(acc[4 * i] + o.x, acc[4 * i + 1] + o.y)); ht[i] = movmat(pack_bf16(acc[4 * i + 2] + o.z, acc[4 * i + 3] + o.w));
      }
      NEWZ(6);
      uint32_t tb = xph * 8192 + WG * 4096 + wq * 1024;
      if (J == 0) {
        tb += OFF_QT;
        sts128(sb + tb + l16, make_uint4(lt[0], lt[1], ht[0], ht[1])); sts128(sb + tb + 512 + l16, make_uint4(lt[2], lt[3], ht[2], ht[3]));
      } else {
        tb += OFF_KT;
#pragma unroll
        for (int i = 0; i < 4; i++) sts64(sb + tb + (lv >> 1) + i * 256, lt[i], ht[i]);
      }
      if (WG == 0 && last_warp) {
        load_ws();
        named_bar(11, 256);
        fence_async_smem();
        const uint32_t tt = (J ? OFF_KT : OFF_QT) + xph * 8192;
        asm volatile("{.reg .pred p; elect.sync _|p, 0xffffffff;\n"
                     "@p cp.async.bulk.shared::cluster.shared::cta.mbarrier::complete_tx::bytes [%0], [%1], 8192, [%2];}"
                     ::"r"(rsb + tt), "r"(sb + tt), "r"(rsb + BAR_TOK + 8 * xph) : "memory");
      } else {
        named_bar_arrive(11, 256);
        load_ws();
      }
    }
    if (!more) break;
    if (__builtin_expect(s < 0, 0)) {
      tref = gtime() / T_SLIP * T_SLIP - T_SLIP;
    }
  }
  cp_async_wait_group<0>();
  if (J == 0) mbar_wait(sb + BAR_TOK + 8, 1);
}

template <int WG>
__device__ __forceinline__ void role_v(const ChainMaps& maps, const bf16* __restrict__ mem0, const uint32_t sb, const uint32_t xbase_hi) {
  using namespace chain;
  const int h = blockIdx.x >> 2;
  const uint32_t u16 = (threadIdx.x & 96) * 64 + (threadIdx.x & 31) * 16;
  const uint32_t t16 = keep(u16), l16 = keep((threadIdx.x & 31) * 16);
  const uint32_t xhi = keep(xbase_hi + (t16 >> 16));
#define j (sb >> 24)
  auto wv_addr = [&](uint32_t t) { return WG * 32768 + ((t & 256) << 2) + ((t & 112) << 3) + ((((t >> 6) & 96) + ((t >> 3) & 16)) ^ (t & 112)); };
  auto wo_addr = [&](uint32_t t) { return OFF_WOR + WG * 32768 + ((t & 6144) << 2) + ((t & 256) << 1) + ((t & 112) << 2) + ((((j ^ 1) << 5) + ((t >> 3) & 16)) ^ ((t >> 1) & 48)); };
#define ovt (((tv + l16) >> 1) + (xo::VT + WG * 512 + j * 4096))
#define ovm (((tv & 4096) >> 1) + ((tv & 2048) >> 3) + (lv >> 1) + (xo::VM + j * 4096))
#define xvt (lds32(sb + CT_HEAD) + ovt)
#define xvm (lds32(sb + CT_HEAD) + ovm)
#define xom (lds32(sb + CT_OM) + t16 + WG * 8192)
#define warp_is(q) __any_sync(0xffffffffu, (tv >> 11) == (q))
#define upper_warps (WG == 1 || __any_sync(0xffffffffu, tv >= 4096))

  uint32_t aV[16][4];
  uint32_t aO[16][4];
  uint32_t bO[16][4];
  uint32_t rot[16][4];
  if (WG == 1 && __any_sync(0xffffffffu, t16 >= 6144)) {
    expect_elect(sb + BAR_X, 32768); expect_elect(sb + BAR_X + 8, 32768);
    issue_x(sb, &maps.x, 0, 0); issue_x(sb, &maps.x, 0, 1);
    prefetch_l2(maps.xp + 65536 + (h * 2 + j) * 3072, 3072);
  }
  cluster_arrive();
  { uint2 m0[8]; load_mem0(m0, mem0); store_mem0(sb, m0); }
  mbar_wait(sb + BAR_P, 0);
#pragma unroll
  for (int ks = 0; ks < 16; ks++) ldsm_x4_t(aV[ks], sb + wv_addr(t16) + OFF_WOR + ks * 2048);
  auto load_v = [&](uint32_t t) {
#pragma unroll
    for (int ks = 0; ks < 16; ks++) ldsm_x4_t(rot[ks], sb + wv_addr(t) + OFF_WVR + ks * 2048);
  };
  load_v(t16);
  named_bar(0, 256);
  if (threadIdx.x == 0) {
    fence_async_smem();
    mbar_expect_tx(sb + BAR_P + 8, 4 * 16384);
    for (int q = 0; q < 4; q++) tma_load_2d(sb + OFF_WOR + q * 16384, &maps.wo, h * 32, j * 2048 + q * 256, sb + BAR_P + 8);
    for (int q = 0; q < 4; q++) tma_prefetch_2d(&maps.wo, h * 32, j * 2048 + 1024 + q * 256);
  }
  __syncwarp();
  cluster_wait();
  const uint32_t rsb = sb ^ RANK_BIT;

  uint32_t tref = 0;
#pragma unroll 1
  for (int n = 0; n <= NSEG; n++) {
    const bool more = __builtin_expect(s + 1 < NSEG, 1);
    uint32_t zr = loop_zero<0>(n);
    if (__builtin_expect(s >= 0, 1)) {
      if (__builtin_expect(s > 0, 1)) {
        const uint32_t dst = sb + OFF_MEM + WG * 8192 + t16 + ((lv >> 5) & 12);
        uint32_t tries = zr;
#pragma unroll 1
        do {
          if (tries) { const char* src = gptr(xhi, xm + WG * 8192 + slot_off(sv)); tref += T_SLIP; WAIT_UNTIL(tref, aV[0], 1, -1); gather_issue(sb + OFF_MEM + WG * 8192 + tv, src); }
          KEEPALIVE(aV[0], zr);
          cp_async_wait_group<0>();
        } while (gather_incomplete<1, 0>(dst) && ++tries < POLL_LIMIT);
        named_bar(1 + WG, 128);
      }
      const uint32_t a_mem = sb + OFF_MEM + WG * 8192 + l16;
      float c[2][4];
      c[0][0] = c[0][1] = c[0][2] = c[0][3] = c[1][0] = c[1][1] = c[1][2] = c[1][3] = 0.f;
      constexpr int NBUF = (48 - 8 - 4 * O_FIX) / 4;
      uint32_t b[NBUF][4];
#pragma unroll
      for (int p = 0; p < NBUF - 1; p++) ldsm_x4_t(b[p], a_mem + p * 512);
#pragma unroll
      for (int p = 0; p < 16; p++) {
        if (p + NBUF - 1 < 16) ldsm_x4_t(b[(p + NBUF - 1) % NBUF], a_mem + (p + NBUF - 1) * 512);
        if (p < 8) { mma16816(c[0], aV[2 * p], b[p % NBUF][0], b[p % NBUF][1]); mma16816(c[1], aV[2 * p + 1], b[p % NBUF][2], b[p % NBUF][3]); }
        else { mma16816(c[0], rot[2 * p - 16], b[p % NBUF][0], b[p % NBUF][1]); mma16816(c[1], rot[2 * p - 15], b[p % NBUF][2], b[p % NBUF][3]); }
      }
      SFENCE(15);
      const float4 own = make_float4(c[0][0] + c[1][0], c[0][1] + c[1][1], c[0][2] + c[1][2], c[0][3] + c[1][3]);
      NEWZ(1);
      const uint32_t pvm = WG == 0 ? xvm + slot_off(sv) : 0;
      if (WG == 1) sts128f(sb + OFF_VPX + wq * 512 + l16, own);
      named_bar(3, 256);
      if (WG == 0) {
        const float4 o = lds128f(sb + OFF_VPX + wq * 512 + l16);
        st_relaxed2(gptr(xhi, pvm), pack_bf16(own.x + o.x, own.y + o.y), pack_bf16(own.z + o.z, own.w + o.w));
      }
    }
    auto token_pv = [&](int seg, bool staged) {
      constexpr int NU = 2 - WG;
      uint4 pt0, pt1, v0[NU], v1[NU]; uint32_t pm0, pm1; uint2 vm[NU];
      const uint32_t ap = l16 + WG * 4096 + xo::PT, am = (lv >> 2) + WG * 4096 + xo::PM;
      const uint32_t at = ovt - WG * 512;
      if (staged) {
        const uint32_t b = sb + OFF_MEM;
        pt0 = lds128(b + ap); pt1 = lds128(b + ap + 2048); pm0 = lds32(b + am); pm1 = lds32(b + am + 2048);
#pragma unroll
        for (int u = 0; u < NU; u++) { v0[u] = lds128(b + at - u * 2048); v1[u] = lds128(b + at + 512 - u * 2048); vm[u] = lds64(b + ovm - u * 2048); }
      } else {
        const uint32_t b = lds32(sb + CT_HEAD) + slot_off(seg);
        pt0.x = EMPTY;
#pragma unroll
        for (int u = 0; u < NU; u++) {
          v0[u] = ld_relaxed4(gptr(xhi, b + at) - u * 2048); v1[u] = ld_relaxed4(gptr(xhi, b + at) + 512 - u * 2048);
          vm[u] = ld_relaxed2(gptr(xhi, b + ovm) - u * 2048);
        }
      }
      const bool odd = lv & 16;
      char* op = gptr(xhi, lds32(sb + CT_O) + (seg * SEG + WG * 16 + (lv >> 6)) * (HD * 2) + wq * 32 + (lv & 16) + ((lv >> 2) & 8));
      if (!staged || __builtin_expect(warp_incomplete(umax4(pt0.x, pt1.x, pm0, pm1)), 0)) {
        const uint32_t b = lds32(sb + CT_HEAD) + slot_off(seg);
        uint32_t tries = zr;
#pragma unroll 1
        do {
          pt0 = ld_relaxed4(gptr(xhi, b + ap)); pt1 = ld_relaxed4(gptr(xhi, b + ap) + 2048);
          pm0 = ld_relaxed1(gptr(xhi, b + am)); pm1 = ld_relaxed1(gptr(xhi, b + am) + 2048);
        } while (warp_incomplete(umax4(pt0.x, pt1.x, pm0, pm1)) && ++tries < POLL_LIMIT);
      }
      const uint32_t pa[4] = {pt0.x, pt1.x, pt0.y, pt1.y}, pb[4] = {pt0.z, pt1.z, pt0.w, pt1.w};
#pragma unroll
      for (int u = 0; u < NU; u++) {
        float o0[4] = {0.f, 0.f, 0.f, 0.f}, o1[4] = {0.f, 0.f, 0.f, 0.f};
        mma1688(o0, pm0, pm1, vm[u].x); mma1688(o1, pm0, pm1, vm[u].y);
        mma16816(o0, pa, v0[u].x, v0[u].y); mma16816(o1, pa, v1[u].x, v1[u].y);
        if (WG) { mma16816(o0, pb, v0[u].z, v0[u].w); mma16816(o1, pb, v1[u].z, v1[u].w); }
#pragma unroll
        for (int r = 0; r < 2; r++) {
          const uint32_t w0 = pack_bf16(o0[2 * r], o0[2 * r + 1]), w1 = pack_bf16(o1[2 * r], o1[2 * r + 1]);
          const uint32_t rv = __shfl_xor_sync(~0u, odd ? w0 : w1, 1);
          *(uint2*)(op + r * 8 * HD * 2 - u * 64) = odd ? make_uint2(rv, w1) : make_uint2(w0, rv);
        }
      }
    };
    if (!more) {
      named_bar(3, 256);
      if (upper_warps) {
#pragma unroll 1
        for (int seg = NSEG - 2; seg < NSEG; seg++) token_pv(seg, false);
      }
      break;
    }
    {
      if (__builtin_expect(s > 0, 1)) {
        const uint32_t o = WG ? ovt - 512 : tv + 512;
        const char* src = gptr(xhi, lds32(sb + CT_HEAD) + slot_off(sv - 1) + o);
#pragma unroll
        for (int i = 0; i < 3 - WG; i++) cp_async16(sb + OFF_MEM + o + i * 512, src + i * 512);
        cp_async_commit();
      }
      bool xw;
      {
        float acc[16];
        mbar_wait<0>(sb + BAR_X + 8 * WG, (s + 1) & 1);
        wg_fence();
#pragma unroll
        for (int ks = 0; ks < 16; ks++) wgmma_m64n32_rs(acc, rot[ks], xdesc<WG>(16 + ks), ks != 0);
        wg_commit();
#pragma unroll
        for (int ks = 0; ks < 16; ks++) wgmma_m64n32_rs(acc, aV[ks], xdesc<WG>(ks), 1);
        wg_commit();
        NEWZ(2);
        xw = warp_is(3) && s + 2 < NSEG;
        const uint32_t pvt = xvt + slot_off(sv + 1), awo = sb + wo_addr(tv);
        if (WG == 0 && warp_is(1) && s >= 0) expect_elect(sb + BAR_EX, 512);
        if (xw) {
          expect_elect(sb + BAR_X + 8 * WG, 32768);
          if (WG == 1 && s + 5 < NSEG) prefetch_l2(maps.xp + (s + 5) * 65536 + lds32(sb + CT_PF), 1024);
        }
        wg_wait<1>();
        if (xw) { named_bar(4 + WG, 128); issue_x(sb, &maps.xq, s + 2, WG, 1); }
        else if (s + 2 < NSEG) named_bar_arrive(4 + WG, 128);
        if (__builtin_expect(s == 0, 0)) {
          mbar_wait(sb + BAR_P + 16, 0);
#pragma unroll
          for (int ks = 16 - O_FIX; ks < 16; ks++) ldsm_x4_t(bO[ks], (awo ^ 32) + (ks & 7) * 1024);
        }
#pragma unroll
        for (int ks = 0; ks < 16 - O_FIX; ks++) ldsm_x4_t(bO[ks], (ks < 8 ? awo : awo ^ 32) + (ks & 7) * 1024);
        wg_wait<0>();
        acc_fence(acc);
        constexpr int K = WG * 2, G = 2 - K;
        sts128f(sb + OFF_RED + WG * 1024 + t16, make_float4(acc[G], acc[G + 1], acc[4 + G], acc[5 + G]));
        sts128f(sb + OFF_RED + WG * 1024 + 512 + t16, make_float4(acc[8 + G], acc[9 + G], acc[12 + G], acc[13 + G]));
        cp_async_wait_group<0>();
        named_bar(3, 256);
        const float4 o0 = lds128f(sb + OFF_RED + (WG ^ 1) * 1024 + t16), o1 = lds128f(sb + OFF_RED + (WG ^ 1) * 1024 + 512 + t16);
        st_relaxed4(gptr(xhi, pvt),
                    pack_bf16(acc[K] + o0.x, acc[K + 1] + o0.y), pack_bf16(acc[4 + K] + o0.z, acc[5 + K] + o0.w),
                    pack_bf16(acc[8 + K] + o1.x, acc[9 + K] + o1.y), pack_bf16(acc[12 + K] + o1.z, acc[13 + K] + o1.w));
      }
      if (__builtin_expect(s >= 0, 1)) {
        uint32_t tries = 0;
#pragma unroll
        for (int ks = 0; ks < 16 - O_FIX; ks++) tries |= bO[ks][0];
        tries = __shfl_sync(0xffffffffu, tries & zr, 0);
        tref += lds32(sb + CT_T1) + (WG * T_LAG - T_SLIP);
        float d[2][2][4];
        uint32_t mx;
#pragma unroll 1
        do {
          NEWZ(5);
          const char* po = gptr(xhi, xom + slot_off(sv));
          tref += T_SLIP;
          WAIT_UNTIL(tref, aV[0], 1, 1);
          uint4 o[8];
#pragma unroll
          for (int i = 0; i < 4; i++) o[i] = ld_relaxed4(po + i * 512);
#pragma unroll
          for (int i = 0; i < 4; i++) o[4 + i] = ld_relaxed4(po + 16384 + i * 512);
          __syncwarp();
#pragma unroll
          for (int i = 0; i < 2; i++)
#pragma unroll
            for (int q = 0; q < 2; q++) { d[i][q][0] = d[i][q][1] = d[i][q][2] = d[i][q][3] = 0.f; }
#pragma unroll
          for (int i = 0; i < 4; i++) {
            mma16816(d[0][0], aO[2 * i], o[i].x, o[i].y); mma16816(d[1][0], aO[8 + 2 * i], o[i].x, o[i].y);
            mma16816(d[0][1], aO[2 * i + 1], o[i].z, o[i].w); mma16816(d[1][1], aO[9 + 2 * i], o[i].z, o[i].w);
          }
          mx = umax4(o[0].w, o[1].w, o[2].w, o[3].w);
          SFENCE(33 + tries);
#pragma unroll
          for (int i = 0; i < 4; i++) {
            mma16816(d[0][0], bO[2 * i], o[4 + i].x, o[4 + i].y); mma16816(d[1][0], bO[8 + 2 * i], o[4 + i].x, o[4 + i].y);
            mma16816(d[0][1], bO[2 * i + 1], o[4 + i].z, o[4 + i].w); mma16816(d[1][1], bO[9 + 2 * i], o[4 + i].z, o[4 + i].w);
          }
          mx = max(mx, umax4(o[4].w, o[5].w, o[6].w, o[7].w));
        } while (warp_incomplete(mx) && ++tries < POLL_LIMIT);
        NEWZ(3);
        const uint32_t rd = sb + OFF_RED + (WG ^ 1) * 1024 + t16;
        sts128f(rd, make_float4(d[0][0][0] + d[0][1][0], d[0][0][1] + d[0][1][1], d[0][0][2] + d[0][1][2], d[0][0][3] + d[0][1][3]));
        sts128f(rd + 512, make_float4(d[1][0][0] + d[1][1][0], d[1][0][1] + d[1][1][1], d[1][0][2] + d[1][1][2], d[1][0][3] + d[1][1][3]));
        if (upper_warps) {
          named_bar_arrive(7, 256);
          if (xw) issue_x(sb, &maps.xq, s + 2, WG, 0);
          if (__builtin_expect(s > 0, 1)) token_pv(sv - 1, true);
        } else {
          uint32_t mp = lds32(sb + CT_MP) + (lv >> 2);
          named_bar(7, 256);
          float4 p[8];
#pragma unroll
          for (int i = 0; i < 8; i++) p[i] = lds128f(sb + OFF_RED + lv + wq * 512 + i * 1024);
          float4 r;
          r.x = ((p[0].x + p[1].x) + (p[2].x + p[3].x)) + ((p[4].x + p[5].x) + (p[6].x + p[7].x));
          r.y = ((p[0].y + p[1].y) + (p[2].y + p[3].y)) + ((p[4].y + p[5].y) + (p[6].y + p[7].y));
          r.z = ((p[0].z + p[1].z) + (p[2].z + p[3].z)) + ((p[4].z + p[5].z) + (p[6].z + p[7].z));
          r.w = ((p[0].w + p[1].w) + (p[2].w + p[3].w)) + ((p[4].w + p[5].w) + (p[6].w + p[7].w));
          const bool w0 = warp_is(0);
          if (w0) st_async4(rsb + OFF_RX + lv, __float_as_uint(r.x), __float_as_uint(r.y), __float_as_uint(r.z), __float_as_uint(r.w), rsb + BAR_EX);
          if (!w0) {
            char* pp = gptr(xhi, mp + slot_off(sv + 1));
            mbar_wait(sb + BAR_EX, s & 1);
            const float4 q = lds128f(sb + OFF_RX + l16);
            st_relaxed1(pp, pack_bf16(r.x + q.x, r.y + q.y)); st_relaxed1(pp + 128, pack_bf16(r.z + q.z, r.w + q.w));
            pp = gptr(xhi, mp + slot_off(sv + 3));
            st_relaxed1(pp, EMPTY); st_relaxed1(pp + 128, EMPTY);
          }
        }
        NEWZ(4);
        const char* src = gptr(xhi, xm + WG * 8192 + slot_off(sv + 1));
        const uint32_t awv = sb + wv_addr(tv) + OFF_WVR;
        tref += lds32(sb + CT_T2) - WG * T_LAG;
        named_bar(8, 256);
#pragma unroll
        for (int ks = 0; ks < V_PRE; ks++) ldsm_x4_t(rot[ks], awv + ks * 2048);
        WAIT_UNTIL(tref, aV[0], 1, 2);
        gather_issue(sb + OFF_MEM + WG * 8192 + tv, src);
#pragma unroll
        for (int ks = V_PRE; ks < 16; ks++) ldsm_x4_t(rot[ks], awv + ks * 2048);
        NEWZ(6);
        st_relaxed4(gptr(xhi, xvt + slot_off(sv + 2)), EMPTY, EMPTY, EMPTY, EMPTY);
        if (WG == 0) st_relaxed2(gptr(xhi, xvm + slot_off(sv + 2)), EMPTY, EMPTY);
      } else {
        load_v(tv);
        if (xw) issue_x(sb, &maps.xq, s + 2, WG, 0);
        mbar_wait(sb + BAR_P + 8, 0);
#pragma unroll
        for (int ks = 0; ks < 8; ks++) { ldsm_x4_t(aO[ks], sb + wo_addr(tv) + ks * 1024); ldsm_x4_t(aO[8 + ks], sb + (wo_addr(tv) ^ 32) + ks * 1024); }
        named_bar(0, 256);
        if (threadIdx.x == 0) {
          fence_async_smem();
          mbar_expect_tx(sb + BAR_P + 16, 4 * 16384);
          for (int q = 0; q < 4; q++) tma_load_2d(sb + OFF_WOR + q * 16384, &maps.wo, h * 32, j * 2048 + 1024 + q * 256, sb + BAR_P + 16);
        }
        __syncwarp();
        tref = gtime() / T_SLIP * T_SLIP - T_SLIP;
      }
    }
  }
}

#undef j
#undef s
#undef sv
#undef xm
#undef wq

__global__ void __launch_bounds__(256, 1) __cluster_dims__(2, 1, 1)
chain_kernel(const __grid_constant__ ChainMaps maps, const bf16* __restrict__ mem0, const uint64_t xbase) {
  using namespace chain;
  extern __shared__ uint8_t smem_raw[];
  uint32_t sb = smem_u32(smem_raw);
  PIN(sb);
  if (sb != SB_LO + (blockIdx.x & 1) * RANK_BIT || mapa(sb, (blockIdx.x & 1) ^ 1) != (sb ^ RANK_BIT)) __trap();
  const int tid = threadIdx.x;
  const int h = blockIdx.x >> 2, role = (blockIdx.x >> 1) & 1, j = blockIdx.x & 1;
  if (tid == 0) {
    for (int i = 0; i < 9; i++) mbar_init(sb + OFF_BAR + 8 * i, 1);
    asm volatile("fence.mbarrier_init.release.cluster;" ::: "memory");
    const uint32_t xl = (uint32_t)xbase;
    sts32(sb + CT_BASE, xl); sts32(sb + CT_HEAD, xl + h * xo::HEAD); sts32(sb + CT_OM, xl + xo::OM + (role ? j * 32768 : h * 2048));
    sts32(sb + CT_MP, xl + xo::MEM + (h * 2 + j) * 256); sts32(sb + CT_O, xl + xo::O + (h * 2 + j) * 128); sts32(sb + CT_PF, (h * 2 + j) * 1024);
    sts32(sb + CT_T1, role ? maps.t_phase : maps.t_step); sts32(sb + CT_T2, maps.t_step - maps.t_phase);
    if (role == 0) {
      const CUtensorMap* wm = j ? &maps.wk : &maps.wq;
      mbar_expect_tx(sb + BAR_P, 6 * 16384);
      for (int c = 0; c < 3; c++)
        for (int q = 0; q < 2; q++) tma_load_2d(sb + OFF_X + (q * 3 + c) * 16384, wm, h * DH + q * 64, q * 512 + c * 128, sb + BAR_P);
      mbar_expect_tx(sb + BAR_P + 8, 4 * 16384);
      for (int c = 0; c < 2; c++)
        for (int q = 0; q < 2; q++) tma_load_2d(sb + OFF_X + (6 + q * 2 + c) * 16384, wm, h * DH + (q ^ 1) * 64, q * 512 + c * 128, sb + BAR_P + 8);
      mbar_expect_tx(sb + BAR_P + 24, 4 * 16384);
      for (int q = 0; q < 2; q++)
        for (int o = 0; o < 2; o++) tma_load_2d(sb + OFF_WS + (q * 2 + o) * 16384, wm, h * DH + (q ^ o) * 64, q * 512 + 384, sb + BAR_P + 24);
      for (int q = 0; q < 2; q++) tma_prefetch_2d(wm, h * DH + (q ^ 1) * 64, q * 512 + 256);
    } else {
      mbar_expect_tx(sb + BAR_P, 8 * 16384);
      for (int q = 0; q < 4; q++) tma_load_2d(sb + OFF_WOR + q * 16384, &maps.wv, h * DH + j * 64, (q >> 1) * 512 + (q & 1) * 128, sb + BAR_P);
      for (int q = 0; q < 4; q++) tma_load_2d(sb + OFF_WVR + q * 16384, &maps.wv, h * DH + j * 64, (q >> 1) * 512 + 256 + (q & 1) * 128, sb + BAR_P);
    }
  }
  for (int r = 0; r < RING; r++) {
    char* p = (char*)xbase + r * xo::SLOT;
    const int wq = (tid >> 5) & 3;
    if (role == 1) st_relaxed4(p + h * xo::HEAD + xo::VT + (8 * j + 2 * wq + (tid >> 7)) * 512 + (tid & 31) * 16, EMPTY, EMPTY, EMPTY, EMPTY);
    else if (j == 0) st_relaxed4(p + (tid < 128 ? xo::OM + h * 2048 + tid * 16 : h * xo::HEAD + wq * 2048 + xo::VM + (tid & 31) * 16), EMPTY, EMPTY, EMPTY, EMPTY);
    else {
      st_relaxed4(p + h * xo::HEAD + (tid >> 6) * 2048 + 1024 + (tid & 63) * 16, EMPTY, EMPTY, EMPTY, EMPTY);
      if (tid < 32) st_relaxed4(p + xo::MEM + h * 512 + tid * 16, EMPTY, EMPTY, EMPTY, EMPTY);
    }
  }
  __syncthreads();
  if (tid == 0) {
    __threadfence();
    const uint32_t target = (atomicAdd(&g_epoch, 1u) & ~127u) + 128u;
    uint32_t v; int guard = 0;
    do { asm volatile("ld.acquire.gpu.global.u32 %0, [%1];" : "=r"(v) : "l"(&g_epoch) : "memory"); } while ((int)(v - target) < 0 && ++guard < (1 << 20));
  }
  __syncwarp();
  const uint32_t xhi = (uint32_t)(xbase >> 32);
  const int wg = __shfl_sync(0xffffffffu, tid >> 7, 0);
  if (role == 0) {
    if (wg == 0) role_a<0>(maps, mem0, sb, xhi); else role_a<1>(maps, mem0, sb, xhi);
  } else {
    if (wg == 0) role_v<0>(maps, mem0, sb, xhi); else role_v<1>(maps, mem0, sb, xhi);
  }
  asm volatile("griddepcontrol.launch_dependents;");
  __syncwarp();
  cluster_arrive();
  cluster_wait();
}

struct BMaps { CUtensorMap q, k, v, out, k8; };

#define B_PRAGMA2(x) _Pragma(#x)
#define B_PRAGMA(x) B_PRAGMA2(x)
#define B_UNROLL 4
#define B_SLEEP 200
namespace bp {
constexpr int U_PITCH = (2048 + 128) * 2 + 16;
constexpr int KR_WORDS = 1048;
constexpr int KR_PITCH = 8704;
constexpr int OFF_U = 0;
constexpr int OFF_KR = (8 * U_PITCH + 127) / 128 * 128;
constexpr int Q_OFF = 4352;
constexpr int OFF_BAR = OFF_KR + 8 * KR_PITCH;
constexpr int GROUP_BYTES = OFF_BAR + 128;
constexpr int SMEM = 2 * GROUP_BYTES + 128;
constexpr int NTASK = DM / 8;
static_assert(Q_OFF >= 4224 && Q_OFF + 4096 <= KR_PITCH, "staging does not fit");
}

__device__ __forceinline__ uint32_t bmul2(uint32_t a, uint32_t b) { uint32_t r; asm("mul.rn.bf16x2 %0, %1, %2;" : "=r"(r) : "r"(a), "r"(b)); return r; }
__device__ __forceinline__ uint32_t badd2(uint32_t a, uint32_t b) { uint32_t r; asm("add.rn.bf16x2 %0, %1, %2;" : "=r"(r) : "r"(a), "r"(b)); return r; }
__device__ __forceinline__ void stsm_x4_t(uint32_t addr, uint32_t r0, uint32_t r1, uint32_t r2, uint32_t r3) {
  asm volatile("stmatrix.sync.aligned.m8n8.x4.trans.shared.b16 [%0], {%1,%2,%3,%4};" ::"r"(addr), "r"(r0), "r"(r1), "r"(r2), "r"(r3) : "memory");
}

__device__ __forceinline__ void mbar_wait_sleep(uint32_t bar, uint32_t parity) {
  int guard = 0;
  while (!mbar_try(bar, parity)) { __nanosleep(B_SLEEP); if (++guard > (1 << 22)) __trap(); }
}

__device__ __forceinline__ void bpart_body(const BMaps& maps, const bf16* __restrict__ shift_k, const bf16* __restrict__ ssm_k,
                                           const bf16* __restrict__ ssm_D, int first, int stride, int end) {
  using namespace bp;
  extern __shared__ uint8_t smem_all[];
  const int grp = __shfl_sync(0xffffffffu, threadIdx.x >> 8, 0);
  const int tid = threadIdx.x & 255, lane = tid & 31, g = lane >> 2, t = lane & 3;
  const int w = __shfl_sync(0xffffffffu, tid >> 5, 0);
  const uint32_t sb = ((smem_u32(smem_all) + 127) & ~127u) + grp * GROUP_BYTES;
  const uint32_t bar_kv = sb + OFF_BAR + 8 * w, bar_q = sb + OFF_BAR + 64 + 8 * w;
  if (lane == 0) { mbar_init(bar_kv, 1); mbar_init(bar_q, 1); asm volatile("fence.mbarrier_init.release.cluster;" ::: "memory"); }
  named_bar(1 + grp, 256);
  if (grp == 1) named_bar_arrive(3, 512);
  const int lm = lane >> 3, lr = lane & 7;
  uint32_t ph = 0;
  for (int task = first + grp; task < end; task += stride, ph ^= 1) {
    const int d0 = task * 8;
    if (lane == 0) {
      const uint32_t kr = sb + OFF_KR + w * KR_PITCH;
      mbar_expect_tx(bar_kv, 2 * 4096 + 128);
      tma_load_2d(kr, &maps.k, d0, w * 256 - 8, bar_kv);
      tma_load_2d(kr + 4096, &maps.k8, d0, w * 256 + 248, bar_kv);
      bulk_wait_read<0>();
      tma_load_2d(kr + Q_OFF, &maps.v, d0, w * 256, bar_kv);
    }
    uint4 x[8];
    {
      const uint4* kf = (const uint4*)(ssm_k + (size_t)(d0 + w) * S_LEN);
#pragma unroll
      for (int it = 0; it < 8; it++) x[it] = __ldg(kf + it * 32 + lane);
    }
    uint32_t sk[4];
    {
      const uint4 a = __ldg((const uint4*)(shift_k + (d0 + 2 * t) * 4));
      sk[0] = __byte_perm(a.x, a.z, 0x5410); sk[1] = __byte_perm(a.x, a.z, 0x7632);
      sk[2] = __byte_perm(a.y, a.w, 0x5410); sk[3] = __byte_perm(a.y, a.w, 0x7632);
    }
    const uint32_t dpair = __ldg((const uint32_t*)(ssm_D + d0) + t);
    if (tid < 128) sts128(sb + OFF_U + (tid >> 4) * U_PITCH + (tid & 15) * 16, make_uint4(0, 0, 0, 0));
    mbar_wait_sleep(bar_kv, ph);
    {
      const uint32_t ka = sb + OFF_KR + w * KR_PITCH + (g + 8) * 16 + t * 4, va = sb + OFF_KR + w * KR_PITCH + Q_OFF + g * 16 + t * 4;
B_PRAGMA(unroll B_UNROLL)
      for (int i = 0; i < 8; i++) {
        uint32_t r[4];
#pragma unroll
        for (int b = 0; b < 4; b++) {
          const uint32_t o = (i * 32 + b * 8) * 16;
          uint32_t acc = bmul2(lds32(ka + o - 48), sk[3]);
          acc = badd2(acc, bmul2(lds32(ka + o - 32), sk[2]));
          acc = badd2(acc, bmul2(lds32(ka + o - 16), sk[1]));
          acc = badd2(acc, bmul2(lds32(ka + o), sk[0]));
          r[b] = bmul2(acc, lds32(va + o));
        }
        const int ch = 16 + w * 32 + i * 4 + lm;
        stsm_x4_t(sb + OFF_U + lr * U_PITCH + ((ch ^ ((ch >> 3) & 1)) << 4), r[0], r[1], r[2], r[3]);
      }
    }
    __syncwarp();
    {
      const uint32_t c0 = sb + OFF_KR + w * KR_PITCH, c1 = c0 + (KR_WORDS + 16) * 4;
      uint32_t carry = 0;
#pragma unroll
      for (int it = 0; it < 8; it++) {
        const int blk = it * 32 + lane;
        uint32_t prev = __shfl_up_sync(0xffffffffu, x[it].w, 1);
        if (lane == 0) prev = carry;
        carry = __shfl_sync(0xffffffffu, x[it].w, 31);
        sts128(c0 + (1028 - 4 * blk) * 4, make_uint4(__byte_perm(x[it].w, 0, 0x1032), __byte_perm(x[it].z, 0, 0x1032),
                                                     __byte_perm(x[it].y, 0, 0x1032), __byte_perm(x[it].x, 0, 0x1032)));
        sts128(c1 + (1028 - 4 * blk) * 4, make_uint4(__byte_perm(x[it].w, x[it].z, 0x7610), __byte_perm(x[it].z, x[it].y, 0x7610),
                                                     __byte_perm(x[it].y, x[it].x, 0x7610), __byte_perm(x[it].x, prev, 0x7610)));
      }
      if (lane < 4) { sts128(c0 + (1032 + 4 * lane) * 4, make_uint4(0, 0, 0, 0)); sts128(c1 + (1032 + 4 * lane) * 4, make_uint4(0, 0, 0, 0)); }
      __syncwarp();
    }
    named_bar(1 + grp, 256);
    named_bar(3 + grp, 512);
    float acc[16][4];
#pragma unroll
    for (int jn = 0; jn < 16; jn++) { acc[jn][0] = acc[jn][1] = acc[jn][2] = acc[jn][3] = 0.f; }
    {
      const uint32_t ub = sb + OFF_U + w * U_PITCH;
      const uint32_t kw = sb + OFF_KR + w * KR_PITCH + (((g & 1) ? 0 : KR_WORDS + 16) + ((((g & 1) ? 2063 : 2062) - (g - 2 * t)) >> 1)) * 4;
#pragma unroll 1
      for (int d0s = 0; d0s < 8; d0s++) {
        const int a0 = 8 - d0s + lr;
        const uint32_t uf = ub + (((2 * a0 + (lm & 1)) ^ ((a0 >> 2) & 1)) << 4);
        const uint32_t kd = kw - 32 * d0s;
        uint32_t A[3][4];
        A[0][0] = lds32v(kd); A[0][1] = lds32v(kd - 16); A[0][2] = lds32v(kd + 16); A[0][3] = lds32v(kd);
        uint32_t F[16][2];
#pragma unroll
        for (int m = 0; m < 16; m++) ldsm_x2(F[m][0], F[m][1], uf + m * 256);
#pragma unroll
        for (int i = 0; i < 16; i++) {
          if (i + 1 < 16) {
            A[(i + 1) % 3][0] = lds32v(kd - 256 * (i + 1)); A[(i + 1) % 3][1] = lds32v(kd - 256 * (i + 1) - 16);
            A[(i + 1) % 3][2] = lds32v(kd - 256 * (i + 1) + 16); A[(i + 1) % 3][3] = lds32v(kd - 256 * (i + 1));
          }
#pragma unroll
          for (int jn = 15; jn >= i; jn--) mma16816(acc[jn], A[i % 3], F[jn - i][0], F[jn - i][1]);
        }
      }
    }
    named_bar_arrive(3 + (grp ^ 1), 512);
    const uint32_t qs = sb + OFF_KR + w * KR_PITCH + Q_OFF;
    __syncwarp();
    fence_async_smem();
    __syncwarp();
    if (lane == 0) { mbar_expect_tx(bar_q, 4096); tma_load_2d(qs, &maps.q, d0, w * 256, bar_q); }
    {
      const uint32_t ya = sb + OFF_KR + w * (KR_PITCH + 16) + (((lm >> 1) * 8 + lr) * 32) + (lm & 1) * 16;
#pragma unroll
      for (int jn = 0; jn < 16; jn += 2)
        stsm_x4_t(ya + jn * 256, pack_bf16(acc[jn][0], acc[jn][1]), pack_bf16(acc[jn][2], acc[jn][3]),
                  pack_bf16(acc[jn + 1][0], acc[jn + 1][1]), pack_bf16(acc[jn + 1][2], acc[jn + 1][3]));
    }
    named_bar(1 + grp, 256);
    mbar_wait_sleep(bar_q, ph);
    {
      const uint32_t ya = sb + OFF_KR + lr * (KR_PITCH + 16) + (w * 256 + lm * 8) * 2;
      const uint32_t qa = qs + g * 16 + t * 4;
B_PRAGMA(unroll B_UNROLL)
      for (int i = 0; i < 8; i++) {
        uint32_t y[4], u[4];
        ldsm_x4_t(y, ya + i * 64);
        const int ch = 16 + w * 32 + i * 4 + lm;
        ldsm_x4_t(u, sb + OFF_U + lr * U_PITCH + ((ch ^ ((ch >> 3) & 1)) << 4));
#pragma unroll
        for (int b = 0; b < 4; b++) {
          const uint32_t a = qa + (i * 32 + b * 8) * 16;
          sts32(a, bmul2(lds32(a), badd2(y[b], bmul2(u[b], dpair))));
        }
      }
      fence_async_smem();
      __syncwarp();
      if (lane == 0) { tma_store_2d(&maps.out, qs, DM + d0, w * 256); bulk_commit(); }
    }
    named_bar(1 + grp, 256);
  }
  if (lane == 0) bulk_wait<0>();
}

__global__ void __launch_bounds__(512, 1) __cluster_dims__(2, 1, 1)
bpart_kernel(const __grid_constant__ BMaps maps, const bf16* __restrict__ shift_k, const bf16* __restrict__ ssm_k, const bf16* __restrict__ ssm_D, int end) {
  bpart_body(maps, shift_k, ssm_k, ssm_D, blockIdx.x * 2, gridDim.x * 2, end);
}

struct GemmMaps {
  CUtensorMap o;
  CUtensorMap w;
  CUtensorMap c;
};
namespace k3 {
constexpr int STAGES = 5;
constexpr int W_BYTES = 2 * 8192, O_BYTES = K3_N * 128, STAGE_BYTES = W_BYTES + O_BYTES;
constexpr int TT = (S_LEN + K3_N - 1) / K3_N, NGEMM = TT * (DM / 128), NB = 128 - NGEMM, KSTEPS = HD / 64;
constexpr int SMEM_G = STAGES * STAGE_BYTES + 1024 + 256;
constexpr int SMEM = SMEM_G > bp::SMEM ? SMEM_G : bp::SMEM;
static_assert(STAGE_BYTES % 1024 == 0, "swizzle atoms");
}

__global__ void __launch_bounds__(512, 1)
tail_kernel(const __grid_constant__ GemmMaps maps, const __grid_constant__ BMaps bmaps, const bf16* __restrict__ shift_k,
            const bf16* __restrict__ ssm_k, const bf16* __restrict__ ssm_D) {
  using namespace k3;
  if (blockIdx.x < NB) {
    bpart_body(bmaps, shift_k, ssm_k, ssm_D, bp::NTASK - 2 * NB + 2 * blockIdx.x, bp::NTASK, bp::NTASK);
    return;
  }
  extern __shared__ uint8_t smem_raw[];
  const uint32_t sbase = (smem_u32(smem_raw) + 1023) & ~1023u;
  const uint32_t bars = sbase + STAGES * STAGE_BYTES;
  const int tid = threadIdx.x, warp = tid >> 5;
  const int tt = (blockIdx.x - NB) % TT, ct = (blockIdx.x - NB) / TT;

  if (tid == 0) {
    for (int s = 0; s < STAGES; s++) { mbar_init(bars + 8 * s, 1); mbar_init(bars + 8 * (STAGES + s), 2); }
    asm volatile("fence.mbarrier_init.release.cluster;" ::: "memory");
  }
  __syncthreads();

  if (warp >= 8) {
    if (tid == 256) {
      tma_prefetch_desc(&maps.o);
      for (int k = 0; k < STAGES; k++) {
        const uint32_t full = bars + 8 * k, sa = sbase + k * STAGE_BYTES;
        mbar_expect_tx(full, STAGE_BYTES);
#pragma unroll
        for (int j = 0; j < 2; j++) tma_load_2d(sa + j * 8192, &maps.w, ct * 128 + j * 64, k * 64, full);
      }
      asm volatile("griddepcontrol.wait;" ::: "memory");
      int stage = 0; uint32_t ph = 1;
      for (int k = 0; k < KSTEPS; k++) {
        mbar_wait(bars + 8 * (STAGES + stage), ph);
        const uint32_t full = bars + 8 * stage, sa = sbase + stage * STAGE_BYTES;
        const bool pre = k < STAGES;
        if (!pre) mbar_expect_tx(full, STAGE_BYTES);
        tma_load_2d(sa + W_BYTES, &maps.o, k * 64, tt * K3_N, full);
        if (!pre) {
#pragma unroll
          for (int j = 0; j < 2; j++) tma_load_2d(sa + j * 8192, &maps.w, ct * 128 + j * 64, k * 64, full);
        }
        if (++stage == STAGES) { stage = 0; ph ^= 1; }
      }
    }
  } else {
    const int wg = warp >> 2, lane = tid & 31, wq = warp & 3;
    int stage = 0; uint32_t ph = 0;
    float acc[K3_N / 2];
    int prev = -1;
    for (int k = 0; k < KSTEPS; k++) {
      mbar_wait(bars + 8 * stage, ph);
      const uint32_t sa = sbase + stage * STAGE_BYTES;
      wg_fence();
#pragma unroll
      for (int kk = 0; kk < 4; kk++) {
        const uint64_t da = make_desc(sa + wg * 8192 + kk * 2048, 16, 1024, 1);
        const uint64_t db = make_desc(sa + W_BYTES + kk * 32, 16, 1024, 1);
        wgmma_k3_ss_ta(acc, da, db, (k | kk) != 0);
      }
      wg_commit();
      if (prev >= 0) { wg_wait<1>(); if ((tid & 127) == 0) mbar_arrive(bars + 8 * (STAGES + prev)); }
      prev = stage;
      if (++stage == STAGES) { stage = 0; ph ^= 1; }
    }
    wg_wait<0>();
#pragma unroll
    for (int i = 0; i < K3_N / 2; i++) asm volatile("" : "+f"(acc[i]) :: "memory");
    named_bar(1, 256);
    const uint32_t ebuf = sbase + wg * STAGE_BYTES;
    const uint32_t ea = ebuf + ((lane >> 4) * 8 + (lane & 7)) * 128 + (((2 * wq + ((lane >> 3) & 1)) ^ (lane & 7)) << 4);
#pragma unroll
    for (int i = 0; i < K3_N / 8; i += 2) {
      const int i1 = i + 1 < K3_N / 8 ? i + 1 : i;
      stsm_x4_t(ea + i * 1024, pack_bf16(acc[4 * i], acc[4 * i + 1]), pack_bf16(acc[4 * i + 2], acc[4 * i + 3]),
                pack_bf16(acc[4 * i1], acc[4 * i1 + 1]), pack_bf16(acc[4 * i1 + 2], acc[4 * i1 + 3]));
    }
    fence_async_smem();
    named_bar(2 + wg, 128);
    if ((tid & 127) == 0) {
      tma_store_2d(&maps.c, ebuf, ct * 128 + wg * 64, tt * K3_N);
      bulk_commit();
      bulk_wait<0>();
    }
  }
}

typedef CUresult (*EncodeFn)(CUtensorMap*, CUtensorMapDataType, cuuint32_t, void*, const cuuint64_t*, const cuuint64_t*,
                             const cuuint32_t*, const cuuint32_t*, CUtensorMapInterleave, CUtensorMapSwizzle,
                             CUtensorMapL2promotion, CUtensorMapFloatOOBfill);

void make_map(EncodeFn enc, CUtensorMap* m, const void* ptr, uint64_t cols, uint64_t rows, uint64_t pitch_elems,
              uint32_t box_cols, uint32_t box_rows, CUtensorMapSwizzle swz,
              CUtensorMapL2promotion promo = CU_TENSOR_MAP_L2_PROMOTION_L2_128B) {
  cuuint64_t dims[2] = {cols, rows};
  cuuint64_t strides[1] = {pitch_elems * 2};
  cuuint32_t box[2] = {box_cols, box_rows};
  cuuint32_t es[2] = {1, 1};
  enc(m, CU_TENSOR_MAP_DATA_TYPE_BFLOAT16, 2, const_cast<void*>(ptr), dims, strides, box, es, CU_TENSOR_MAP_INTERLEAVE_NONE, swz,
      promo, CU_TENSOR_MAP_FLOAT_OOB_FILL_NONE);
}

void make_map_nd(EncodeFn enc, CUtensorMap* m, const void* ptr, int rank, const uint64_t* dims, const uint64_t* strides_elems,
                 const uint32_t* box, CUtensorMapSwizzle swz) {
  cuuint64_t d[5], st[4]; cuuint32_t b[5], es[5];
  for (int i = 0; i < rank; i++) { d[i] = dims[i]; b[i] = box[i]; es[i] = 1; if (i) st[i - 1] = strides_elems[i] * 2; }
  enc(m, CU_TENSOR_MAP_DATA_TYPE_BFLOAT16, rank, const_cast<void*>(ptr), d, st, b, es, CU_TENSOR_MAP_INTERLEAVE_NONE, swz,
      CU_TENSOR_MAP_L2_PROMOTION_L2_128B, CU_TENSOR_MAP_FLOAT_OOB_FILL_NONE);
}

}

extern "C" void kernel_launch(void* const* d_in, const int* in_sizes, int n_in, void* d_out, int out_size) {
  (void)in_sizes; (void)n_in; (void)out_size;
  const bf16* x = (const bf16*)d_in[0];
  const bf16* mem0 = (const bf16*)d_in[1];
  const bf16* Wq = (const bf16*)d_in[2];
  const bf16* Wk = (const bf16*)d_in[3];
  const bf16* Wv = (const bf16*)d_in[4];
  const bf16* Wo = (const bf16*)d_in[5];
  const bf16* Bq = (const bf16*)d_in[7];
  const bf16* Bk = (const bf16*)d_in[8];
  const bf16* Bv = (const bf16*)d_in[9];
  const bf16* shift_k = (const bf16*)d_in[10];
  const bf16* ssm_k = (const bf16*)d_in[11];
  const bf16* ssm_D = (const bf16*)d_in[12];
  bf16* out = (bf16*)d_out;

  static EncodeFn enc = nullptr;
  static uint64_t xbase;
  static int nsm = 132;
  static cudaStream_t s1;
  static cudaEvent_t ev_fork, ev_join;
  if (!enc) {
    cudaDriverEntryPointQueryResult qr;
    void* fn = nullptr;
    cudaGetDriverEntryPoint("cuTensorMapEncodeTiled", &fn, cudaEnableDefault, &qr);
    enc = (EncodeFn)fn;
    void* ps = nullptr;
    cudaGetSymbolAddress(&ps, g_scratch);
    xbase = (uint64_t)ps;
    if ((xbase >> 32) != ((xbase + xo::BYTES - 1) >> 32)) xbase += xo::BYTES;
    cudaFuncSetAttribute(tail_kernel, cudaFuncAttributeMaxDynamicSharedMemorySize, k3::SMEM);
    cudaFuncSetAttribute(chain_kernel, cudaFuncAttributeMaxDynamicSharedMemorySize, chain::SMEM);
    cudaFuncSetAttribute(bpart_kernel, cudaFuncAttributeMaxDynamicSharedMemorySize, bp::SMEM);
    cudaStreamCreateWithFlags(&s1, cudaStreamNonBlocking);
    cudaEventCreateWithFlags(&ev_fork, cudaEventDisableTiming);
    cudaEventCreateWithFlags(&ev_join, cudaEventDisableTiming);
    int dev = 0; cudaGetDevice(&dev);
    cudaDeviceGetAttribute(&nsm, cudaDevAttrMultiProcessorCount, dev);
  }
  const CUtensorMapSwizzle SW128 = CU_TENSOR_MAP_SWIZZLE_128B, SW64 = CU_TENSOR_MAP_SWIZZLE_64B;
  GemmMaps m3; ChainMaps mc;
  make_map(enc, &m3.o, (void*)(xbase + xo::O), HD, S_LEN, HD, 64, K3_N, SW128);
  make_map(enc, &m3.w, Wo, DM, HD, DM, 64, 64, SW128);
  make_map(enc, &m3.c, out, DM, S_LEN, OUT_LD, 64, K3_N, SW128);
  const CUtensorMapL2promotion P256 = CU_TENSOR_MAP_L2_PROMOTION_L2_256B;
  make_map(enc, &mc.wq, Wq, HD, DM, HD, 64, 128, SW128, P256);
  make_map(enc, &mc.wk, Wk, HD, DM, HD, 64, 128, SW128, P256);
  make_map(enc, &mc.wv, Wv, HD, DM, HD, 64, 128, SW128, P256);
  make_map(enc, &mc.wo, Wo, DM, HD, DM, 32, 256, SW64, P256);
  {
    const uint64_t dx[3] = {64, S_LEN, DM / 64}, sx[3] = {1, DM, 64};
    const uint32_t bx[3] = {64, SEG, 8};
    make_map_nd(enc, &mc.x, x, 3, dx, sx, bx, SW128);
    const uint32_t bq[3] = {64, SEG, 4};
    make_map_nd(enc, &mc.xq, x, 3, dx, sx, bq, SW128);
    mc.xp = (const char*)x;
  }

  const int skip = 0;
  mc.t_step = T_STEP; mc.t_phase = T_PHASE;
  BMaps mb;
  const CUtensorMapSwizzle SWN = CU_TENSOR_MAP_SWIZZLE_NONE;
  make_map(enc, &mb.q, Bq, DM, S_LEN, DM, 8, 256, SWN);
  make_map(enc, &mb.k, Bk, DM, S_LEN, DM, 8, 256, SWN);
  make_map(enc, &mb.v, Bv, DM, S_LEN, DM, 8, 256, SWN);
  make_map(enc, &mb.out, out, OUT_LD, S_LEN, OUT_LD, 8, 256, SWN);
  make_map(enc, &mb.k8, Bk, DM, S_LEN, DM, 8, 8, SWN);
  cudaStream_t s0 = cudaStreamPerThread;
  const int nb = nsm >= 132 ? 4 : 2, ntask1 = bp::NTASK - 2 * k3::NB;
  const bool fork = nsm >= 130 && !(skip & 16);
  if (fork) {
    cudaEventRecord(ev_fork, s0);
    cudaStreamWaitEvent(s1, ev_fork, 0);
    if (!(skip & 1)) bpart_kernel<<<nb, 512, bp::SMEM, s1>>>(mb, shift_k, ssm_k, ssm_D, ntask1);
    cudaEventRecord(ev_join, s1);
  } else if (!(skip & 1)) {
    bpart_kernel<<<ntask1 / 2, 512, bp::SMEM, s0>>>(mb, shift_k, ssm_k, ssm_D, ntask1);
  }
  if (!(skip & 4)) chain_kernel<<<128, 256, chain::SMEM, s0>>>(mc, mem0, xbase);
  if (!(skip & 8)) {
    cudaLaunchAttribute pdl[1];
    pdl[0].id = cudaLaunchAttributeProgrammaticStreamSerialization;
    pdl[0].val.programmaticStreamSerializationAllowed = 1;
    cudaLaunchConfig_t cfg = {};
    cfg.gridDim = dim3(128); cfg.blockDim = dim3(512); cfg.dynamicSmemBytes = k3::SMEM; cfg.stream = s0;
    cfg.attrs = pdl; cfg.numAttrs = 1;
    cudaLaunchKernelEx(&cfg, tail_kernel, m3, mb, shift_k, ssm_k, ssm_D);
  }
  if (fork) cudaStreamWaitEvent(s0, ev_join, 0);
}
```

```cpp
#include <cuda_runtime.h>
#include <cuda_bf16.h>
#include <cuda.h>
#include <stdint.h>

namespace {

constexpr int S_LEN = 2048;
constexpr int DM = 1024;
constexpr int NH = 32;
constexpr int DH = 128;
constexpr int HD = NH * DH;
constexpr int SEG = 32;
constexpr int NSEG = S_LEN / SEG;
constexpr int OUT_LD = 2048;

typedef __nv_bfloat16 bf16;
#define K3_N 160

__device__ __forceinline__ uint32_t smem_u32(const void* p) { return (uint32_t)__cvta_generic_to_shared(p); }

__device__ __forceinline__ void mbar_init(uint32_t bar, uint32_t count) {
  asm volatile("mbarrier.init.shared::cta.b64 [%0], %1;" ::"r"(bar), "r"(count) : "memory");
}
__device__ __forceinline__ void mbar_expect_tx(uint32_t bar, uint32_t bytes) {
  asm volatile("mbarrier.arrive.expect_tx.shared::cta.b64 _, [%0], %1;" ::"r"(bar), "r"(bytes) : "memory");
}
__device__ __forceinline__ void mbar_arrive(uint32_t bar) {
  asm volatile("mbarrier.arrive.shared::cta.b64 _, [%0];" ::"r"(bar) : "memory");
}
__device__ __forceinline__ bool mbar_try(uint32_t bar, uint32_t parity) {
  uint32_t ok;
  asm volatile("{.reg .pred p; mbarrier.try_wait.parity.shared::cta.b64 p, [%1], %2; selp.u32 %0, 1, 0, p;}"
               : "=r"(ok) : "r"(bar), "r"(parity) : "memory");
  return ok;
}
__device__ __forceinline__ bool mbar_test(uint32_t bar, uint32_t parity) {
  uint32_t ok;
  asm volatile("{.reg .pred p; mbarrier.test_wait.parity.shared::cta.b64 p, [%1], %2; selp.u32 %0, 1, 0, p;}"
               : "=r"(ok) : "r"(bar), "r"(parity) : "memory");
  return ok;
}
template <int HINT = 1>
__device__ __forceinline__ void mbar_wait(uint32_t bar, uint32_t parity) {
  int guard = 0;
  while (__builtin_expect(!mbar_try(bar, parity), HINT)) { if (++guard > (1 << 22)) __trap(); }
}
__device__ __forceinline__ void tma_load_2d(uint32_t dst, const CUtensorMap* map, int c0, int c1, uint32_t bar) {
  asm volatile("cp.async.bulk.tensor.2d.shared::cluster.global.mbarrier::complete_tx::bytes [%0], [%1, {%3, %4}], [%2];"
               ::"r"(dst), "l"(map), "r"(bar), "r"(c0), "r"(c1) : "memory");
}
__device__ __forceinline__ void tma_load_3d(uint32_t dst, const CUtensorMap* map, int c0, int c1, int c2, uint32_t bar) {
  asm volatile("cp.async.bulk.tensor.3d.shared::cluster.global.mbarrier::complete_tx::bytes [%0], [%1, {%3, %4, %5}], [%2];"
               ::"r"(dst), "l"(map), "r"(bar), "r"(c0), "r"(c1), "r"(c2) : "memory");
}
__device__ __forceinline__ void tma_load_4d(uint32_t dst, const CUtensorMap* map, int c0, int c1, int c2, int c3, uint32_t bar) {
  asm volatile("cp.async.bulk.tensor.4d.shared::cluster.global.mbarrier::complete_tx::bytes [%0], [%1, {%3, %4, %5, %6}], [%2];"
               ::"r"(dst), "l"(map), "r"(bar), "r"(c0), "r"(c1), "r"(c2), "r"(c3) : "memory");
}
__device__ __forceinline__ void tma_store_2d(const CUtensorMap* map, uint32_t src, int c0, int c1) {
  asm volatile("cp.async.bulk.tensor.2d.global.shared::cta.bulk_group [%0, {%2, %3}], [%1];"
               ::"l"(map), "r"(src), "r"(c0), "r"(c1) : "memory");
}
__device__ __forceinline__ void tma_prefetch_2d(const CUtensorMap* map, int c0, int c1) {
  asm volatile("cp.async.bulk.prefetch.tensor.2d.L2.global [%0, {%1, %2}];" ::"l"(map), "r"(c0), "r"(c1) : "memory");
}
__device__ __forceinline__ void tma_prefetch_desc(const CUtensorMap* map) {
  asm volatile("prefetch.tensormap [%0];" ::"l"(map) : "memory");
}
__device__ __forceinline__ void fence_async_smem() { asm volatile("fence.proxy.async.shared::cta;" ::: "memory"); }
__device__ __forceinline__ void bulk_commit() { asm volatile("cp.async.bulk.commit_group;" ::: "memory"); }
template <int N> __device__ __forceinline__ void bulk_wait_read() { asm volatile("cp.async.bulk.wait_group.read %0;" ::"n"(N) : "memory"); }
template <int N> __device__ __forceinline__ void bulk_wait() { asm volatile("cp.async.bulk.wait_group %0;" ::"n"(N) : "memory"); }
__device__ __forceinline__ void named_bar(int id, int n) { asm volatile("bar.sync %0, %1;" ::"r"(id), "r"(n) : "memory"); }

__device__ __forceinline__ void named_bar_arrive(int id, int n) { asm volatile("bar.arrive %0, %1;" ::"r"(id), "r"(n) : "memory"); }
__device__ __forceinline__ float ex2(float x) { float y; asm("ex2.approx.ftz.f32 %0, %1;" : "=f"(y) : "f"(x)); return y; }
__device__ __forceinline__ float rcp(float x) { float y; asm("rcp.approx.ftz.f32 %0, %1;" : "=f"(y) : "f"(x)); return y; }

__device__ __forceinline__ void sts32(uint32_t a, uint32_t x) { asm volatile("st.shared.b32 [%0], %1;" ::"r"(a), "r"(x) : "memory"); }
__device__ __forceinline__ uint32_t lds32(uint32_t a) { uint32_t x; asm volatile("ld.shared.b32 %0, [%1];" : "=r"(x) : "r"(a) : "memory"); return x; }
__device__ __forceinline__ uint32_t lds32v(uint32_t a) { uint32_t x; asm volatile("ld.volatile.shared.b32 %0, [%1];" : "=r"(x) : "r"(a) : "memory"); return x; }
__device__ __forceinline__ void sts128(uint32_t a, const uint4& v) { asm volatile("st.shared.v4.b32 [%0], {%1,%2,%3,%4};" ::"r"(a), "r"(v.x), "r"(v.y), "r"(v.z), "r"(v.w) : "memory"); }
__device__ __forceinline__ void sts128f(uint32_t a, const float4& v) { asm volatile("st.shared.v4.f32 [%0], {%1,%2,%3,%4};" ::"r"(a), "f"(v.x), "f"(v.y), "f"(v.z), "f"(v.w) : "memory"); }
__device__ __forceinline__ uint4 lds128(uint32_t a) { uint4 v; asm volatile("ld.shared.v4.b32 {%0,%1,%2,%3}, [%4];" : "=r"(v.x), "=r"(v.y), "=r"(v.z), "=r"(v.w) : "r"(a) : "memory"); return v; }
__device__ __forceinline__ float4 lds128f(uint32_t a) { float4 v; asm volatile("ld.shared.v4.f32 {%0,%1,%2,%3}, [%4];" : "=f"(v.x), "=f"(v.y), "=f"(v.z), "=f"(v.w) : "r"(a) : "memory"); return v; }

__device__ __forceinline__ void cp_async16(uint32_t dst, const void* src) { asm volatile("cp.async.cg.shared.global [%0], [%1], 16;" ::"r"(dst), "l"(src) : "memory"); }
__device__ __forceinline__ void cp_async_commit() { asm volatile("cp.async.commit_group;" ::: "memory"); }
template <int N> __device__ __forceinline__ void cp_async_wait_group() { asm volatile("cp.async.wait_group %0;" ::"n"(N) : "memory"); }

__device__ __forceinline__ void wg_fence() { asm volatile("wgmma.fence.sync.aligned;" ::: "memory"); }
__device__ __forceinline__ void wg_commit() { asm volatile("wgmma.commit_group.sync.aligned;" ::: "memory"); }
template <int N> __device__ __forceinline__ void wg_wait() { asm volatile("wgmma.wait_group.sync.aligned %0;" ::"n"(N) : "memory"); }
__device__ __forceinline__ uint64_t make_desc(uint32_t addr, uint32_t lbo, uint32_t sbo, uint32_t swz) {
  return (uint64_t)((addr & 0x3FFFF) >> 4) | ((uint64_t)(lbo >> 4) << 16) | ((uint64_t)(sbo >> 4) << 32) | ((uint64_t)swz << 62);
}

__device__ __forceinline__ void ldsm_x4(uint32_t (&r)[4], uint32_t addr) {
  asm volatile("ldmatrix.sync.aligned.m8n8.x4.shared.b16 {%0,%1,%2,%3}, [%4];"
               : "=r"(r[0]), "=r"(r[1]), "=r"(r[2]), "=r"(r[3]) : "r"(addr) : "memory");
}
__device__ __forceinline__ void ldsm_x4_t(uint32_t (&r)[4], uint32_t addr) {
  asm volatile("ldmatrix.sync.aligned.m8n8.x4.trans.shared.b16 {%0,%1,%2,%3}, [%4];"
               : "=r"(r[0]), "=r"(r[1]), "=r"(r[2]), "=r"(r[3]) : "r"(addr) : "memory");
}
__device__ __forceinline__ void ldsm_x2(uint32_t& r0, uint32_t& r1, uint32_t addr) {
  asm volatile("ldmatrix.sync.aligned.m8n8.x2.shared.b16 {%0,%1}, [%2];" : "=r"(r0), "=r"(r1) : "r"(addr) : "memory");
}
__device__ __forceinline__ void stsm_x4(uint32_t addr, uint32_t r0, uint32_t r1, uint32_t r2, uint32_t r3) {
  asm volatile("stmatrix.sync.aligned.m8n8.x4.shared.b16 [%0], {%1,%2,%3,%4};"
               ::"r"(addr), "r"(r0), "r"(r1), "r"(r2), "r"(r3) : "memory");
}
__device__ __forceinline__ void mma16816(float (&c)[4], const uint32_t (&a)[4], uint32_t b0, uint32_t b1) {
  asm volatile("mma.sync.aligned.m16n8k16.row.col.f32.bf16.bf16.f32 {%0,%1,%2,%3}, {%4,%5,%6,%7}, {%8,%9}, {%0,%1,%2,%3};"
               : "+f"(c[0]), "+f"(c[1]), "+f"(c[2]), "+f"(c[3])
               : "r"(a[0]), "r"(a[1]), "r"(a[2]), "r"(a[3]), "r"(b0), "r"(b1));
}
__device__ __forceinline__ void mma1688(float (&c)[4], uint32_t a0, uint32_t a1, uint32_t b0) {
  asm volatile("mma.sync.aligned.m16n8k8.row.col.f32.bf16.bf16.f32 {%0,%1,%2,%3}, {%4,%5}, {%6}, {%0,%1,%2,%3};"
               : "+f"(c[0]), "+f"(c[1]), "+f"(c[2]), "+f"(c[3]) : "r"(a0), "r"(a1), "r"(b0));
}
__device__ __forceinline__ uint32_t pack_bf16(float lo, float hi) {
  uint32_t r;
  asm("cvt.rn.bf16x2.f32 %0, %1, %2;" : "=r"(r) : "f"(hi), "f"(lo));
  return r;
}
__device__ __forceinline__ float bf_lo(uint32_t w) { return __uint_as_float(w << 16); }
__device__ __forceinline__ float bf_hi(uint32_t w) { return __uint_as_float(w & 0xFFFF0000u); }

__device__ __forceinline__ uint4 ld_relaxed4(const void* p) {
  uint4 v;
  asm volatile("ld.relaxed.gpu.global.v4.u32 {%0,%1,%2,%3}, [%4];" : "=r"(v.x), "=r"(v.y), "=r"(v.z), "=r"(v.w) : "l"(p) : "memory");
  return v;
}
__device__ __forceinline__ void st_relaxed4(void* p, uint32_t a, uint32_t b, uint32_t c, uint32_t d) {
  asm volatile("st.relaxed.gpu.global.v4.u32 [%0], {%1,%2,%3,%4};" ::"l"(p), "r"(a), "r"(b), "r"(c), "r"(d) : "memory");
}
__device__ __forceinline__ void st_relaxed2(void* p, uint32_t a, uint32_t b) {
  asm volatile("st.relaxed.gpu.global.v2.u32 [%0], {%1,%2};" ::"l"(p), "r"(a), "r"(b) : "memory");
}
__device__ __forceinline__ void st_relaxed1(void* p, uint32_t a) {
  asm volatile("st.relaxed.gpu.global.u32 [%0], %1;" ::"l"(p), "r"(a) : "memory");
}

__device__ __forceinline__ uint2 ld_relaxed2(const void* p) {
  uint2 v;
  asm volatile("ld.relaxed.gpu.global.v2.u32 {%0,%1}, [%2];" : "=r"(v.x), "=r"(v.y) : "l"(p) : "memory");
  return v;
}
__device__ __forceinline__ void sts64(uint32_t a, uint32_t x, uint32_t y) { asm volatile("st.shared.v2.b32 [%0], {%1,%2};" ::"r"(a), "r"(x), "r"(y) : "memory"); }
__device__ __forceinline__ uint2 lds64(uint32_t a) { uint2 v; asm volatile("ld.shared.v2.b32 {%0,%1}, [%2];" : "=r"(v.x), "=r"(v.y) : "r"(a) : "memory"); return v; }
__device__ __forceinline__ void lds128r(uint32_t (&r)[4], uint32_t a) {
  asm volatile("ld.shared.v4.b32 {%0,%1,%2,%3}, [%4];" : "=r"(r[0]), "=r"(r[1]), "=r"(r[2]), "=r"(r[3]) : "r"(a) : "memory");
}
__device__ __forceinline__ uint32_t movmat(uint32_t a) { uint32_t d; asm volatile("movmatrix.sync.aligned.m8n8.trans.b16 %0, %1;" : "=r"(d) : "r"(a)); return d; }
__device__ __forceinline__ uint32_t mapa(uint32_t addr, uint32_t rank) { uint32_t r; asm volatile("mapa.shared::cluster.u32 %0, %1, %2;" : "=r"(r) : "r"(addr), "r"(rank)); return r; }
__device__ __forceinline__ void st_async1(uint32_t dst, uint32_t a, uint32_t bar) {
  asm volatile("st.async.weak.shared::cluster.mbarrier::complete_tx::bytes.b32 [%0], %1, [%2];" ::"r"(dst), "r"(a), "r"(bar) : "memory");
}
__device__ __forceinline__ void st_async2(uint32_t dst, uint32_t a, uint32_t b, uint32_t bar) {
  asm volatile("st.async.weak.shared::cluster.mbarrier::complete_tx::bytes.v2.b32 [%0], {%1,%2}, [%3];" ::"r"(dst), "r"(a), "r"(b), "r"(bar) : "memory");
}
__device__ __forceinline__ void st_async4(uint32_t dst, uint32_t a, uint32_t b, uint32_t c, uint32_t d, uint32_t bar) {
  asm volatile("st.async.weak.shared::cluster.mbarrier::complete_tx::bytes.v4.b32 [%0], {%1,%2,%3,%4}, [%5];" ::"r"(dst), "r"(a), "r"(b), "r"(c), "r"(d), "r"(bar) : "memory");
}
__device__ __forceinline__ void cluster_arrive() { asm volatile("barrier.cluster.arrive.relaxed.aligned;" ::: "memory"); }
__device__ __forceinline__ void cluster_wait() { asm volatile("barrier.cluster.wait.acquire.aligned;" ::: "memory"); }

__device__ __forceinline__ void wgmma_k3_ss_ta(float (&d)[80], uint64_t da, uint64_t db, int scale_d) {
  asm volatile("{.reg .pred p; setp.ne.b32 p, %82, 0;\n"
    "wgmma.mma_async.sync.aligned.m64n160k16.f32.bf16.bf16 {%0, %1, %2, %3, %4, %5, %6, %7, %8, %9, %10, %11, %12, %13, %14, %15, %16, %17, %18, %19, %20, %21, %22, %23, %24, %25, %26, %27, %28, %29, %30, %31, %32, %33, %34, %35, %36, %37, %38, %39, %40, %41, %42, %43, %44, %45, %46, %47, %48, %49, %50, %51, %52, %53, %54, %55, %56, %57, %58, %59, %60, %61, %62, %63, %64, %65, %66, %67, %68, %69, %70, %71, %72, %73, %74, %75, %76, %77, %78, %79}, %80, %81, p, 1, 1, 1, 0;}"
    : "+f"(d[0]), "+f"(d[1]), "+f"(d[2]), "+f"(d[3]), "+f"(d[4]), "+f"(d[5]), "+f"(d[6]), "+f"(d[7]), "+f"(d[8]), "+f"(d[9]), "+f"(d[10]), "+f"(d[11]), "+f"(d[12]), "+f"(d[13]), "+f"(d[14]), "+f"(d[15]), "+f"(d[16]), "+f"(d[17]), "+f"(d[18]), "+f"(d[19]), "+f"(d[20]), "+f"(d[21]), "+f"(d[22]), "+f"(d[23]), "+f"(d[24]), "+f"(d[25]), "+f"(d[26]), "+f"(d[27]), "+f"(d[28]), "+f"(d[29]), "+f"(d[30]), "+f"(d[31]), "+f"(d[32]), "+f"(d[33]), "+f"(d[34]), "+f"(d[35]), "+f"(d[36]), "+f"(d[37]), "+f"(d[38]), "+f"(d[39]), "+f"(d[40]), "+f"(d[41]), "+f"(d[42]), "+f"(d[43]), "+f"(d[44]), "+f"(d[45]), "+f"(d[46]), "+f"(d[47]), "+f"(d[48]), "+f"(d[49]), "+f"(d[50]), "+f"(d[51]), "+f"(d[52]), "+f"(d[53]), "+f"(d[54]), "+f"(d[55]), "+f"(d[56]), "+f"(d[57]), "+f"(d[58]), "+f"(d[59]), "+f"(d[60]), "+f"(d[61]), "+f"(d[62]), "+f"(d[63]), "+f"(d[64]), "+f"(d[65]), "+f"(d[66]), "+f"(d[67]), "+f"(d[68]), "+f"(d[69]), "+f"(d[70]), "+f"(d[71]), "+f"(d[72]), "+f"(d[73]), "+f"(d[74]), "+f"(d[75]), "+f"(d[76]), "+f"(d[77]), "+f"(d[78]), "+f"(d[79])
    : "l"(da), "l"(db), "r"(scale_d));
}
__device__ __forceinline__ void wgmma_m64n32_ss_ta(float (&d)[16], uint64_t da, uint64_t db, int scale_d) {
  asm volatile("{.reg .pred p; setp.ne.b32 p, %18, 0;\n"
    "wgmma.mma_async.sync.aligned.m64n32k16.f32.bf16.bf16 {%0, %1, %2, %3, %4, %5, %6, %7, %8, %9, %10, %11, %12, %13, %14, %15}, %16, %17, p, 1, 1, 1, 0;}"
    : "+f"(d[0]), "+f"(d[1]), "+f"(d[2]), "+f"(d[3]), "+f"(d[4]), "+f"(d[5]), "+f"(d[6]), "+f"(d[7]), "+f"(d[8]), "+f"(d[9]), "+f"(d[10]), "+f"(d[11]), "+f"(d[12]), "+f"(d[13]), "+f"(d[14]), "+f"(d[15])
    : "l"(da), "l"(db), "r"(scale_d));
}

__device__ __forceinline__ void wgmma_m64n32_rs(float (&d)[16], const uint32_t (&a)[4], uint64_t db, int scale_d) {
  asm volatile("{.reg .pred p; setp.ne.b32 p, %21, 0;\n"
    "wgmma.mma_async.sync.aligned.m64n32k16.f32.bf16.bf16 {%0, %1, %2, %3, %4, %5, %6, %7, %8, %9, %10, %11, %12, %13, %14, %15}, {%16, %17, %18, %19}, %20, p, 1, 1, 0;}"
    : "+f"(d[0]), "+f"(d[1]), "+f"(d[2]), "+f"(d[3]), "+f"(d[4]), "+f"(d[5]), "+f"(d[6]), "+f"(d[7]), "+f"(d[8]), "+f"(d[9]), "+f"(d[10]), "+f"(d[11]), "+f"(d[12]), "+f"(d[13]), "+f"(d[14]), "+f"(d[15])
    : "r"(a[0]), "r"(a[1]), "r"(a[2]), "r"(a[3]), "l"(db), "r"(scale_d));
}

#define X_POS 5
#define T_STEP 2848
#define T_PHASE 1792
#define T_LAG 32
#define T_TOL 192
#define T_SLIP 640
#define O_FIX 5
#define VM_POS 2
#define V_PRE 6
#define SFENCE(i) asm volatile("{.reg .pred p; setp.eq.u32 p, %0, %1; @p trap;}" ::"r"(n), "r"(4096 + (i)) : "memory")
constexpr int RING = 4;
constexpr uint32_t EMPTY = 0xFFFFFFFFu;
namespace xo {
constexpr uint32_t SLOT = 1u << 20, HEAD = 16384;
constexpr uint32_t VM = 512;
constexpr uint32_t PT = 1024;
constexpr uint32_t PM = 1536;
constexpr uint32_t VT = 8192;
constexpr uint32_t MEM = NH * HEAD;
constexpr uint32_t OM = MEM + 16384;
constexpr uint32_t O = RING * SLOT;
constexpr uint32_t BYTES = O + S_LEN * HD * 2;
}
__device__ __align__(1024) uint4 g_scratch[2 * (xo::BYTES / 16)];
__device__ unsigned g_epoch;

struct ChainMaps {
  CUtensorMap wq, wk, wv;
  CUtensorMap wo;
  CUtensorMap x, xq;
  const char* xp;
  uint32_t t_step, t_phase;
};

namespace chain {
constexpr int OFF_X = 65536;
constexpr int OFF_MEM = 131072;
constexpr int OFF_WS = 0;
constexpr int OFF_FP = 147456;
constexpr int OFF_KT = 163840;
constexpr int OFF_QT = 180224;
constexpr int OFF_VT = 196608;
constexpr int OFF_PX = 204800;
constexpr int OFF_S4 = OFF_PX + 1536;
constexpr int OFF_QM = 212992;
constexpr int OFF_KM = 215040;
constexpr int OFF_S1 = 217088;
constexpr int OFF_WVR = 0;
constexpr int OFF_WOR = 147456;
constexpr int OFF_RED = 212992;
constexpr int OFF_VPX = 221184;
constexpr int OFF_RX = 223232;
constexpr int OFF_TR = 225280;
constexpr int OFF_BAR = 229376;
constexpr int BAR_X = OFF_BAR, BAR_TOK = OFF_BAR + 16, BAR_EX = OFF_BAR + 32, BAR_P = OFF_BAR + 40, GRID_TGT = OFF_BAR + 128;
constexpr int CT_BASE = GRID_TGT + 4, CT_HEAD = GRID_TGT + 8, CT_OM = GRID_TGT + 12, CT_MP = GRID_TGT + 16, CT_O = GRID_TGT + 20, CT_PF = GRID_TGT + 24;
constexpr int CT_T1 = GRID_TGT + 32, CT_T2 = GRID_TGT + 36;
constexpr uint32_t RANK_BIT = 1u << 24;
constexpr int SMEM = OFF_BAR + 256;
constexpr uint32_t SB_LO = 1024;
constexpr float SCALE = 0.08838834764831845f, L2E = 1.4426950408889634f;
}

__device__ __forceinline__ uint32_t umax4(uint32_t a, uint32_t b, uint32_t c, uint32_t d) { return max(max(a, b), max(c, d)); }
__device__ __forceinline__ bool warp_incomplete(uint32_t m) { return __any_sync(0xffffffffu, m == EMPTY); }
#define PIN(x) asm volatile("" : "+r"(x))
#define KEEPALIVE(a, z) do { float _d0, _d1, _d2, _d3; asm volatile("mma.sync.aligned.m16n8k16.row.col.f32.bf16.bf16.f32 {%0,%1,%2,%3}, {%4,%5,%6,%7}, {%4,%5}, {%8,%8,%8,%8};" \
    : "=f"(_d0), "=f"(_d1), "=f"(_d2), "=f"(_d3) : "r"(a[0]), "r"(a[1]), "r"(a[2]), "r"(a[3]), "f"(0.f)); \
      \
    asm volatile("{.reg .pred p; setp.ne.u32 p, %0, 0; @p st.shared.f32 [%0], %1;}" ::"r"(z), "f"(_d0 + _d3) : "memory"); } while (0)
constexpr int POLL_LIMIT = 1 << 17;

__device__ __forceinline__ uint32_t keep(uint32_t x) { return __shfl_sync(0xffffffffu, x, threadIdx.x & 31); }
__device__ __forceinline__ char* gptr(uint32_t hi, uint32_t lo) { return (char*)(((uint64_t)hi << 32) | lo); }
__device__ __forceinline__ uint32_t slot_off(int n) { return ((uint32_t)n & (RING - 1)) * xo::SLOT; }
__device__ __forceinline__ float quad_max(float x) {
  const float a = __shfl_xor_sync(~0u, x, 1), b = __shfl_xor_sync(~0u, x, 2), c = __shfl_xor_sync(~0u, x, 3);
  return fmaxf(fmaxf(x, a), fmaxf(b, c));
}
__device__ __forceinline__ void acc_fence(float (&a)[16]) {
#pragma unroll
  for (int i = 0; i < 16; i++) asm volatile("" : "+f"(a[i]) :: "memory");
}
template <int NB = 1, int STRIDE = 0>
__device__ __forceinline__ void gather_issue(uint32_t dst, const char* src) {
#pragma unroll
  for (int b = 0; b < NB; b++)
#pragma unroll
    for (int i = 0; i < 4; i++) cp_async16(dst + b * STRIDE + i * 512, src + b * STRIDE + i * 512);
  cp_async_commit();
}
template <int NB, int STRIDE>
__device__ __forceinline__ bool gather_incomplete(uint32_t chk) {
  uint32_t m = 0;
#pragma unroll
  for (int b = 0; b < NB; b++) m = max(m, umax4(lds32(chk + b * STRIDE), lds32(chk + b * STRIDE + 512), lds32(chk + b * STRIDE + 1024), lds32(chk + b * STRIDE + 1536)));
  return warp_incomplete(m);
}
__device__ __forceinline__ uint32_t ld_relaxed1(const void* p) {
  uint32_t v;
  asm volatile("ld.relaxed.gpu.global.u32 %0, [%1];" : "=r"(v) : "l"(p) : "memory");
  return v;
}
__device__ __forceinline__ uint32_t gtime() { uint64_t g; asm volatile("mov.u64 %0, %%globaltimer;" : "=l"(g) :: "memory"); return (uint32_t)g; }
#define WAIT_UNTIL(t, ka, alive, id) do { \
    int _d = gtime() - (t); \
    if (__builtin_expect(_d > T_TOL, 0)) do { t += T_SLIP; _d -= T_SLIP; } while (_d > T_TOL); \
    if (alive) for (int _k = 64; _d < -96 && --_k; _d = gtime() - (t)) KEEPALIVE(ka, zr); \
    for (uint32_t _g = -128; (int)(_d & ++_g) < 0;) _d = gtime() - (t); } while (0)
__device__ __forceinline__ void issue_x(uint32_t sb, const CUtensorMap* map, int n, int part, int q = 0) {
  asm volatile("{.reg .pred p; elect.sync _|p, 0xffffffff;\n"
               "@p cp.async.bulk.tensor.3d.shared::cluster.global.mbarrier::complete_tx::bytes [%0], [%1, {%3, %4, %5}], [%2];}"
               ::"r"(sb + chain::OFF_X + part * 32768 + q * 16384), "l"(map), "r"(sb + chain::BAR_X + 8 * part), "r"(0), "r"(n * SEG), "r"(part * 8 + q * 4) : "memory");
}
__device__ __forceinline__ void issue_x_if(uint32_t sb, const CUtensorMap* map, int n, int part, uint32_t on) {
  asm volatile("{.reg .pred p, q; elect.sync _|p, 0xffffffff; setp.ne.and.u32 q, %6, 0, p;\n"
               "@q cp.async.bulk.tensor.3d.shared::cluster.global.mbarrier::complete_tx::bytes [%0], [%1, {%3, %4, %5}], [%2];}"
               ::"r"(sb + chain::OFF_X + part * 32768), "l"(map), "r"(sb + chain::BAR_X + 8 * part), "r"(0), "r"(n * SEG), "r"(part * 8), "r"(on) : "memory");
}
__device__ __forceinline__ void prefetch_l2(const char* p, uint32_t bytes) {
  asm volatile("{.reg .pred p; elect.sync _|p, 0xffffffff; @p cp.async.bulk.prefetch.L2.global [%0], %1;}" ::"l"(p), "r"(bytes) : "memory");
}
__device__ __forceinline__ void expect_elect(uint32_t bar, uint32_t bytes) {
  asm volatile("{.reg .pred p; elect.sync _|p, 0xffffffff; @p mbarrier.arrive.expect_tx.shared::cta.b64 _, [%0], %1;}" ::"r"(bar), "r"(bytes) : "memory");
}
template <int WG> __device__ __forceinline__ constexpr uint64_t xdesc(int ks) {
  return (uint64_t)(((chain::SB_LO + chain::OFF_X + WG * 32768 + (ks >> 2) * 4096 + (ks & 3) * 32) >> 4) + (1u << 16)) |
         ((uint64_t)(64u | (1u << 30)) << 32);
}
template <int WG> __device__ __forceinline__ constexpr uint64_t wdesc(int o, int ks) {
  return (uint64_t)(((chain::SB_LO + chain::OFF_WS + WG * 32768 + o * 16384 + ks * 2048) >> 4) + (1u << 16)) | ((uint64_t)(64u | (1u << 30)) << 32);
}
__device__ __forceinline__ void load_mem0(uint2 (&m)[8], const bf16* __restrict__ mem0) {
#pragma unroll
  for (int r = 0; r < 8; r++) m[r] = ld_relaxed2((const uint2*)(mem0 + r * DM) + threadIdx.x);
}
__device__ __forceinline__ void store_mem0(uint32_t sb, const uint2 (&m)[8]) {
  const uint32_t d = sb + chain::OFF_MEM + threadIdx.x * 64;
  sts128(d, make_uint4(__byte_perm(m[0].x, m[1].x, 0x5410), __byte_perm(m[2].x, m[3].x, 0x5410), __byte_perm(m[4].x, m[5].x, 0x5410), __byte_perm(m[6].x, m[7].x, 0x5410)));
  sts128(d + 16, make_uint4(__byte_perm(m[0].x, m[1].x, 0x7632), __byte_perm(m[2].x, m[3].x, 0x7632), __byte_perm(m[4].x, m[5].x, 0x7632), __byte_perm(m[6].x, m[7].x, 0x7632)));
  sts128(d + 32, make_uint4(__byte_perm(m[0].y, m[1].y, 0x5410), __byte_perm(m[2].y, m[3].y, 0x5410), __byte_perm(m[4].y, m[5].y, 0x5410), __byte_perm(m[6].y, m[7].y, 0x5410)));
  sts128(d + 48, make_uint4(__byte_perm(m[0].y, m[1].y, 0x7632), __byte_perm(m[2].y, m[3].y, 0x7632), __byte_perm(m[4].y, m[5].y, 0x7632), __byte_perm(m[6].y, m[7].y, 0x7632)));
}
template <int K> __device__ __forceinline__ uint32_t loop_zero(int n) { uint32_t z; asm volatile("shr.u32 %0, %1, %2;" : "=r"(z) : "r"(n), "n"(16 + K)); return z; }
#define NEWZ(k) zr = loop_zero<k>(n)

template <int WG>
__device__ __forceinline__ void role_a(const ChainMaps& maps, const bf16* __restrict__ mem0, const uint32_t sb, const uint32_t xbase_hi) {
  using namespace chain;
  const int h = blockIdx.x >> 2;
  const bool J = sb >= RANK_BIT;
  const uint32_t u16 = (threadIdx.x & 96) * 64 + (threadIdx.x & 31) * 16;
  const uint32_t t16 = keep(u16), l16 = keep((threadIdx.x & 31) * 16);
  const uint32_t a_wl = keep((((threadIdx.x >> 4) & 1) * 8 + (threadIdx.x & 7)) * 128 + (((((threadIdx.x >> 4) & 6) + ((threadIdx.x >> 3) & 1)) ^ (threadIdx.x & 7)) << 4));
  const uint32_t xhi = keep(xbase_hi + (t16 >> 16));
#define xh (lds32(sb + CT_HEAD) + t16)
#define xm (lds32(sb + CT_BASE) + t16 + xo::MEM)
#define last_warp __any_sync(0xffffffffu, tv >= 6144)
#define tv (t16 ^ zr)
  const CUtensorMap* wm = J ? &maps.wk : &maps.wq;

  uint32_t aW[2][24][4];
  uint2 m0[8];
  load_mem0(m0, mem0);
  mbar_wait(sb + BAR_P, 0);
#pragma unroll
  for (int ks = 0; ks < 24; ks++) ldsm_x4_t(aW[0][ks], sb + a_wl + OFF_X + WG * 49152 + ks * 2048);
  named_bar(0, 256);
  if (WG == 1 && __any_sync(0xffffffffu, t16 >= 6144)) {
    fence_async_smem();
    if (l16 == 0) {
      mbar_expect_tx(sb + BAR_P + 16, 2 * 16384);
      for (int q = 0; q < 2; q++) tma_load_2d(sb + OFF_X + (4 + q) * 16384, wm, h * DH + (q ^ 1) * 64, q * 512 + 256, sb + BAR_P + 16);
    }
    __syncwarp();
    expect_elect(sb + BAR_X, 32768); expect_elect(sb + BAR_X + 8, 32768); expect_elect(sb + BAR_TOK, 8192);
    issue_x(sb, &maps.x, 0, 0); issue_x(sb, &maps.x, 0, 1);
  }
  mbar_wait(sb + BAR_P + 8, 0);
#pragma unroll
  for (int ks = 0; ks < 16; ks++) ldsm_x4_t(aW[1][ks], sb + a_wl + OFF_X + 6 * 16384 + WG * 32768 + ks * 2048);
  mbar_wait(sb + BAR_P + 16, 0);
#pragma unroll
  for (int ks = 0; ks < 8; ks++) ldsm_x4_t(aW[1][16 + ks], sb + a_wl + OFF_X + (4 + WG) * 16384 + ks * 2048);
  named_bar(0, 256);
  cluster_arrive();
  store_mem0(sb, m0);
  mbar_wait(sb + BAR_P + 24, 0);
  cluster_wait();
  const uint32_t rsb = sb ^ RANK_BIT;
  const uint32_t a_ws = sb + a_wl + OFF_WS + WG * 32768;

  uint32_t ws[2][4][4];
  auto load_ws = [&]() {
#pragma unroll
    for (int q = 0; q < 2; q++) {
      const uint32_t a = a_ws + q * 4096;
      ldsm_x4_t(ws[q][0], a); ldsm_x4_t(ws[q][1], a + 16384); ldsm_x4_t(ws[q][2], a + 2048); ldsm_x4_t(ws[q][3], a + 16384 + 2048);
    }
  };
  uint32_t tref = 0;
#pragma unroll 1
  for (int n = 0; n <= (J ? NSEG : NSEG - 1); n++) {
#define s (n - 1)
#define sv ((int)(n ^ zr) - 1)
    const bool more = __builtin_expect(s + 1 < NSEG, 1);
    uint32_t zr = loop_zero<0>(n);
#define wq ((int)(tv >> 11))
#define lv (l16 ^ zr)
#define gh (xh + slot_off(sv))
    uint32_t tmp[4][4];
    auto load_tmp = [&](int o) {
#pragma unroll
      for (int ks = 0; ks < 4; ks++) ldsm_x4_t(tmp[ks], a_ws + o * 16384 + ks * 2048);
    };
    auto wait_x = [&]() { mbar_wait<0>(sb + BAR_X + 8 * WG, n & 1); };
    if (__builtin_expect(s < 0, 0)) { load_tmp(1); wait_x(); }
    else {
      {
        if (WG == 1) { if (__builtin_expect(s > 0, 1)) {
          const uint32_t chk = sb + OFF_MEM + t16 + ((lv >> 5) & 12);
          uint32_t tries = zr;
#pragma unroll 1
          do {
            if (tries) {
              const char* src = gptr(xhi, xm + slot_off(sv));
              tref += T_SLIP;
              WAIT_UNTIL(tref, aW[0][0], 1, -1);
              gather_issue<2, 8192>(sb + OFF_MEM + tv, src);
            }
            KEEPALIVE(aW[0][0], zr);
            cp_async_wait_group<0>();
          } while (gather_incomplete<2, 8192>(chk) && ++tries < POLL_LIMIT);
        } } else if (J == 0) {
          uint32_t tries = s == 0;
#pragma unroll 1
          do {
            if (tries) gather_issue(sb + OFF_VT + tv, gptr(xhi, gh) + xo::VT);
            cp_async_wait_group<0>();
          } while (gather_incomplete<1, 0>(sb + OFF_VT + t16 + ((lv >> 5) & 12)) && ++tries < POLL_LIMIT);
        }
        named_bar(1, 256);
      }
      float c[2][2][4];
#pragma unroll
      for (int i = 0; i < 4; i++) c[i >> 1][i & 1][0] = c[i >> 1][i & 1][1] = c[i >> 1][i & 1][2] = c[i >> 1][i & 1][3] = 0.f;
      {
        const uint32_t a_mem = sb + OFF_MEM + WG * 8192 + l16;
        uint32_t b[4][4];
        bool tok;
        constexpr int PR[16] = {12, 13, 0, 1, 2, 3, 4, 14, 5, 6, 7, 8, 9, 15, 10, 11};
        ldsm_x4_t(b[0], a_mem + PR[0] * 512); ldsm_x4_t(b[1], a_mem + PR[1] * 512);
#pragma unroll
        for (int i = 0; i < 16; i++) {
          if ((i & 1) == 0 && i < 14) {
            ldsm_x4_t(b[(i + 2) & 3], a_mem + PR[i + 2] * 512); ldsm_x4_t(b[(i + 3) & 3], a_mem + PR[i + 3] * 512);
            if (i == 2 || i == 8) { ldsm_x4_t(ws[1][0], a_ws + (i == 2 ? 2 : 3) * 4096); ldsm_x4_t(ws[1][1], a_ws + (i == 2 ? 2 : 3) * 4096 + 16384); }
            if (i == 4 || i == 10) { ldsm_x4_t(ws[1][2], a_ws + (i == 4 ? 2 : 3) * 4096 + 2048); ldsm_x4_t(ws[1][3], a_ws + (i == 4 ? 2 : 3) * 4096 + 16384 + 2048); }
          }
          const int p = PR[i];
          if (p >= 12) {
            const int z = i != 0;
            mma16816(c[0][0], ws[z][0], b[i & 3][0], b[i & 3][1]); mma16816(c[1][0], ws[z][1], b[i & 3][0], b[i & 3][1]);
            mma16816(c[0][1], ws[z][2], b[i & 3][2], b[i & 3][3]); mma16816(c[1][1], ws[z][3], b[i & 3][2], b[i & 3][3]);
          } else {
            mma16816(c[1][0], aW[1][2 * p], b[i & 3][0], b[i & 3][1]); mma16816(c[1][1], aW[1][2 * p + 1], b[i & 3][2], b[i & 3][3]);
            mma16816(c[0][0], aW[0][2 * p], b[i & 3][0], b[i & 3][1]); mma16816(c[0][1], aW[0][2 * p + 1], b[i & 3][2], b[i & 3][3]);
          }
          if (i == 12) tok = mbar_test(sb + BAR_TOK + 8 * (s & 1), (s >> 1) & 1);
          if (i == 15 && __builtin_expect(!tok, 0)) mbar_wait(sb + BAR_TOK + 8 * (s & 1), (s >> 1) & 1);
          if (i == X_POS + 4 * (1 - WG)) { issue_x_if(sb, &maps.x, s + 1, WG, t16 >= 6144 && more); if (WG) __syncwarp(); }
        }
      }
      sts128f(sb + OFF_PX + WG * 512 + t16, make_float4(c[1][0][0] + c[1][1][0], c[1][0][1] + c[1][1][1], c[1][0][2] + c[1][1][2], c[1][0][3] + c[1][1][3]));
      const float4 own = make_float4(c[0][0][0] + c[0][1][0], c[0][0][1] + c[0][1][1], c[0][0][2] + c[0][1][2], c[0][0][3] + c[0][1][3]);
      NEWZ(1);
      uint32_t a = (J ? OFF_KM : OFF_QM) + WG * 1024 + wq * 256 + (lv >> 2);
      uint32_t ra = rsb + a, ra2 = ra + 128, rx = rsb + BAR_EX + zr;
      PIN(a); PIN(ra); PIN(ra2); PIN(rx);
      SFENCE(16);
      named_bar(3, 256);
      {
        const float4 o = lds128f(sb + OFF_PX + (WG ^ 1) * 512 + t16);
        const uint32_t lo = pack_bf16(own.x + o.x, own.y + o.y), hi = pack_bf16(own.z + o.z, own.w + o.w);
        if (J == 1 && more) { st_async1(ra, lo, rx); st_async1(ra2, hi, rx); }
        sts32(sb + a, lo); sts32(sb + a + 128, hi);
      }
      const uint32_t kt = sb + OFF_KT + (s & 1) * 8192;
      auto load_kb = [&](uint32_t (&d)[4], uint32_t a) { const uint2 u = lds64(a), v = lds64(a + 1024); d[0] = u.x; d[1] = u.y; d[2] = v.x; d[3] = v.y; };
      if (J == 0) {
        uint32_t am[4][4], kb[4][4];
        uint2 vm0, vm1;
        const char* pvm = WG == 0 ? gptr(xhi, gh - (lv >> 1)) + xo::VM : nullptr;
        if (WG == 0 && VM_POS == 0) { vm0 = ld_relaxed2(pvm); vm1 = ld_relaxed2(pvm + 256); }
        if (WG == 1) {
#pragma unroll
          for (int p = 0; p < 4; p++) load_kb(kb[p], kt + wq * 256 + (lv >> 1) + p * 2048);
        }
        named_bar(7, 256);
#pragma unroll
        for (int p = 0; p < 4; p++) ldsm_x4_t(am[p], sb + OFF_QM + p * 512 + ((lv & 128) << 1) + ((lv & 256) >> 1) + (lv & 112));
        auto scores = [&]() {
          float c0[2][4], c1[2][4];
#pragma unroll
          for (int i = 0; i < 2; i++) { c0[i][0] = c0[i][1] = c0[i][2] = c0[i][3] = 0.f; c1[i][0] = c1[i][1] = c1[i][2] = c1[i][3] = 0.f; }
#pragma unroll
          for (int p = 0; p < 4; p++) { mma16816(c0[p & 1], am[p], kb[p][0], kb[p][1]); mma16816(c1[p & 1], am[p], kb[p][2], kb[p][3]); }
          const uint32_t r1 = pack_bf16((c0[0][0] + c0[1][0]) + (c1[0][2] + c1[1][2]), (c0[0][1] + c0[1][1]) + (c1[0][3] + c1[1][3]));
          return pack_bf16(bf_lo(r1) * SCALE, bf_hi(r1) * SCALE);
        };
        if (WG == 1) {
          const uint32_t st = scores();
          uint32_t vb[4][4];
#pragma unroll
          for (int e = 0; e < 4; e++) lds128r(vb[e], sb + OFF_VT + t16 + e * 512);
          __syncwarp();
          sts32(sb + OFF_S4 + l16 + wq * 4, st);
          named_bar(8, 128);
          const uint4 sc = lds128(sb + OFF_S4 + l16);
          float x[8] = {bf_lo(sc.x), bf_hi(sc.x), bf_lo(sc.y), bf_hi(sc.y), bf_lo(sc.z), bf_hi(sc.z), bf_lo(sc.w), bf_hi(sc.w)};
          float mx = fmaxf(fmaxf(fmaxf(x[0], x[1]), fmaxf(x[2], x[3])), fmaxf(fmaxf(x[4], x[5]), fmaxf(x[6], x[7])));
          mx = quad_max(mx);
          const float mb = mx * L2E;
#pragma unroll
          for (int i = 0; i < 8; i++) x[i] = ex2(fmaf(x[i], L2E, -mb));
          uint32_t pa[4], pb[4];
          asm volatile("" : "=r"(pa[1]), "=r"(pa[3]), "=r"(pb[1]), "=r"(pb[3]));
          pa[0] = pack_bf16(x[0], x[1]); pa[2] = pack_bf16(x[2], x[3]);
          pb[0] = pack_bf16(x[4], x[5]); pb[2] = pack_bf16(x[6], x[7]);
          float oa[4][4];
#pragma unroll
          for (int e = 0; e < 4; e++) { oa[e][0] = oa[e][1] = oa[e][2] = oa[e][3] = 0.f; mma16816(oa[e], pa, vb[e][0], vb[e][1]); }
#pragma unroll
          for (int e = 0; e < 4; e++) mma16816(oa[e], pb, vb[e][2], vb[e][3]);
          sts64(sb + OFF_PX + 1024 + t16, __float_as_uint(mx), __float_as_uint(((x[0] + x[1]) + (x[2] + x[3])) + ((x[4] + x[5]) + (x[6] + x[7]))));
          sts128f(sb + OFF_PX + t16, make_float4(oa[0][0], oa[0][1], oa[1][0], oa[1][1]));
          sts128f(sb + OFF_PX + 512 + t16, make_float4(oa[2][0], oa[2][1], oa[3][0], oa[3][1]));
          named_bar_arrive(9, 256);
          wait_x();
          load_tmp(1);
        } else {
          if (VM_POS == 1) { pvm += am[3][0] & zr; vm0 = ld_relaxed2(pvm); vm1 = ld_relaxed2(pvm + 256); }
          const uint32_t xo0 = lds32(sb + CT_OM) + wq * 512 + l16;
          mbar_wait<0>(sb + BAR_EX, s & 1);
          if (VM_POS == 2) { vm0 = ld_relaxed2(pvm); vm1 = ld_relaxed2(pvm + 256); }
#pragma unroll
          for (int p = 0; p < 4; p++) ldsm_x4_t(kb[p], sb + OFF_KM + p * 512 + l16);
          const uint32_t sm = scores();
          float mx = quad_max(fmaxf(bf_lo(sm), bf_hi(sm)));
          SFENCE(25);
          named_bar(9, 256);
          const uint2 ms = lds64(sb + OFF_PX + 1024 + t16);
          const float4 t0 = lds128f(sb + OFF_PX + t16), t1 = lds128f(sb + OFF_PX + 512 + t16);
          mx = fmaxf(mx, __uint_as_float(ms.x));
          const float mb = mx * L2E;
          const float e0 = ex2(fmaf(bf_lo(sm), L2E, -mb)), e1 = ex2(fmaf(bf_hi(sm), L2E, -mb)), ct = ex2(fmaf(__uint_as_float(ms.x), L2E, -mb));
          uint32_t p4 = pack_bf16(e0, e1), p5;
          asm volatile("" : "=r"(p5));
          float sx = fmaf(ct, __uint_as_float(ms.y), e0 + e1);
          float oa[4][4] = {{t0.x * ct, t0.y * ct, 0.f, 0.f}, {t0.z * ct, t0.w * ct, 0.f, 0.f}, {t1.x * ct, t1.y * ct, 0.f, 0.f}, {t1.z * ct, t1.w * ct, 0.f, 0.f}};
          const float s1 = __shfl_xor_sync(~0u, sx, 1), s2 = __shfl_xor_sync(~0u, sx, 2), s3 = __shfl_xor_sync(~0u, sx, 3);
          if (__builtin_expect(warp_incomplete(max(vm0.x, vm1.x)), 0)) {
            uint32_t tries = zr;
#pragma unroll 1
            do { vm0 = ld_relaxed2(pvm); vm1 = ld_relaxed2(pvm + 256); } while (warp_incomplete(max(vm0.x, vm1.x)) && ++tries < POLL_LIMIT);
          }
          mma1688(oa[0], p4, p5, vm0.x); mma1688(oa[1], p4, p5, vm0.y); mma1688(oa[2], p4, p5, vm1.x); mma1688(oa[3], p4, p5, vm1.y);
          const float rx = rcp((sx + s1) + (s2 + s3));
          st_relaxed4(gptr(xhi, xo0 + slot_off(sv)), pack_bf16(oa[0][0] * rx, oa[0][1] * rx), pack_bf16(oa[1][0] * rx, oa[1][1] * rx),
                      pack_bf16(oa[2][0] * rx, oa[2][1] * rx), pack_bf16(oa[3][0] * rx, oa[3][1] * rx));
          SFENCE(24);
          named_bar_arrive(10, 256);
          st_relaxed4(gptr(xhi, xo0 + slot_off(sv + 3)), EMPTY, EMPTY, EMPTY, EMPTY);
          load_tmp(1);
          wait_x();
        }
      } else {
        bool xok;
        {
          const int mt = WG | (wq == 3), ktile = wq == 3 ? 2 + WG : wq - 1;
          const uint32_t qt = sb + OFF_QT + (s & 1) * 8192 + mt * 512 + l16;
          uint32_t kb[4][4], q[8][4];
          if (__any_sync(0xffffffffu, tv < 2048)) {
            named_bar(7, 256);
#pragma unroll
            for (int p = 0; p < 4; p++) ldsm_x4_t(kb[p], sb + OFF_KM + p * 512 + l16);
          } else {
            named_bar_arrive(7, 256);
#pragma unroll
            for (int p = 0; p < 4; p++) load_kb(kb[p], kt + (lv >> 1) + ktile * 256 + p * 2048);
          }
#pragma unroll
          for (int i = 0; i < 8; i++) lds128r(q[i], qt + i * 1024);
          __syncwarp();
          float c0[4][4];
#pragma unroll
          for (int i = 0; i < 4; i++) { c0[i][0] = c0[i][1] = c0[i][2] = c0[i][3] = 0.f; mma16816(c0[i], q[i], kb[i >> 1][(i & 1) * 2], kb[i >> 1][(i & 1) * 2 + 1]); }
#pragma unroll
          for (int i = 0; i < 4; i++) mma16816(c0[i], q[4 + i], kb[2 + (i >> 1)][(i & 1) * 2], kb[2 + (i >> 1)][(i & 1) * 2 + 1]);
          load_tmp(1);
          xok = mbar_test(sb + BAR_X + 8 * WG, n & 1);
          NEWZ(3);
          const uint32_t r0 = pack_bf16((c0[0][0] + c0[1][0]) + (c0[2][0] + c0[3][0]), (c0[0][1] + c0[1][1]) + (c0[2][1] + c0[3][1]));
          const uint32_t r1 = pack_bf16((c0[0][2] + c0[1][2]) + (c0[2][2] + c0[3][2]), (c0[0][3] + c0[1][3]) + (c0[2][3] + c0[3][3]));
          const uint32_t sa = wq == 0 ? sb + OFF_S1 + (lv >> 2) + mt * 256 : sb + OFF_S4 + l16 + mt * 4096 + ktile * 4;
          sts32(sa, pack_bf16(bf_lo(r0) * SCALE, bf_hi(r0) * SCALE));
          sts32(sa + (wq == 0 ? 128 : 2048), pack_bf16(bf_lo(r1) * SCALE, bf_hi(r1) * SCALE));
        }
        if (WG == 1) named_bar_arrive(8, 256);
        else {
          if (more) named_bar_arrive(10, 256);
          const uint32_t gp = gh;
          named_bar(8, 256);
          const uint4 sc = lds128(sb + OFF_S4 + t16); const uint32_t s1 = lds32(sb + OFF_S1 + wq * 128 + (lv >> 2));
          float y[10] = {bf_lo(s1), bf_hi(s1), bf_lo(sc.x), bf_hi(sc.x), bf_lo(sc.y), bf_hi(sc.y), bf_lo(sc.z), bf_hi(sc.z), bf_lo(sc.w), bf_hi(sc.w)};
          const int rel = wq * 8 + (int)(lv >> 6) - (int)((lv >> 3) & 6);
          const float NEG = -999292928.f;
#pragma unroll
          for (int e = 0; e < 4; e++) {
            if (e * 8 > rel) y[2 * e + 2] = NEG;
            if (e * 8 + 1 > rel) y[2 * e + 3] = NEG;
          }
          float my = fmaxf(fmaxf(fmaxf(y[0], y[1]), fmaxf(y[2], y[3])), fmaxf(fmaxf(y[4], y[5]), fmaxf(y[6], y[7])));
          my = quad_max(fmaxf(my, fmaxf(y[8], y[9])));
#pragma unroll
          for (int i = 0; i < 10; i++) y[i] = ex2((y[i] - my) * L2E);
          float sy = ((y[0] + y[1]) + (y[2] + y[3])) + ((y[4] + y[5]) + (y[6] + y[7])) + (y[8] + y[9]);
          const float ry = rcp((sy + __shfl_xor_sync(~0u, sy, 1)) + (__shfl_xor_sync(~0u, sy, 2) + __shfl_xor_sync(~0u, sy, 3)));
          st_relaxed4(gptr(xhi, gp) + xo::PT, pack_bf16(y[2] * ry, y[3] * ry), pack_bf16(y[4] * ry, y[5] * ry), pack_bf16(y[6] * ry, y[7] * ry), pack_bf16(y[8] * ry, y[9] * ry));
          const uint32_t l12 = lv - (lv >> 2);
          st_relaxed1(gptr(xhi, gp - l12) + xo::PM, pack_bf16(y[0] * ry, y[1] * ry));
        }
        if (!xok && more) wait_x();
      }
    }
    if (more) {
      float acc[16];
      const uint32_t xph = (s + 1) & 1;
      auto batch = [&](const uint32_t (&a)[24][4], int o) {
        wg_fence();
#pragma unroll
        for (int ks = 4; ks < 8; ks++) wgmma_m64n32_ss_ta(acc, wdesc<WG>(o, ks), xdesc<WG>(24 + ks), ks != 4);
#pragma unroll
        for (int ks = 0; ks < 4; ks++) wgmma_m64n32_rs(acc, tmp[ks], xdesc<WG>(24 + ks), 1);
#pragma unroll
        for (int ks = 0; ks < 24; ks++) wgmma_m64n32_rs(acc, a[ks], xdesc<WG>(ks), 1);
        wg_commit();
      };
      if (WG == 0) named_bar(12, 256);
      else if (__builtin_expect(s >= 0, 1)) named_bar(10, 256);
      batch(aW[1], 1);
      named_bar_arrive(WG ? 12 : 13, 256);
      wg_wait<0>();
      acc_fence(acc);
      load_tmp(0);
#pragma unroll
      for (int i = 0; i < 4; i++) sts128f(sb + OFF_FP + WG * 8192 + t16 + i * 512, make_float4(acc[4 * i], acc[4 * i + 1], acc[4 * i + 2], acc[4 * i + 3]));
      NEWZ(4);
      if (WG == 0 && s >= 0) {
        const uint32_t g1 = xh + slot_off(sv + 1);
        if (J == 0) gather_issue(sb + OFF_VT + tv, gptr(xhi, g1) + xo::VT);
        else {
          st_relaxed4(gptr(xhi, g1) + xo::PT, EMPTY, EMPTY, EMPTY, EMPTY);
          st_relaxed1(gptr(xhi, g1 - lv + (lv >> 2)) + xo::PM, EMPTY);
        }
      }
      uint32_t esrc = 0;
      if (WG == 1) { esrc = xm + slot_off(sv + 1); tref += lds32(sb + CT_T1); }
      named_bar(WG ? 13 : 14, 256);
      batch(aW[0], 0);
      NEWZ(5);
      if (WG == 1) {
        named_bar(14, 256);
        if (last_warp && s + 2 < NSEG) {
          expect_elect(sb + BAR_TOK + 8 * (xph ^ 1), 8192); expect_elect(sb + BAR_X, 32768); expect_elect(sb + BAR_X + 8, 32768);
          if (J == 0) expect_elect(sb + BAR_EX, 2048);
          if (s == NSEG - 3) asm volatile("griddepcontrol.launch_dependents;");
        }
      }
      float4 oth[4];
#pragma unroll
      for (int i = 0; i < 4; i++) oth[i] = lds128f(sb + OFF_FP + (WG ^ 1) * 8192 + t16 + i * 512);
      if (WG == 1 && __builtin_expect(s >= 0, 1)) {
        WAIT_UNTIL(tref, aW[0][0], 0, 0);
        gather_issue<2, 8192>(sb + OFF_MEM + tv, gptr(xhi, esrc));
      }
      wg_wait<0>();
      acc_fence(acc);
      uint32_t lt[4], ht[4];
#pragma unroll
      for (int i = 0; i < 4; i++) {
        const float4 o = oth[i];
        lt[i] = movmat(pack_bf16(acc[4 * i] + o.x, acc[4 * i + 1] + o.y)); ht[i] = movmat(pack_bf16(acc[4 * i + 2] + o.z, acc[4 * i + 3] + o.w));
      }
      NEWZ(6);
      uint32_t tb = xph * 8192 + WG * 4096 + wq * 1024;
      if (J == 0) {
        tb += OFF_QT;
        sts128(sb + tb + l16, make_uint4(lt[0], lt[1], ht[0], ht[1])); sts128(sb + tb + 512 + l16, make_uint4(lt[2], lt[3], ht[2], ht[3]));
      } else {
        tb += OFF_KT;
#pragma unroll
        for (int i = 0; i < 4; i++) sts64(sb + tb + (lv >> 1) + i * 256, lt[i], ht[i]);
      }
      if (WG == 0 && last_warp) {
        load_ws();
        named_bar(11, 256);
        fence_async_smem();
        const uint32_t tt = (J ? OFF_KT : OFF_QT) + xph * 8192;
        asm volatile("{.reg .pred p; elect.sync _|p, 0xffffffff;\n"
                     "@p cp.async.bulk.shared::cluster.shared::cta.mbarrier::complete_tx::bytes [%0], [%1], 8192, [%2];}"
                     ::"r"(rsb + tt), "r"(sb + tt), "r"(rsb + BAR_TOK + 8 * xph) : "memory");
      } else {
        named_bar_arrive(11, 256);
        load_ws();
      }
    }
    if (!more) break;
    if (__builtin_expect(s < 0, 0)) {
      tref = gtime() / T_SLIP * T_SLIP - T_SLIP;
    }
  }
  cp_async_wait_group<0>();
  if (J == 0) mbar_wait(sb + BAR_TOK + 8, 1);
}

template <int WG>
__device__ __forceinline__ void role_v(const ChainMaps& maps, const bf16* __restrict__ mem0, const uint32_t sb, const uint32_t xbase_hi) {
  using namespace chain;
  const int h = blockIdx.x >> 2;
  const uint32_t u16 = (threadIdx.x & 96) * 64 + (threadIdx.x & 31) * 16;
  const uint32_t t16 = keep(u16), l16 = keep((threadIdx.x & 31) * 16);
  const uint32_t xhi = keep(xbase_hi + (t16 >> 16));
#define j (sb >> 24)
  auto wv_addr = [&](uint32_t t) { return WG * 32768 + ((t & 256) << 2) + ((t & 112) << 3) + ((((t >> 6) & 96) + ((t >> 3) & 16)) ^ (t & 112)); };
  auto wo_addr = [&](uint32_t t) { return OFF_WOR + WG * 32768 + ((t & 6144) << 2) + ((t & 256) << 1) + ((t & 112) << 2) + ((((j ^ 1) << 5) + ((t >> 3) & 16)) ^ ((t >> 1) & 48)); };
#define ovt (((tv + l16) >> 1) + (xo::VT + WG * 512 + j * 4096))
#define ovm (((tv & 4096) >> 1) + ((tv & 2048) >> 3) + (lv >> 1) + (xo::VM + j * 4096))
#define xvt (lds32(sb + CT_HEAD) + ovt)
#define xvm (lds32(sb + CT_HEAD) + ovm)
#define xom (lds32(sb + CT_OM) + t16 + WG * 8192)
#define warp_is(q) __any_sync(0xffffffffu, (tv >> 11) == (q))
#define upper_warps (WG == 1 || __any_sync(0xffffffffu, tv >= 4096))

  uint32_t aV[16][4];
  uint32_t aO[16][4];
  uint32_t bO[16][4];
  uint32_t rot[16][4];
  if (WG == 1 && __any_sync(0xffffffffu, t16 >= 6144)) {
    expect_elect(sb + BAR_X, 32768); expect_elect(sb + BAR_X + 8, 32768);
    issue_x(sb, &maps.x, 0, 0); issue_x(sb, &maps.x, 0, 1);
    prefetch_l2(maps.xp + 65536 + (h * 2 + j) * 3072, 3072);
  }
  cluster_arrive();
  { uint2 m0[8]; load_mem0(m0, mem0); store_mem0(sb, m0); }
  mbar_wait(sb + BAR_P, 0);
#pragma unroll
  for (int ks = 0; ks < 16; ks++) ldsm_x4_t(aV[ks], sb + wv_addr(t16) + OFF_WOR + ks * 2048);
  auto load_v = [&](uint32_t t) {
#pragma unroll
    for (int ks = 0; ks < 16; ks++) ldsm_x4_t(rot[ks], sb + wv_addr(t) + OFF_WVR + ks * 2048);
  };
  load_v(t16);
  named_bar(0, 256);
  if (threadIdx.x == 0) {
    fence_async_smem();
    mbar_expect_tx(sb + BAR_P + 8, 4 * 16384);
    for (int q = 0; q < 4; q++) tma_load_2d(sb + OFF_WOR + q * 16384, &maps.wo, h * 32, j * 2048 + q * 256, sb + BAR_P + 8);
    for (int q = 0; q < 4; q++) tma_prefetch_2d(&maps.wo, h * 32, j * 2048 + 1024 + q * 256);
  }
  __syncwarp();
  cluster_wait();
  const uint32_t rsb = sb ^ RANK_BIT;

  uint32_t tref = 0;
#pragma unroll 1
  for (int n = 0; n <= NSEG; n++) {
    const bool more = __builtin_expect(s + 1 < NSEG, 1);
    uint32_t zr = loop_zero<0>(n);
    if (__builtin_expect(s >= 0, 1)) {
      if (__builtin_expect(s > 0, 1)) {
        const uint32_t dst = sb + OFF_MEM + WG * 8192 + t16 + ((lv >> 5) & 12);
        uint32_t tries = zr;
#pragma unroll 1
        do {
          if (tries) { const char* src = gptr(xhi, xm + WG * 8192 + slot_off(sv)); tref += T_SLIP; WAIT_UNTIL(tref, aV[0], 1, -1); gather_issue(sb + OFF_MEM + WG * 8192 + tv, src); }
          KEEPALIVE(aV[0], zr);
          cp_async_wait_group<0>();
        } while (gather_incomplete<1, 0>(dst) && ++tries < POLL_LIMIT);
        named_bar(1 + WG, 128);
      }
      const uint32_t a_mem = sb + OFF_MEM + WG * 8192 + l16;
      float c[2][4];
      c[0][0] = c[0][1] = c[0][2] = c[0][3] = c[1][0] = c[1][1] = c[1][2] = c[1][3] = 0.f;
      constexpr int NBUF = (48 - 8 - 4 * O_FIX) / 4;
      uint32_t b[NBUF][4];
#pragma unroll
      for (int p = 0; p < NBUF - 1; p++) ldsm_x4_t(b[p], a_mem + p * 512);
#pragma unroll
      for (int p = 0; p < 16; p++) {
        if (p + NBUF - 1 < 16) ldsm_x4_t(b[(p + NBUF - 1) % NBUF], a_mem + (p + NBUF - 1) * 512);
        if (p < 8) { mma16816(c[0], aV[2 * p], b[p % NBUF][0], b[p % NBUF][1]); mma16816(c[1], aV[2 * p + 1], b[p % NBUF][2], b[p % NBUF][3]); }
        else { mma16816(c[0], rot[2 * p - 16], b[p % NBUF][0], b[p % NBUF][1]); mma16816(c[1], rot[2 * p - 15], b[p % NBUF][2], b[p % NBUF][3]); }
      }
      SFENCE(15);
      const float4 own = make_float4(c[0][0] + c[1][0], c[0][1] + c[1][1], c[0][2] + c[1][2], c[0][3] + c[1][3]);
      NEWZ(1);
      const uint32_t pvm = WG == 0 ? xvm + slot_off(sv) : 0;
      if (WG == 1) sts128f(sb + OFF_VPX + wq * 512 + l16, own);
      named_bar(3, 256);
      if (WG == 0) {
        const float4 o = lds128f(sb + OFF_VPX + wq * 512 + l16);
        st_relaxed2(gptr(xhi, pvm), pack_bf16(own.x + o.x, own.y + o.y), pack_bf16(own.z + o.z, own.w + o.w));
      }
    }
    auto token_pv = [&](int seg, bool staged) {
      constexpr int NU = 2 - WG;
      uint4 pt0, pt1, v0[NU], v1[NU]; uint32_t pm0, pm1; uint2 vm[NU];
      const uint32_t ap = l16 + WG * 4096 + xo::PT, am = (lv >> 2) + WG * 4096 + xo::PM;
      const uint32_t at = ovt - WG * 512;
      if (staged) {
        const uint32_t b = sb + OFF_MEM;
        pt0 = lds128(b + ap); pt1 = lds128(b + ap + 2048); pm0 = lds32(b + am); pm1 = lds32(b + am + 2048);
#pragma unroll
        for (int u = 0; u < NU; u++) { v0[u] = lds128(b + at - u * 2048); v1[u] = lds128(b + at + 512 - u * 2048); vm[u] = lds64(b + ovm - u * 2048); }
      } else {
        const uint32_t b = lds32(sb + CT_HEAD) + slot_off(seg);
        pt0.x = EMPTY;
#pragma unroll
        for (int u = 0; u < NU; u++) {
          v0[u] = ld_relaxed4(gptr(xhi, b + at) - u * 2048); v1[u] = ld_relaxed4(gptr(xhi, b + at) + 512 - u * 2048);
          vm[u] = ld_relaxed2(gptr(xhi, b + ovm) - u * 2048);
        }
      }
      const bool odd = lv & 16;
      char* op = gptr(xhi, lds32(sb + CT_O) + (seg * SEG + WG * 16 + (lv >> 6)) * (HD * 2) + wq * 32 + (lv & 16) + ((lv >> 2) & 8));
      if (!staged || __builtin_expect(warp_incomplete(umax4(pt0.x, pt1.x, pm0, pm1)), 0)) {
        const uint32_t b = lds32(sb + CT_HEAD) + slot_off(seg);
        uint32_t tries = zr;
#pragma unroll 1
        do {
          pt0 = ld_relaxed4(gptr(xhi, b + ap)); pt1 = ld_relaxed4(gptr(xhi, b + ap) + 2048);
          pm0 = ld_relaxed1(gptr(xhi, b + am)); pm1 = ld_relaxed1(gptr(xhi, b + am) + 2048);
        } while (warp_incomplete(umax4(pt0.x, pt1.x, pm0, pm1)) && ++tries < POLL_LIMIT);
      }
      const uint32_t pa[4] = {pt0.x, pt1.x, pt0.y, pt1.y}, pb[4] = {pt0.z, pt1.z, pt0.w, pt1.w};
#pragma unroll
      for (int u = 0; u < NU; u++) {
        float o0[4] = {0.f, 0.f, 0.f, 0.f}, o1[4] = {0.f, 0.f, 0.f, 0.f};
        mma1688(o0, pm0, pm1, vm[u].x); mma1688(o1, pm0, pm1, vm[u].y);
        mma16816(o0, pa, v0[u].x, v0[u].y); mma16816(o1, pa, v1[u].x, v1[u].y);
        if (WG) { mma16816(o0, pb, v0[u].z, v0[u].w); mma16816(o1, pb, v1[u].z, v1[u].w); }
#pragma unroll
        for (int r = 0; r < 2; r++) {
          const uint32_t w0 = pack_bf16(o0[2 * r], o0[2 * r + 1]), w1 = pack_bf16(o1[2 * r], o1[2 * r + 1]);
          const uint32_t rv = __shfl_xor_sync(~0u, odd ? w0 : w1, 1);
          *(uint2*)(op + r * 8 * HD * 2 - u * 64) = odd ? make_uint2(rv, w1) : make_uint2(w0, rv);
        }
      }
    };
    if (!more) {
      named_bar(3, 256);
      if (upper_warps) {
#pragma unroll 1
        for (int seg = NSEG - 2; seg < NSEG; seg++) token_pv(seg, false);
      }
      break;
    }
    {
      if (__builtin_expect(s > 0, 1)) {
        const uint32_t o = WG ? ovt - 512 : tv + 512;
        const char* src = gptr(xhi, lds32(sb + CT_HEAD) + slot_off(sv - 1) + o);
#pragma unroll
        for (int i = 0; i < 3 - WG; i++) cp_async16(sb + OFF_MEM + o + i * 512, src + i * 512);
        cp_async_commit();
      }
      bool xw;
      {
        float acc[16];
        mbar_wait<0>(sb + BAR_X + 8 * WG, (s + 1) & 1);
        wg_fence();
#pragma unroll
        for (int ks = 0; ks < 16; ks++) wgmma_m64n32_rs(acc, rot[ks], xdesc<WG>(16 + ks), ks != 0);
        wg_commit();
#pragma unroll
        for (int ks = 0; ks < 16; ks++) wgmma_m64n32_rs(acc, aV[ks], xdesc<WG>(ks), 1);
        wg_commit();
        NEWZ(2);
        xw = warp_is(3) && s + 2 < NSEG;
        const uint32_t pvt = xvt + slot_off(sv + 1), awo = sb + wo_addr(tv);
        if (WG == 0 && warp_is(1) && s >= 0) expect_elect(sb + BAR_EX, 512);
        if (xw) {
          expect_elect(sb + BAR_X + 8 * WG, 32768);
          if (WG == 1 && s == NSEG - 3) asm volatile("griddepcontrol.launch_dependents;");
          if (WG == 1 && s + 5 < NSEG) prefetch_l2(maps.xp + (s + 5) * 65536 + lds32(sb + CT_PF), 1024);
        }
        wg_wait<1>();
        if (xw) { named_bar(4 + WG, 128); issue_x(sb, &maps.xq, s + 2, WG, 1); }
        else if (s + 2 < NSEG) named_bar_arrive(4 + WG, 128);
        if (__builtin_expect(s == 0, 0)) {
          mbar_wait(sb + BAR_P + 16, 0);
#pragma unroll
          for (int ks = 16 - O_FIX; ks < 16; ks++) ldsm_x4_t(bO[ks], (awo ^ 32) + (ks & 7) * 1024);
        }
#pragma unroll
        for (int ks = 0; ks < 16 - O_FIX; ks++) ldsm_x4_t(bO[ks], (ks < 8 ? awo : awo ^ 32) + (ks & 7) * 1024);
        wg_wait<0>();
        acc_fence(acc);
        constexpr int K = WG * 2, G = 2 - K;
        sts128f(sb + OFF_RED + WG * 1024 + t16, make_float4(acc[G], acc[G + 1], acc[4 + G], acc[5 + G]));
        sts128f(sb + OFF_RED + WG * 1024 + 512 + t16, make_float4(acc[8 + G], acc[9 + G], acc[12 + G], acc[13 + G]));
        cp_async_wait_group<0>();
        named_bar(3, 256);
        const float4 o0 = lds128f(sb + OFF_RED + (WG ^ 1) * 1024 + t16), o1 = lds128f(sb + OFF_RED + (WG ^ 1) * 1024 + 512 + t16);
        st_relaxed4(gptr(xhi, pvt),
                    pack_bf16(acc[K] + o0.x, acc[K + 1] + o0.y), pack_bf16(acc[4 + K] + o0.z, acc[5 + K] + o0.w),
                    pack_bf16(acc[8 + K] + o1.x, acc[9 + K] + o1.y), pack_bf16(acc[12 + K] + o1.z, acc[13 + K] + o1.w));
      }
      if (__builtin_expect(s >= 0, 1)) {
        uint32_t tries = 0;
#pragma unroll
        for (int ks = 0; ks < 16 - O_FIX; ks++) tries |= bO[ks][0];
        tries = __shfl_sync(0xffffffffu, tries & zr, 0);
        tref += lds32(sb + CT_T1) + (WG * T_LAG - T_SLIP);
        float d[2][2][4];
        uint32_t mx;
#pragma unroll 1
        do {
          NEWZ(5);
          const char* po = gptr(xhi, xom + slot_off(sv));
          tref += T_SLIP;
          WAIT_UNTIL(tref, aV[0], 1, 1);
          uint4 o[8];
#pragma unroll
          for (int i = 0; i < 4; i++) o[i] = ld_relaxed4(po + i * 512);
#pragma unroll
          for (int i = 0; i < 4; i++) o[4 + i] = ld_relaxed4(po + 16384 + i * 512);
          __syncwarp();
#pragma unroll
          for (int i = 0; i < 2; i++)
#pragma unroll
            for (int q = 0; q < 2; q++) { d[i][q][0] = d[i][q][1] = d[i][q][2] = d[i][q][3] = 0.f; }
#pragma unroll
          for (int i = 0; i < 4; i++) {
            mma16816(d[0][0], aO[2 * i], o[i].x, o[i].y); mma16816(d[1][0], aO[8 + 2 * i], o[i].x, o[i].y);
            mma16816(d[0][1], aO[2 * i + 1], o[i].z, o[i].w); mma16816(d[1][1], aO[9 + 2 * i], o[i].z, o[i].w);
          }
          mx = umax4(o[0].w, o[1].w, o[2].w, o[3].w);
          SFENCE(33 + tries);
#pragma unroll
          for (int i = 0; i < 4; i++) {
            mma16816(d[0][0], bO[2 * i], o[4 + i].x, o[4 + i].y); mma16816(d[1][0], bO[8 + 2 * i], o[4 + i].x, o[4 + i].y);
            mma16816(d[0][1], bO[2 * i + 1], o[4 + i].z, o[4 + i].w); mma16816(d[1][1], bO[9 + 2 * i], o[4 + i].z, o[4 + i].w);
          }
          mx = max(mx, umax4(o[4].w, o[5].w, o[6].w, o[7].w));
        } while (warp_incomplete(mx) && ++tries < POLL_LIMIT);
        NEWZ(3);
        const uint32_t rd = sb + OFF_RED + (WG ^ 1) * 1024 + t16;
        sts128f(rd, make_float4(d[0][0][0] + d[0][1][0], d[0][0][1] + d[0][1][1], d[0][0][2] + d[0][1][2], d[0][0][3] + d[0][1][3]));
        sts128f(rd + 512, make_float4(d[1][0][0] + d[1][1][0], d[1][0][1] + d[1][1][1], d[1][0][2] + d[1][1][2], d[1][0][3] + d[1][1][3]));
        if (upper_warps) {
          named_bar_arrive(7, 256);
          if (xw) issue_x(sb, &maps.xq, s + 2, WG, 0);
          if (__builtin_expect(s > 0, 1)) token_pv(sv - 1, true);
        } else {
          uint32_t mp = lds32(sb + CT_MP) + (lv >> 2);
          named_bar(7, 256);
          float4 p[8];
#pragma unroll
          for (int i = 0; i < 8; i++) p[i] = lds128f(sb + OFF_RED + lv + wq * 512 + i * 1024);
          float4 r;
          r.x = ((p[0].x + p[1].x) + (p[2].x + p[3].x)) + ((p[4].x + p[5].x) + (p[6].x + p[7].x));
          r.y = ((p[0].y + p[1].y) + (p[2].y + p[3].y)) + ((p[4].y + p[5].y) + (p[6].y + p[7].y));
          r.z = ((p[0].z + p[1].z) + (p[2].z + p[3].z)) + ((p[4].z + p[5].z) + (p[6].z + p[7].z));
          r.w = ((p[0].w + p[1].w) + (p[2].w + p[3].w)) + ((p[4].w + p[5].w) + (p[6].w + p[7].w));
          const bool w0 = warp_is(0);
          if (w0) st_async4(rsb + OFF_RX + lv, __float_as_uint(r.x), __float_as_uint(r.y), __float_as_uint(r.z), __float_as_uint(r.w), rsb + BAR_EX);
          if (!w0) {
            char* pp = gptr(xhi, mp + slot_off(sv + 1));
            mbar_wait(sb + BAR_EX, s & 1);
            const float4 q = lds128f(sb + OFF_RX + l16);
            st_relaxed1(pp, pack_bf16(r.x + q.x, r.y + q.y)); st_relaxed1(pp + 128, pack_bf16(r.z + q.z, r.w + q.w));
            pp = gptr(xhi, mp + slot_off(sv + 3));
            st_relaxed1(pp, EMPTY); st_relaxed1(pp + 128, EMPTY);
          }
        }
        NEWZ(4);
        const char* src = gptr(xhi, xm + WG * 8192 + slot_off(sv + 1));
        const uint32_t awv = sb + wv_addr(tv) + OFF_WVR;
        tref += lds32(sb + CT_T2) - WG * T_LAG;
        named_bar(8, 256);
#pragma unroll
        for (int ks = 0; ks < V_PRE; ks++) ldsm_x4_t(rot[ks], awv + ks * 2048);
        WAIT_UNTIL(tref, aV[0], 1, 2);
        gather_issue(sb + OFF_MEM + WG * 8192 + tv, src);
#pragma unroll
        for (int ks = V_PRE; ks < 16; ks++) ldsm_x4_t(rot[ks], awv + ks * 2048);
        NEWZ(6);
        st_relaxed4(gptr(xhi, xvt + slot_off(sv + 2)), EMPTY, EMPTY, EMPTY, EMPTY);
        if (WG == 0) st_relaxed2(gptr(xhi, xvm + slot_off(sv + 2)), EMPTY, EMPTY);
      } else {
        load_v(tv);
        if (xw) issue_x(sb, &maps.xq, s + 2, WG, 0);
        mbar_wait(sb + BAR_P + 8, 0);
#pragma unroll
        for (int ks = 0; ks < 8; ks++) { ldsm_x4_t(aO[ks], sb + wo_addr(tv) + ks * 1024); ldsm_x4_t(aO[8 + ks], sb + (wo_addr(tv) ^ 32) + ks * 1024); }
        named_bar(0, 256);
        if (threadIdx.x == 0) {
          fence_async_smem();
          mbar_expect_tx(sb + BAR_P + 16, 4 * 16384);
          for (int q = 0; q < 4; q++) tma_load_2d(sb + OFF_WOR + q * 16384, &maps.wo, h * 32, j * 2048 + 1024 + q * 256, sb + BAR_P + 16);
        }
        __syncwarp();
        tref = gtime() / T_SLIP * T_SLIP - T_SLIP;
      }
    }
  }
}

#undef j
#undef s
#undef sv
#undef xm
#undef wq

__global__ void __launch_bounds__(256, 1) __cluster_dims__(2, 1, 1)
chain_kernel(const __grid_constant__ ChainMaps maps, const bf16* __restrict__ mem0, const uint64_t xbase) {
  using namespace chain;
  extern __shared__ uint8_t smem_raw[];
  uint32_t sb = smem_u32(smem_raw);
  PIN(sb);
  if (sb != SB_LO + (blockIdx.x & 1) * RANK_BIT || mapa(sb, (blockIdx.x & 1) ^ 1) != (sb ^ RANK_BIT)) __trap();
  const int tid = threadIdx.x;
  const int h = blockIdx.x >> 2, role = (blockIdx.x >> 1) & 1, j = blockIdx.x & 1;
  if (tid == 0) {
    for (int i = 0; i < 9; i++) mbar_init(sb + OFF_BAR + 8 * i, 1);
    asm volatile("fence.mbarrier_init.release.cluster;" ::: "memory");
    const uint32_t xl = (uint32_t)xbase;
    sts32(sb + CT_BASE, xl); sts32(sb + CT_HEAD, xl + h * xo::HEAD); sts32(sb + CT_OM, xl + xo::OM + (role ? j * 32768 : h * 2048));
    sts32(sb + CT_MP, xl + xo::MEM + (h * 2 + j) * 256); sts32(sb + CT_O, xl + xo::O + (h * 2 + j) * 128); sts32(sb + CT_PF, (h * 2 + j) * 1024);
    sts32(sb + CT_T1, role ? maps.t_phase : maps.t_step); sts32(sb + CT_T2, maps.t_step - maps.t_phase);
    if (role == 0) {
      const CUtensorMap* wm = j ? &maps.wk : &maps.wq;
      mbar_expect_tx(sb + BAR_P, 6 * 16384);
      for (int c = 0; c < 3; c++)
        for (int q = 0; q < 2; q++) tma_load_2d(sb + OFF_X + (q * 3 + c) * 16384, wm, h * DH + q * 64, q * 512 + c * 128, sb + BAR_P);
      mbar_expect_tx(sb + BAR_P + 8, 4 * 16384);
      for (int c = 0; c < 2; c++)
        for (int q = 0; q < 2; q++) tma_load_2d(sb + OFF_X + (6 + q * 2 + c) * 16384, wm, h * DH + (q ^ 1) * 64, q * 512 + c * 128, sb + BAR_P + 8);
      mbar_expect_tx(sb + BAR_P + 24, 4 * 16384);
      for (int q = 0; q < 2; q++)
        for (int o = 0; o < 2; o++) tma_load_2d(sb + OFF_WS + (q * 2 + o) * 16384, wm, h * DH + (q ^ o) * 64, q * 512 + 384, sb + BAR_P + 24);
      for (int q = 0; q < 2; q++) tma_prefetch_2d(wm, h * DH + (q ^ 1) * 64, q * 512 + 256);
    } else {
      mbar_expect_tx(sb + BAR_P, 8 * 16384);
      for (int q = 0; q < 4; q++) tma_load_2d(sb + OFF_WOR + q * 16384, &maps.wv, h * DH + j * 64, (q >> 1) * 512 + (q & 1) * 128, sb + BAR_P);
      for (int q = 0; q < 4; q++) tma_load_2d(sb + OFF_WVR + q * 16384, &maps.wv, h * DH + j * 64, (q >> 1) * 512 + 256 + (q & 1) * 128, sb + BAR_P);
    }
  }
  for (int r = 0; r < RING; r++) {
    char* p = (char*)xbase + r * xo::SLOT;
    const int wq = (tid >> 5) & 3;
    if (role == 1) st_relaxed4(p + h * xo::HEAD + xo::VT + (8 * j + 2 * wq + (tid >> 7)) * 512 + (tid & 31) * 16, EMPTY, EMPTY, EMPTY, EMPTY);
    else if (j == 0) st_relaxed4(p + (tid < 128 ? xo::OM + h * 2048 + tid * 16 : h * xo::HEAD + wq * 2048 + xo::VM + (tid & 31) * 16), EMPTY, EMPTY, EMPTY, EMPTY);
    else {
      st_relaxed4(p + h * xo::HEAD + (tid >> 6) * 2048 + 1024 + (tid & 63) * 16, EMPTY, EMPTY, EMPTY, EMPTY);
      if (tid < 32) st_relaxed4(p + xo::MEM + h * 512 + tid * 16, EMPTY, EMPTY, EMPTY, EMPTY);
    }
  }
  __syncthreads();
  if (tid == 0) {
    __threadfence();
    const uint32_t target = (atomicAdd(&g_epoch, 1u) & ~127u) + 128u;
    uint32_t v; int guard = 0;
    do { asm volatile("ld.acquire.gpu.global.u32 %0, [%1];" : "=r"(v) : "l"(&g_epoch) : "memory"); } while ((int)(v - target) < 0 && ++guard < (1 << 20));
  }
  __syncwarp();
  const uint32_t xhi = (uint32_t)(xbase >> 32);
  const int wg = __shfl_sync(0xffffffffu, tid >> 7, 0);
  if (role == 0) {
    if (wg == 0) role_a<0>(maps, mem0, sb, xhi); else role_a<1>(maps, mem0, sb, xhi);
  } else {
    if (wg == 0) role_v<0>(maps, mem0, sb, xhi); else role_v<1>(maps, mem0, sb, xhi);
  }
  __syncwarp();
  cluster_arrive();
  cluster_wait();
}

struct BMaps {
  CUtensorMap q, k, v, out, k8;
  const bf16 *shift_k, *ssm_k, *ssm_D;
};

#define B_SLEEP 200
namespace bp {
constexpr int U_PITCH = (2048 + 128) * 2 + 16;
constexpr int KR_WORDS = 1048;
constexpr int KR_PITCH = 8704;
constexpr int OFF_U = 0;
constexpr int OFF_KR = (8 * U_PITCH + 127) / 128 * 128;
constexpr int Q_OFF = 4352;
constexpr int OFF_BAR = OFF_KR + 8 * KR_PITCH;
constexpr int GROUP_BYTES = OFF_BAR + 128;
constexpr int SMEM = 2 * GROUP_BYTES + 128;
constexpr int NTASK = DM / 8;
static_assert(Q_OFF >= 4224 && Q_OFF + 4096 <= KR_PITCH, "staging does not fit");
}

__device__ __forceinline__ uint32_t bmul2(uint32_t a, uint32_t b) { uint32_t r; asm("mul.rn.bf16x2 %0, %1, %2;" : "=r"(r) : "r"(a), "r"(b)); return r; }
__device__ __forceinline__ uint32_t badd2(uint32_t a, uint32_t b) { uint32_t r; asm("add.rn.bf16x2 %0, %1, %2;" : "=r"(r) : "r"(a), "r"(b)); return r; }
__device__ __forceinline__ void stsm_x4_t(uint32_t addr, uint32_t r0, uint32_t r1, uint32_t r2, uint32_t r3) {
  asm volatile("stmatrix.sync.aligned.m8n8.x4.trans.shared.b16 [%0], {%1,%2,%3,%4};" ::"r"(addr), "r"(r0), "r"(r1), "r"(r2), "r"(r3) : "memory");
}

__device__ __forceinline__ void mbar_wait_sleep(uint32_t bar, uint32_t parity) {
  int guard = 0;
  while (!mbar_try(bar, parity)) { __nanosleep(B_SLEEP); if (++guard > (1 << 22)) __trap(); }
}

__device__ __forceinline__ void bpart_body(const BMaps& maps, int first, int stride, int end) {
  using namespace bp;
  extern __shared__ uint8_t smem_all[];
  const int grp = __shfl_sync(0xffffffffu, threadIdx.x >> 8, 0);
  const int lane = keep(threadIdx.x & 31), g = lane >> 2, t = lane & 3;
  const int w = __shfl_sync(0xffffffffu, (threadIdx.x >> 5) & 7, 0);
  const uint32_t sb = ((smem_u32(smem_all) + 127) & ~127u) + grp * GROUP_BYTES;
  const uint32_t kr = sb + OFF_KR + w * KR_PITCH, bar_k = sb + OFF_BAR + 8 * w, bar_q = bar_k + 64;
  if (lane == 0) { mbar_init(bar_k, 1); mbar_init(bar_q, 1); asm volatile("fence.mbarrier_init.release.cluster;" ::: "memory"); }
  if (lane < 16) sts128(sb + OFF_U + w * U_PITCH + lane * 16, make_uint4(0, 0, 0, 0));
  __syncwarp();
  if (grp == 1) { named_bar_arrive(3, 512); named_bar(5, 512); }
  const int lm = lane >> 3, lr = lane & 7;
  uint32_t ph = 0;
  for (int task = first + grp; task < end; task += stride, ph ^= 1) {
    const int d0 = task * 8;
    uint4 x[8];
    {
      const uint4* kf = (const uint4*)(maps.ssm_k + (size_t)(d0 + w) * S_LEN);
#pragma unroll
      for (int it = 0; it < 8; it++) x[it] = __ldg(kf + it * 32 + lane);
    }
    const uint4 ska = __ldg((const uint4*)(maps.shift_k + (d0 + 2 * t) * 4));
    __syncwarp();
    if (lane == 0) {
      mbar_expect_tx(bar_k, 2 * 4096 + 128);
      tma_load_2d(kr + 4096, &maps.k8, d0, w * 256 + 248, bar_k);
      tma_load_2d(kr, &maps.k, d0, w * 256 - 8, bar_k);
      bulk_wait_read<0>();
      tma_load_2d(kr + Q_OFF, &maps.v, d0, w * 256, bar_k);
    }
    __syncwarp();
    if (task == first) named_bar_arrive(5, 512);
    const uint32_t sk[4] = {__byte_perm(ska.x, ska.z, 0x5410), __byte_perm(ska.x, ska.z, 0x7632), __byte_perm(ska.y, ska.w, 0x5410), __byte_perm(ska.y, ska.w, 0x7632)};
    mbar_wait_sleep(bar_k, ph);
    {
      const uint32_t ka = kr + (lane + 8) * 16;
#pragma unroll
      for (int i = 0; i < 8; i++) {
        uint32_t k0[4], k1[4], k2[4], k3[4], v[4], r[4];
        ldsm_x4(k3, ka + i * 512 - 48); ldsm_x4(k2, ka + i * 512 - 32); ldsm_x4(k1, ka + i * 512 - 16); ldsm_x4(k0, ka + i * 512);
        ldsm_x4(v, ka + (Q_OFF - 128) + i * 512);
#pragma unroll
        for (int b = 0; b < 4; b++) {
          uint32_t acc = bmul2(k3[b], sk[3]);
          acc = badd2(acc, bmul2(k2[b], sk[2]));
          acc = badd2(acc, bmul2(k1[b], sk[1]));
          acc = badd2(acc, bmul2(k0[b], sk[0]));
          r[b] = bmul2(acc, v[b]);
        }
        const int ch = 16 + w * 32 + i * 4 + lm;
        stsm_x4_t(sb + OFF_U + lr * U_PITCH + ((ch ^ ((ch >> 3) & 1)) << 4), r[0], r[1], r[2], r[3]);
      }
    }
    __syncwarp();
    {
      const uint32_t c0 = kr, c1 = c0 + (KR_WORDS + 16) * 4;
      uint32_t carry = 0;
#pragma unroll
      for (int it = 0; it < 8; it++) {
        const int blk = it * 32 + lane;
        uint32_t prev = __shfl_up_sync(0xffffffffu, x[it].w, 1);
        if (lane == 0) prev = carry;
        carry = __shfl_sync(0xffffffffu, x[it].w, 31);
        sts128(c0 + (1028 - 4 * blk) * 4, make_uint4(__byte_perm(x[it].w, 0, 0x1032), __byte_perm(x[it].z, 0, 0x1032),
                                                     __byte_perm(x[it].y, 0, 0x1032), __byte_perm(x[it].x, 0, 0x1032)));
        sts128(c1 + (1028 - 4 * blk) * 4, make_uint4(__byte_perm(x[it].w, x[it].z, 0x7610), __byte_perm(x[it].z, x[it].y, 0x7610),
                                                     __byte_perm(x[it].y, x[it].x, 0x7610), __byte_perm(x[it].x, prev, 0x7610)));
      }
      if (lane < 4) { sts128(c0 + (1032 + 4 * lane) * 4, make_uint4(0, 0, 0, 0)); sts128(c1 + (1032 + 4 * lane) * 4, make_uint4(0, 0, 0, 0)); }
      __syncwarp();
    }
    named_bar(3 + grp, 512);
    float acc[16][4];
#pragma unroll
    for (int jn = 0; jn < 16; jn++) { acc[jn][0] = acc[jn][1] = acc[jn][2] = acc[jn][3] = 0.f; }
    {
      const uint32_t ub = sb + OFF_U + w * U_PITCH;
      uint32_t kd = kr + (((g & 1) ? 0 : KR_WORDS + 16) + ((((g & 1) ? 2063 : 2062) - (g - 2 * t)) >> 1)) * 4;
      uint32_t uc = 2 * (8 + lr + (lm >> 1) * 8) + (lm & 1);
#pragma unroll 1
      for (int d0s = 0; d0s < 8; d0s++, kd -= 32, uc -= 2) {
        const uint32_t uf = ub + ((uc ^ ((uc >> 3) & 1)) << 4);
        uint32_t A[3][4];
        A[0][0] = lds32v(kd); A[0][1] = lds32v(kd - 16); A[0][2] = lds32v(kd + 16); A[0][3] = lds32v(kd);
        uint32_t F[8][4];
#pragma unroll
        for (int m = 7; m >= 0; m--) ldsm_x4(F[m], uf + m * 512);
#pragma unroll
        for (int i = 0; i < 16; i++) {
          if (i + 1 < 16) {
            A[(i + 1) % 3][0] = lds32v(kd - 256 * (i + 1)); A[(i + 1) % 3][1] = lds32v(kd - 256 * (i + 1) - 16);
            A[(i + 1) % 3][2] = lds32v(kd - 256 * (i + 1) + 16); A[(i + 1) % 3][3] = lds32v(kd - 256 * (i + 1));
          }
#pragma unroll
          for (int jn = 15; jn >= i; jn--) mma16816(acc[jn], A[i % 3], F[(jn - i) >> 1][((jn - i) & 1) * 2], F[(jn - i) >> 1][((jn - i) & 1) * 2 + 1]);
        }
      }
    }
    named_bar_arrive(3 + (grp ^ 1), 512);
    __syncwarp();
    fence_async_smem();
    __syncwarp();
    if (lane == 0) { mbar_expect_tx(bar_q, 4096); tma_load_2d(kr + Q_OFF, &maps.q, d0, w * 256, bar_q); }
    const uint32_t dpair = __ldg((const uint32_t*)(maps.ssm_D + d0) + t);
    {
      const uint32_t ya = kr + w * 16 + (((lm >> 1) * 8 + lr) * 32) + (lm & 1) * 16;
#pragma unroll
      for (int jn = 0; jn < 16; jn += 2)
        stsm_x4_t(ya + jn * 256, pack_bf16(acc[jn][0], acc[jn][1]), pack_bf16(acc[jn][2], acc[jn][3]),
                  pack_bf16(acc[jn + 1][0], acc[jn + 1][1]), pack_bf16(acc[jn + 1][2], acc[jn + 1][3]));
    }
    named_bar(1 + grp, 256);
    mbar_wait_sleep(bar_q, ph);
    {
      const uint32_t ya = sb + OFF_KR + lr * (KR_PITCH + 16) + (w * 256 + lm * 8) * 2;
#pragma unroll
      for (int i = 0; i < 8; i++) {
        uint32_t y[4], u[4], q[4], r[4];
        ldsm_x4(q, kr + Q_OFF + lane * 16 + i * 512);
        ldsm_x4_t(y, ya + i * 64);
        const int ch = 16 + w * 32 + i * 4 + lm;
        ldsm_x4_t(u, sb + OFF_U + lr * U_PITCH + ((ch ^ ((ch >> 3) & 1)) << 4));
#pragma unroll
        for (int b = 0; b < 4; b++) r[b] = bmul2(q[b], badd2(y[b], bmul2(u[b], dpair)));
        stsm_x4(kr + Q_OFF + lane * 16 + i * 512, r[0], r[1], r[2], r[3]);
      }
      fence_async_smem();
      __syncwarp();
      if (lane == 0) { tma_store_2d(&maps.out, kr + Q_OFF, DM + d0, w * 256); bulk_commit(); }
    }
    named_bar(1 + grp, 256);
  }
  if (lane == 0) bulk_wait<0>();
}

__global__ void __launch_bounds__(512, 1) __cluster_dims__(2, 1, 1) bpart_kernel(const __grid_constant__ BMaps maps, int end) {
  bpart_body(maps, blockIdx.x * 2, gridDim.x * 2, end);
}

struct GemmMaps {
  CUtensorMap o;
  CUtensorMap w;
  CUtensorMap c;
};
namespace k3 {
constexpr int STAGES = 6;
constexpr int W_BYTES = 2 * 8192, O_BYTES = K3_N * 128, STAGE_BYTES = W_BYTES + O_BYTES;
constexpr int TT = (S_LEN + K3_N - 1) / K3_N, NGEMM = TT * (DM / 128), NB = 128 - NGEMM, KSTEPS = HD / 64;
constexpr int SMEM_G = STAGES * STAGE_BYTES + 1024 + 256;
constexpr int SMEM = SMEM_G > bp::SMEM ? SMEM_G : bp::SMEM;
static_assert(STAGE_BYTES % 1024 == 0, "swizzle atoms");
}

__global__ void __launch_bounds__(512, 1)
tail_kernel(const __grid_constant__ GemmMaps maps, const __grid_constant__ BMaps bmaps) {
  using namespace k3;
  if (blockIdx.x < NB) {
    bpart_body(bmaps, bp::NTASK - 2 * NB + 2 * blockIdx.x, bp::NTASK, bp::NTASK);
    return;
  }
  extern __shared__ uint8_t smem_raw[];
  const uint32_t sbase = (smem_u32(smem_raw) + 1023) & ~1023u;
  const uint32_t bars = sbase + STAGES * STAGE_BYTES;
  const int tid = threadIdx.x, warp = tid >> 5;
  const int tt = (blockIdx.x - NB) / 8, ct = (blockIdx.x - NB) % 8;

  if (tid == 0) {
    for (int s = 0; s < STAGES; s++) { mbar_init(bars + 8 * s, 1); mbar_init(bars + 8 * (STAGES + s), 2); }
    asm volatile("fence.mbarrier_init.release.cluster;" ::: "memory");
  }
  __syncthreads();

  if (warp >= 8) {
    if (tid == 256) {
      tma_prefetch_desc(&maps.o);
      for (int k = 0; k < STAGES; k++) {
        const uint32_t full = bars + 8 * k, sa = sbase + k * STAGE_BYTES;
        mbar_expect_tx(full, STAGE_BYTES);
#pragma unroll
        for (int j = 0; j < 2; j++) tma_load_2d(sa + j * 8192, &maps.w, ct * 128 + j * 64, k * 64, full);
      }
      asm volatile("griddepcontrol.wait;" ::: "memory");
      int stage = 0; uint32_t ph = 1;
      for (int k = 0; k < KSTEPS; k++) {
        mbar_wait(bars + 8 * (STAGES + stage), ph);
        const uint32_t full = bars + 8 * stage, sa = sbase + stage * STAGE_BYTES;
        const bool pre = k < STAGES;
        if (!pre) mbar_expect_tx(full, STAGE_BYTES);
        tma_load_2d(sa + W_BYTES, &maps.o, k * 64, tt * K3_N, full);
        if (!pre) {
#pragma unroll
          for (int j = 0; j < 2; j++) tma_load_2d(sa + j * 8192, &maps.w, ct * 128 + j * 64, k * 64, full);
        }
        if (++stage == STAGES) { stage = 0; ph ^= 1; }
      }
    }
  } else {
    const int wg = warp >> 2, lane = tid & 31, wq = warp & 3;
    int stage = 0; uint32_t ph = 0;
    float acc[K3_N / 2];
    int prev = -1;
    for (int k = 0; k < KSTEPS; k++) {
      mbar_wait(bars + 8 * stage, ph);
      const uint32_t sa = sbase + stage * STAGE_BYTES;
      wg_fence();
#pragma unroll
      for (int kk = 0; kk < 4; kk++) {
        const uint64_t da = make_desc(sa + wg * 8192 + kk * 2048, 16, 1024, 1);
        const uint64_t db = make_desc(sa + W_BYTES + kk * 32, 16, 1024, 1);
        wgmma_k3_ss_ta(acc, da, db, (k | kk) != 0);
      }
      wg_commit();
      if (prev >= 0) { wg_wait<1>(); if ((tid & 127) == 0) mbar_arrive(bars + 8 * (STAGES + prev)); }
      prev = stage;
      if (++stage == STAGES) { stage = 0; ph ^= 1; }
    }
    wg_wait<0>();
#pragma unroll
    for (int i = 0; i < K3_N / 2; i++) asm volatile("" : "+f"(acc[i]) :: "memory");
    named_bar(1, 256);
    const uint32_t ebuf = sbase + wg * STAGE_BYTES;
    const uint32_t ea = ebuf + ((lane >> 4) * 8 + (lane & 7)) * 128 + (((2 * wq + ((lane >> 3) & 1)) ^ (lane & 7)) << 4);
#pragma unroll
    for (int i = 0; i < K3_N / 8; i += 2) {
      const int i1 = i + 1 < K3_N / 8 ? i + 1 : i;
      stsm_x4_t(ea + i * 1024, pack_bf16(acc[4 * i], acc[4 * i + 1]), pack_bf16(acc[4 * i + 2], acc[4 * i + 3]),
                pack_bf16(acc[4 * i1], acc[4 * i1 + 1]), pack_bf16(acc[4 * i1 + 2], acc[4 * i1 + 3]));
    }
    fence_async_smem();
    named_bar(2 + wg, 128);
    if ((tid & 127) == 0) {
      tma_store_2d(&maps.c, ebuf, ct * 128 + wg * 64, tt * K3_N);
      bulk_commit();
      bulk_wait<0>();
    }
  }
}

typedef CUresult (*EncodeFn)(CUtensorMap*, CUtensorMapDataType, cuuint32_t, void*, const cuuint64_t*, const cuuint64_t*,
                             const cuuint32_t*, const cuuint32_t*, CUtensorMapInterleave, CUtensorMapSwizzle,
                             CUtensorMapL2promotion, CUtensorMapFloatOOBfill);

void make_map(EncodeFn enc, CUtensorMap* m, const void* ptr, uint64_t cols, uint64_t rows, uint64_t pitch_elems,
              uint32_t box_cols, uint32_t box_rows, CUtensorMapSwizzle swz,
              CUtensorMapL2promotion promo = CU_TENSOR_MAP_L2_PROMOTION_L2_128B) {
  cuuint64_t dims[2] = {cols, rows};
  cuuint64_t strides[1] = {pitch_elems * 2};
  cuuint32_t box[2] = {box_cols, box_rows};
  cuuint32_t es[2] = {1, 1};
  enc(m, CU_TENSOR_MAP_DATA_TYPE_BFLOAT16, 2, const_cast<void*>(ptr), dims, strides, box, es, CU_TENSOR_MAP_INTERLEAVE_NONE, swz,
      promo, CU_TENSOR_MAP_FLOAT_OOB_FILL_NONE);
}

void make_map_nd(EncodeFn enc, CUtensorMap* m, const void* ptr, int rank, const uint64_t* dims, const uint64_t* strides_elems,
                 const uint32_t* box, CUtensorMapSwizzle swz) {
  cuuint64_t d[5], st[4]; cuuint32_t b[5], es[5];
  for (int i = 0; i < rank; i++) { d[i] = dims[i]; b[i] = box[i]; es[i] = 1; if (i) st[i - 1] = strides_elems[i] * 2; }
  enc(m, CU_TENSOR_MAP_DATA_TYPE_BFLOAT16, rank, const_cast<void*>(ptr), d, st, b, es, CU_TENSOR_MAP_INTERLEAVE_NONE, swz,
      CU_TENSOR_MAP_L2_PROMOTION_L2_128B, CU_TENSOR_MAP_FLOAT_OOB_FILL_NONE);
}

}

extern "C" void kernel_launch(void* const* d_in, const int* in_sizes, int n_in, void* d_out, int out_size) {
  (void)in_sizes; (void)n_in; (void)out_size;
  const bf16* x = (const bf16*)d_in[0];
  const bf16* mem0 = (const bf16*)d_in[1];
  const bf16* Wq = (const bf16*)d_in[2];
  const bf16* Wk = (const bf16*)d_in[3];
  const bf16* Wv = (const bf16*)d_in[4];
  const bf16* Wo = (const bf16*)d_in[5];
  const bf16* Bq = (const bf16*)d_in[7];
  const bf16* Bk = (const bf16*)d_in[8];
  const bf16* Bv = (const bf16*)d_in[9];
  const bf16* shift_k = (const bf16*)d_in[10];
  const bf16* ssm_k = (const bf16*)d_in[11];
  const bf16* ssm_D = (const bf16*)d_in[12];
  bf16* out = (bf16*)d_out;

  static EncodeFn enc = nullptr;
  static uint64_t xbase;
  static int nsm = 132;
  static cudaStream_t s1;
  static cudaEvent_t ev_fork, ev_join;
  if (!enc) {
    cudaDriverEntryPointQueryResult qr;
    void* fn = nullptr;
    cudaGetDriverEntryPoint("cuTensorMapEncodeTiled", &fn, cudaEnableDefault, &qr);
    enc = (EncodeFn)fn;
    void* ps = nullptr;
    cudaGetSymbolAddress(&ps, g_scratch);
    xbase = (uint64_t)ps;
    if ((xbase >> 32) != ((xbase + xo::BYTES - 1) >> 32)) xbase += xo::BYTES;
    cudaFuncSetAttribute(tail_kernel, cudaFuncAttributeMaxDynamicSharedMemorySize, k3::SMEM);
    cudaFuncSetAttribute(chain_kernel, cudaFuncAttributeMaxDynamicSharedMemorySize, chain::SMEM);
    cudaFuncSetAttribute(bpart_kernel, cudaFuncAttributeMaxDynamicSharedMemorySize, bp::SMEM);
    cudaStreamCreateWithFlags(&s1, cudaStreamNonBlocking);
    cudaEventCreateWithFlags(&ev_fork, cudaEventDisableTiming);
    cudaEventCreateWithFlags(&ev_join, cudaEventDisableTiming);
    int dev = 0; cudaGetDevice(&dev);
    cudaDeviceGetAttribute(&nsm, cudaDevAttrMultiProcessorCount, dev);
  }
  const CUtensorMapSwizzle SW128 = CU_TENSOR_MAP_SWIZZLE_128B, SW64 = CU_TENSOR_MAP_SWIZZLE_64B;
  GemmMaps m3; ChainMaps mc;
  make_map(enc, &m3.o, (void*)(xbase + xo::O), HD, S_LEN, HD, 64, K3_N, SW128);
  make_map(enc, &m3.w, Wo, DM, HD, DM, 64, 64, SW128);
  make_map(enc, &m3.c, out, DM, S_LEN, OUT_LD, 64, K3_N, SW128);
  const CUtensorMapL2promotion P256 = CU_TENSOR_MAP_L2_PROMOTION_L2_256B;
  make_map(enc, &mc.wq, Wq, HD, DM, HD, 64, 128, SW128, P256);
  make_map(enc, &mc.wk, Wk, HD, DM, HD, 64, 128, SW128, P256);
  make_map(enc, &mc.wv, Wv, HD, DM, HD, 64, 128, SW128, P256);
  make_map(enc, &mc.wo, Wo, DM, HD, DM, 32, 256, SW64, P256);
  {
    const uint64_t dx[3] = {64, S_LEN, DM / 64}, sx[3] = {1, DM, 64};
    const uint32_t bx[3] = {64, SEG, 8};
    make_map_nd(enc, &mc.x, x, 3, dx, sx, bx, SW128);
    const uint32_t bq[3] = {64, SEG, 4};
    make_map_nd(enc, &mc.xq, x, 3, dx, sx, bq, SW128);
    mc.xp = (const char*)x;
  }

  const int skip = 0;
  mc.t_step = T_STEP; mc.t_phase = T_PHASE;
  BMaps mb;
  const CUtensorMapSwizzle SWN = CU_TENSOR_MAP_SWIZZLE_NONE;
  make_map(enc, &mb.k, Bk, DM, S_LEN, DM, 8, 256, SWN);
  make_map(enc, &mb.q, Bq, DM, S_LEN, DM, 8, 256, SWN);
  make_map(enc, &mb.v, Bv, DM, S_LEN, DM, 8, 256, SWN);
  mb.shift_k = shift_k; mb.ssm_k = ssm_k; mb.ssm_D = ssm_D;
  make_map(enc, &mb.out, out, OUT_LD, S_LEN, OUT_LD, 8, 256, SWN);
  make_map(enc, &mb.k8, Bk, DM, S_LEN, DM, 8, 8, SWN);
  cudaStream_t s0 = cudaStreamPerThread;
  const int nb = nsm >= 132 ? 4 : 2, ntask1 = bp::NTASK - 2 * k3::NB;
  const bool fork = nsm >= 130 && !(skip & 16);
  if (fork) {
    cudaEventRecord(ev_fork, s0);
    cudaStreamWaitEvent(s1, ev_fork, 0);
    if (!(skip & 1)) bpart_kernel<<<nb, 512, bp::SMEM, s1>>>(mb, ntask1);
    cudaEventRecord(ev_join, s1);
  } else if (!(skip & 1)) {
    bpart_kernel<<<ntask1 / 2, 512, bp::SMEM, s0>>>(mb, ntask1);
  }
  if (!(skip & 4)) chain_kernel<<<128, 256, chain::SMEM, s0>>>(mc, mem0, xbase);
  if (!(skip & 8)) {
    cudaLaunchAttribute pdl[1];
    pdl[0].id = cudaLaunchAttributeProgrammaticStreamSerialization;
    pdl[0].val.programmaticStreamSerializationAllowed = 1;
    cudaLaunchConfig_t cfg = {};
    cfg.gridDim = dim3(128); cfg.blockDim = dim3(512); cfg.dynamicSmemBytes = k3::SMEM; cfg.stream = s0;
    cfg.attrs = pdl; cfg.numAttrs = 1;
    cudaLaunchKernelEx(&cfg, tail_kernel, m3, mb);
  }
  if (fork) cudaStreamWaitEvent(s0, ev_join, 0);
}
```

```cpp
#include <cuda_runtime.h>
#include <cuda_bf16.h>
#include <cuda.h>
#include <stdint.h>

namespace {

constexpr int S_LEN = 2048;
constexpr int DM = 1024;
constexpr int NH = 32;
constexpr int DH = 128;
constexpr int HD = NH * DH;
constexpr int SEG = 32;
constexpr int NSEG = S_LEN / SEG;
constexpr int OUT_LD = 2048;

typedef __nv_bfloat16 bf16;
#define K3_N 160

__device__ __forceinline__ uint32_t smem_u32(const void* p) { return (uint32_t)__cvta_generic_to_shared(p); }

__device__ __forceinline__ void mbar_init(uint32_t bar, uint32_t count) {
  asm volatile("mbarrier.init.shared::cta.b64 [%0], %1;" ::"r"(bar), "r"(count) : "memory");
}
__device__ __forceinline__ void mbar_expect_tx(uint32_t bar, uint32_t bytes) {
  asm volatile("mbarrier.arrive.expect_tx.shared::cta.b64 _, [%0], %1;" ::"r"(bar), "r"(bytes) : "memory");
}
__device__ __forceinline__ void mbar_arrive(uint32_t bar) {
  asm volatile("mbarrier.arrive.shared::cta.b64 _, [%0];" ::"r"(bar) : "memory");
}
__device__ __forceinline__ bool mbar_try(uint32_t bar, uint32_t parity) {
  uint32_t ok;
  asm volatile("{.reg .pred p; mbarrier.try_wait.parity.shared::cta.b64 p, [%1], %2; selp.u32 %0, 1, 0, p;}"
               : "=r"(ok) : "r"(bar), "r"(parity) : "memory");
  return ok;
}
__device__ __forceinline__ bool mbar_test(uint32_t bar, uint32_t parity) {
  uint32_t ok;
  asm volatile("{.reg .pred p; mbarrier.test_wait.parity.shared::cta.b64 p, [%1], %2; selp.u32 %0, 1, 0, p;}"
               : "=r"(ok) : "r"(bar), "r"(parity) : "memory");
  return ok;
}
template <int HINT = 1>
__device__ __forceinline__ void mbar_wait(uint32_t bar, uint32_t parity) {
  int guard = 0;
  while (__builtin_expect(!mbar_try(bar, parity), HINT)) { if (++guard > (1 << 22)) __trap(); }
}
__device__ __forceinline__ void tma_load_2d(uint32_t dst, const CUtensorMap* map, int c0, int c1, uint32_t bar) {
  asm volatile("cp.async.bulk.tensor.2d.shared::cluster.global.mbarrier::complete_tx::bytes [%0], [%1, {%3, %4}], [%2];"
               ::"r"(dst), "l"(map), "r"(bar), "r"(c0), "r"(c1) : "memory");
}
__device__ __forceinline__ void tma_load_3d(uint32_t dst, const CUtensorMap* map, int c0, int c1, int c2, uint32_t bar) {
  asm volatile("cp.async.bulk.tensor.3d.shared::cluster.global.mbarrier::complete_tx::bytes [%0], [%1, {%3, %4, %5}], [%2];"
               ::"r"(dst), "l"(map), "r"(bar), "r"(c0), "r"(c1), "r"(c2) : "memory");
}
__device__ __forceinline__ void tma_load_4d(uint32_t dst, const CUtensorMap* map, int c0, int c1, int c2, int c3, uint32_t bar) {
  asm volatile("cp.async.bulk.tensor.4d.shared::cluster.global.mbarrier::complete_tx::bytes [%0], [%1, {%3, %4, %5, %6}], [%2];"
               ::"r"(dst), "l"(map), "r"(bar), "r"(c0), "r"(c1), "r"(c2), "r"(c3) : "memory");
}
__device__ __forceinline__ void tma_store_2d(const CUtensorMap* map, uint32_t src, int c0, int c1) {
  asm volatile("cp.async.bulk.tensor.2d.global.shared::cta.bulk_group [%0, {%2, %3}], [%1];"
               ::"l"(map), "r"(src), "r"(c0), "r"(c1) : "memory");
}
__device__ __forceinline__ void tma_prefetch_2d(const CUtensorMap* map, int c0, int c1) {
  asm volatile("cp.async.bulk.prefetch.tensor.2d.L2.global [%0, {%1, %2}];" ::"l"(map), "r"(c0), "r"(c1) : "memory");
}
__device__ __forceinline__ void tma_prefetch_desc(const CUtensorMap* map) {
  asm volatile("prefetch.tensormap [%0];" ::"l"(map) : "memory");
}
__device__ __forceinline__ void fence_async_smem() { asm volatile("fence.proxy.async.shared::cta;" ::: "memory"); }
__device__ __forceinline__ void bulk_commit() { asm volatile("cp.async.bulk.commit_group;" ::: "memory"); }
template <int N> __device__ __forceinline__ void bulk_wait_read() { asm volatile("cp.async.bulk.wait_group.read %0;" ::"n"(N) : "memory"); }
template <int N> __device__ __forceinline__ void bulk_wait() { asm volatile("cp.async.bulk.wait_group %0;" ::"n"(N) : "memory"); }
__device__ __forceinline__ void named_bar(int id, int n) { asm volatile("bar.sync %0, %1;" ::"r"(id), "r"(n) : "memory"); }

__device__ __forceinline__ void named_bar_arrive(int id, int n) { asm volatile("bar.arrive %0, %1;" ::"r"(id), "r"(n) : "memory"); }
__device__ __forceinline__ float ex2(float x) { float y; asm("ex2.approx.ftz.f32 %0, %1;" : "=f"(y) : "f"(x)); return y; }
__device__ __forceinline__ float rcp(float x) { float y; asm("rcp.approx.ftz.f32 %0, %1;" : "=f"(y) : "f"(x)); return y; }

__device__ __forceinline__ void sts32(uint32_t a, uint32_t x) { asm volatile("st.shared.b32 [%0], %1;" ::"r"(a), "r"(x) : "memory"); }
__device__ __forceinline__ uint32_t lds32(uint32_t a) { uint32_t x; asm volatile("ld.shared.b32 %0, [%1];" : "=r"(x) : "r"(a) : "memory"); return x; }
__device__ __forceinline__ uint32_t lds32v(uint32_t a) { uint32_t x; asm volatile("ld.volatile.shared.b32 %0, [%1];" : "=r"(x) : "r"(a) : "memory"); return x; }
__device__ __forceinline__ void sts128(uint32_t a, const uint4& v) { asm volatile("st.shared.v4.b32 [%0], {%1,%2,%3,%4};" ::"r"(a), "r"(v.x), "r"(v.y), "r"(v.z), "r"(v.w) : "memory"); }
__device__ __forceinline__ void sts128f(uint32_t a, const float4& v) { asm volatile("st.shared.v4.f32 [%0], {%1,%2,%3,%4};" ::"r"(a), "f"(v.x), "f"(v.y), "f"(v.z), "f"(v.w) : "memory"); }
__device__ __forceinline__ uint4 lds128(uint32_t a) { uint4 v; asm volatile("ld.shared.v4.b32 {%0,%1,%2,%3}, [%4];" : "=r"(v.x), "=r"(v.y), "=r"(v.z), "=r"(v.w) : "r"(a) : "memory"); return v; }
__device__ __forceinline__ float4 lds128f(uint32_t a) { float4 v; asm volatile("ld.shared.v4.f32 {%0,%1,%2,%3}, [%4];" : "=f"(v.x), "=f"(v.y), "=f"(v.z), "=f"(v.w) : "r"(a) : "memory"); return v; }

__device__ __forceinline__ void cp_async16(uint32_t dst, const void* src) { asm volatile("cp.async.cg.shared.global [%0], [%1], 16;" ::"r"(dst), "l"(src) : "memory"); }
__device__ __forceinline__ void cp_async_commit() { asm volatile("cp.async.commit_group;" ::: "memory"); }
template <int N> __device__ __forceinline__ void cp_async_wait_group() { asm volatile("cp.async.wait_group %0;" ::"n"(N) : "memory"); }

__device__ __forceinline__ void wg_fence() { asm volatile("wgmma.fence.sync.aligned;" ::: "memory"); }
__device__ __forceinline__ void wg_commit() { asm volatile("wgmma.commit_group.sync.aligned;" ::: "memory"); }
template <int N> __device__ __forceinline__ void wg_wait() { asm volatile("wgmma.wait_group.sync.aligned %0;" ::"n"(N) : "memory"); }
__device__ __forceinline__ uint64_t make_desc(uint32_t addr, uint32_t lbo, uint32_t sbo, uint32_t swz) {
  return (uint64_t)((addr & 0x3FFFF) >> 4) | ((uint64_t)(lbo >> 4) << 16) | ((uint64_t)(sbo >> 4) << 32) | ((uint64_t)swz << 62);
}

__device__ __forceinline__ void ldsm_x4(uint32_t (&r)[4], uint32_t addr) {
  asm volatile("ldmatrix.sync.aligned.m8n8.x4.shared.b16 {%0,%1,%2,%3}, [%4];"
               : "=r"(r[0]), "=r"(r[1]), "=r"(r[2]), "=r"(r[3]) : "r"(addr) : "memory");
}
__device__ __forceinline__ void ldsm_x4_t(uint32_t (&r)[4], uint32_t addr) {
  asm volatile("ldmatrix.sync.aligned.m8n8.x4.trans.shared.b16 {%0,%1,%2,%3}, [%4];"
               : "=r"(r[0]), "=r"(r[1]), "=r"(r[2]), "=r"(r[3]) : "r"(addr) : "memory");
}
__device__ __forceinline__ void ldsm_x2(uint32_t& r0, uint32_t& r1, uint32_t addr) {
  asm volatile("ldmatrix.sync.aligned.m8n8.x2.shared.b16 {%0,%1}, [%2];" : "=r"(r0), "=r"(r1) : "r"(addr) : "memory");
}
__device__ __forceinline__ void stsm_x4(uint32_t addr, uint32_t r0, uint32_t r1, uint32_t r2, uint32_t r3) {
  asm volatile("stmatrix.sync.aligned.m8n8.x4.shared.b16 [%0], {%1,%2,%3,%4};"
               ::"r"(addr), "r"(r0), "r"(r1), "r"(r2), "r"(r3) : "memory");
}
__device__ __forceinline__ void stsm_x4_t(uint32_t addr, uint32_t r0, uint32_t r1, uint32_t r2, uint32_t r3) {
  asm volatile("stmatrix.sync.aligned.m8n8.x4.trans.shared.b16 [%0], {%1,%2,%3,%4};" ::"r"(addr), "r"(r0), "r"(r1), "r"(r2), "r"(r3) : "memory");
}
__device__ __forceinline__ void mma16816(float (&c)[4], const uint32_t (&a)[4], uint32_t b0, uint32_t b1) {
  asm volatile("mma.sync.aligned.m16n8k16.row.col.f32.bf16.bf16.f32 {%0,%1,%2,%3}, {%4,%5,%6,%7}, {%8,%9}, {%0,%1,%2,%3};"
               : "+f"(c[0]), "+f"(c[1]), "+f"(c[2]), "+f"(c[3])
               : "r"(a[0]), "r"(a[1]), "r"(a[2]), "r"(a[3]), "r"(b0), "r"(b1));
}
__device__ __forceinline__ void mma1688(float (&c)[4], uint32_t a0, uint32_t a1, uint32_t b0) {
  asm volatile("mma.sync.aligned.m16n8k8.row.col.f32.bf16.bf16.f32 {%0,%1,%2,%3}, {%4,%5}, {%6}, {%0,%1,%2,%3};"
               : "+f"(c[0]), "+f"(c[1]), "+f"(c[2]), "+f"(c[3]) : "r"(a0), "r"(a1), "r"(b0));
}
__device__ __forceinline__ uint32_t pack_bf16(float lo, float hi) {
  uint32_t r;
  asm("cvt.rn.bf16x2.f32 %0, %1, %2;" : "=r"(r) : "f"(hi), "f"(lo));
  return r;
}
__device__ __forceinline__ float bf_lo(uint32_t w) { return __uint_as_float(w << 16); }
__device__ __forceinline__ float bf_hi(uint32_t w) { return __uint_as_float(w & 0xFFFF0000u); }

__device__ __forceinline__ uint4 ld_relaxed4(const void* p) {
  uint4 v;
  asm volatile("ld.relaxed.gpu.global.v4.u32 {%0,%1,%2,%3}, [%4];" : "=r"(v.x), "=r"(v.y), "=r"(v.z), "=r"(v.w) : "l"(p) : "memory");
  return v;
}
__device__ __forceinline__ void st_relaxed4(void* p, uint32_t a, uint32_t b, uint32_t c, uint32_t d) {
  asm volatile("st.relaxed.gpu.global.v4.u32 [%0], {%1,%2,%3,%4};" ::"l"(p), "r"(a), "r"(b), "r"(c), "r"(d) : "memory");
}
__device__ __forceinline__ void st_relaxed2(void* p, uint32_t a, uint32_t b) {
  asm volatile("st.relaxed.gpu.global.v2.u32 [%0], {%1,%2};" ::"l"(p), "r"(a), "r"(b) : "memory");
}
__device__ __forceinline__ void st_relaxed1(void* p, uint32_t a) {
  asm volatile("st.relaxed.gpu.global.u32 [%0], %1;" ::"l"(p), "r"(a) : "memory");
}

__device__ __forceinline__ uint2 ld_relaxed2(const void* p) {
  uint2 v;
  asm volatile("ld.relaxed.gpu.global.v2.u32 {%0,%1}, [%2];" : "=r"(v.x), "=r"(v.y) : "l"(p) : "memory");
  return v;
}
__device__ __forceinline__ void sts64(uint32_t a, uint32_t x, uint32_t y) { asm volatile("st.shared.v2.b32 [%0], {%1,%2};" ::"r"(a), "r"(x), "r"(y) : "memory"); }
__device__ __forceinline__ uint2 lds64(uint32_t a) { uint2 v; asm volatile("ld.shared.v2.b32 {%0,%1}, [%2];" : "=r"(v.x), "=r"(v.y) : "r"(a) : "memory"); return v; }
__device__ __forceinline__ void lds128r(uint32_t (&r)[4], uint32_t a) {
  asm volatile("ld.shared.v4.b32 {%0,%1,%2,%3}, [%4];" : "=r"(r[0]), "=r"(r[1]), "=r"(r[2]), "=r"(r[3]) : "r"(a) : "memory");
}
__device__ __forceinline__ uint32_t movmat(uint32_t a) { uint32_t d; asm volatile("movmatrix.sync.aligned.m8n8.trans.b16 %0, %1;" : "=r"(d) : "r"(a)); return d; }
__device__ __forceinline__ uint32_t mapa(uint32_t addr, uint32_t rank) { uint32_t r; asm volatile("mapa.shared::cluster.u32 %0, %1, %2;" : "=r"(r) : "r"(addr), "r"(rank)); return r; }
__device__ __forceinline__ void st_async1(uint32_t dst, uint32_t a, uint32_t bar) {
  asm volatile("st.async.weak.shared::cluster.mbarrier::complete_tx::bytes.b32 [%0], %1, [%2];" ::"r"(dst), "r"(a), "r"(bar) : "memory");
}
__device__ __forceinline__ void st_async2(uint32_t dst, uint32_t a, uint32_t b, uint32_t bar) {
  asm volatile("st.async.weak.shared::cluster.mbarrier::complete_tx::bytes.v2.b32 [%0], {%1,%2}, [%3];" ::"r"(dst), "r"(a), "r"(b), "r"(bar) : "memory");
}
__device__ __forceinline__ void st_async4(uint32_t dst, uint32_t a, uint32_t b, uint32_t c, uint32_t d, uint32_t bar) {
  asm volatile("st.async.weak.shared::cluster.mbarrier::complete_tx::bytes.v4.b32 [%0], {%1,%2,%3,%4}, [%5];" ::"r"(dst), "r"(a), "r"(b), "r"(c), "r"(d), "r"(bar) : "memory");
}
__device__ __forceinline__ void cluster_arrive() { asm volatile("barrier.cluster.arrive.relaxed.aligned;" ::: "memory"); }
__device__ __forceinline__ void cluster_wait() { asm volatile("barrier.cluster.wait.acquire.aligned;" ::: "memory"); }

__device__ __forceinline__ void wgmma_k3_ss_ta(float (&d)[80], uint64_t da, uint64_t db, int scale_d) {
  asm volatile("{.reg .pred p; setp.ne.b32 p, %82, 0;\n"
    "wgmma.mma_async.sync.aligned.m64n160k16.f32.bf16.bf16 {%0, %1, %2, %3, %4, %5, %6, %7, %8, %9, %10, %11, %12, %13, %14, %15, %16, %17, %18, %19, %20, %21, %22, %23, %24, %25, %26, %27, %28, %29, %30, %31, %32, %33, %34, %35, %36, %37, %38, %39, %40, %41, %42, %43, %44, %45, %46, %47, %48, %49, %50, %51, %52, %53, %54, %55, %56, %57, %58, %59, %60, %61, %62, %63, %64, %65, %66, %67, %68, %69, %70, %71, %72, %73, %74, %75, %76, %77, %78, %79}, %80, %81, p, 1, 1, 1, 0;}"
    : "+f"(d[0]), "+f"(d[1]), "+f"(d[2]), "+f"(d[3]), "+f"(d[4]), "+f"(d[5]), "+f"(d[6]), "+f"(d[7]), "+f"(d[8]), "+f"(d[9]), "+f"(d[10]), "+f"(d[11]), "+f"(d[12]), "+f"(d[13]), "+f"(d[14]), "+f"(d[15]), "+f"(d[16]), "+f"(d[17]), "+f"(d[18]), "+f"(d[19]), "+f"(d[20]), "+f"(d[21]), "+f"(d[22]), "+f"(d[23]), "+f"(d[24]), "+f"(d[25]), "+f"(d[26]), "+f"(d[27]), "+f"(d[28]), "+f"(d[29]), "+f"(d[30]), "+f"(d[31]), "+f"(d[32]), "+f"(d[33]), "+f"(d[34]), "+f"(d[35]), "+f"(d[36]), "+f"(d[37]), "+f"(d[38]), "+f"(d[39]), "+f"(d[40]), "+f"(d[41]), "+f"(d[42]), "+f"(d[43]), "+f"(d[44]), "+f"(d[45]), "+f"(d[46]), "+f"(d[47]), "+f"(d[48]), "+f"(d[49]), "+f"(d[50]), "+f"(d[51]), "+f"(d[52]), "+f"(d[53]), "+f"(d[54]), "+f"(d[55]), "+f"(d[56]), "+f"(d[57]), "+f"(d[58]), "+f"(d[59]), "+f"(d[60]), "+f"(d[61]), "+f"(d[62]), "+f"(d[63]), "+f"(d[64]), "+f"(d[65]), "+f"(d[66]), "+f"(d[67]), "+f"(d[68]), "+f"(d[69]), "+f"(d[70]), "+f"(d[71]), "+f"(d[72]), "+f"(d[73]), "+f"(d[74]), "+f"(d[75]), "+f"(d[76]), "+f"(d[77]), "+f"(d[78]), "+f"(d[79])
    : "l"(da), "l"(db), "r"(scale_d));
}
__device__ __forceinline__ void wgmma_m64n32_ss_ta(float (&d)[16], uint64_t da, uint64_t db, int scale_d) {
  asm volatile("{.reg .pred p; setp.ne.b32 p, %18, 0;\n"
    "wgmma.mma_async.sync.aligned.m64n32k16.f32.bf16.bf16 {%0, %1, %2, %3, %4, %5, %6, %7, %8, %9, %10, %11, %12, %13, %14, %15}, %16, %17, p, 1, 1, 1, 0;}"
    : "+f"(d[0]), "+f"(d[1]), "+f"(d[2]), "+f"(d[3]), "+f"(d[4]), "+f"(d[5]), "+f"(d[6]), "+f"(d[7]), "+f"(d[8]), "+f"(d[9]), "+f"(d[10]), "+f"(d[11]), "+f"(d[12]), "+f"(d[13]), "+f"(d[14]), "+f"(d[15])
    : "l"(da), "l"(db), "r"(scale_d));
}

__device__ __forceinline__ void wgmma_m64n32_rs(float (&d)[16], const uint32_t (&a)[4], uint64_t db, int scale_d) {
  asm volatile("{.reg .pred p; setp.ne.b32 p, %21, 0;\n"
    "wgmma.mma_async.sync.aligned.m64n32k16.f32.bf16.bf16 {%0, %1, %2, %3, %4, %5, %6, %7, %8, %9, %10, %11, %12, %13, %14, %15}, {%16, %17, %18, %19}, %20, p, 1, 1, 0;}"
    : "+f"(d[0]), "+f"(d[1]), "+f"(d[2]), "+f"(d[3]), "+f"(d[4]), "+f"(d[5]), "+f"(d[6]), "+f"(d[7]), "+f"(d[8]), "+f"(d[9]), "+f"(d[10]), "+f"(d[11]), "+f"(d[12]), "+f"(d[13]), "+f"(d[14]), "+f"(d[15])
    : "r"(a[0]), "r"(a[1]), "r"(a[2]), "r"(a[3]), "l"(db), "r"(scale_d));
}

#define X_POS 5
#define T_STEP 2848
#define T_PHASE 1792
#define RATE0 2295
#define T_LAG 32
#define T_TOL 192
#define T_SLIP 640
#define O_FIX 5
#define VM_POS 2
#define NTMP 4
#define V_PRE 6
#define SFENCE(i) asm volatile("{.reg .pred p; setp.eq.u32 p, %0, %1; @p trap;}" ::"r"(n), "r"(4096 + (i)) : "memory")
constexpr int RING = 4;
constexpr uint32_t EMPTY = 0xFFFFFFFFu;
namespace xo {
constexpr uint32_t SLOT = 1u << 20, HEAD = 16384;
constexpr uint32_t VM = 512;
constexpr uint32_t PT = 1024;
constexpr uint32_t PM = 1536;
constexpr uint32_t VT = 8192;
constexpr uint32_t MEM = NH * HEAD;
constexpr uint32_t OM = MEM + 16384;
constexpr uint32_t O = RING * SLOT;
constexpr uint32_t BYTES = O + S_LEN * HD * 2;
}
__device__ __align__(1024) uint4 g_scratch[2 * (xo::BYTES / 16)];
__device__ unsigned g_epoch;
__device__ __align__(16) unsigned g_rate[128];

struct ChainMaps {
  CUtensorMap wq, wk, wv;
  CUtensorMap wo;
  CUtensorMap x, xq;
  const char* xp;
  uint32_t t_step, t_phase;
};

namespace chain {
constexpr int OFF_X = 65536;
constexpr int OFF_MEM = 131072;
constexpr int OFF_WS = 0;
constexpr int OFF_FP = 147456;
constexpr int OFF_KT = 163840;
constexpr int OFF_QT = 180224;
constexpr int OFF_VT = 196608;
constexpr int OFF_PX = 204800;
constexpr int OFF_S4 = OFF_PX + 1536;
constexpr int OFF_QM = 212992;
constexpr int OFF_KM = 215040;
constexpr int OFF_S1 = 217088;
constexpr int OFF_WVR = 0;
constexpr int OFF_WOR = 147456;
constexpr int OFF_RED = 212992;
constexpr int OFF_VPX = 221184;
constexpr int OFF_RX = 223232;
constexpr int OFF_TR = 225280;
constexpr int OFF_BAR = 229376;
constexpr int BAR_X = OFF_BAR, BAR_TOK = OFF_BAR + 16, BAR_EX = OFF_BAR + 32, BAR_P = OFF_BAR + 40, GRID_TGT = OFF_BAR + 128;
constexpr int CT_BASE = GRID_TGT + 4, CT_HEAD = GRID_TGT + 8, CT_OM = GRID_TGT + 12, CT_MP = GRID_TGT + 16, CT_O = GRID_TGT + 20, CT_PF = GRID_TGT + 24;
constexpr int CT_TT = GRID_TGT + 28, CT_T = GRID_TGT + 32;
constexpr uint32_t RANK_BIT = 1u << 24;
constexpr int SMEM = OFF_BAR + 256;
constexpr uint32_t SB_LO = 1024;
constexpr float SCALE = 0.08838834764831845f, L2E = 1.4426950408889634f;
}

__device__ __forceinline__ uint32_t umax4(uint32_t a, uint32_t b, uint32_t c, uint32_t d) { return max(max(a, b), max(c, d)); }
__device__ __forceinline__ bool warp_incomplete(uint32_t m) { return __any_sync(0xffffffffu, m == EMPTY); }
#define PIN(x) asm volatile("" : "+r"(x))
#define KEEPALIVE(a, z) do { float _d0, _d1, _d2, _d3; asm volatile("mma.sync.aligned.m16n8k16.row.col.f32.bf16.bf16.f32 {%0,%1,%2,%3}, {%4,%5,%6,%7}, {%4,%5}, {%8,%8,%8,%8};" \
    : "=f"(_d0), "=f"(_d1), "=f"(_d2), "=f"(_d3) : "r"(a[0]), "r"(a[1]), "r"(a[2]), "r"(a[3]), "f"(0.f)); \
      \
    asm volatile("{.reg .pred p; setp.ne.u32 p, %0, 0; @p st.shared.f32 [%0], %1;}" ::"r"(z), "f"(_d0 + _d3) : "memory"); } while (0)
constexpr int POLL_LIMIT = 1 << 17;

__device__ __forceinline__ uint32_t keep(uint32_t x) { return __shfl_sync(0xffffffffu, x, threadIdx.x & 31); }
__device__ __forceinline__ char* gptr(uint32_t hi, uint32_t lo) { return (char*)(((uint64_t)hi << 32) | lo); }
__device__ __forceinline__ uint32_t slot_off(int n) { return ((uint32_t)n & (RING - 1)) * xo::SLOT; }
__device__ __forceinline__ float quad_max(float x) {
  const float a = __shfl_xor_sync(~0u, x, 1), b = __shfl_xor_sync(~0u, x, 2), c = __shfl_xor_sync(~0u, x, 3);
  return fmaxf(fmaxf(x, a), fmaxf(b, c));
}
__device__ __forceinline__ void acc_fence(float (&a)[16]) {
#pragma unroll
  for (int i = 0; i < 16; i++) asm volatile("" : "+f"(a[i]) :: "memory");
}
template <int NB = 1, int STRIDE = 0>
__device__ __forceinline__ void gather_issue(uint32_t dst, const char* src) {
#pragma unroll
  for (int b = 0; b < NB; b++)
#pragma unroll
    for (int i = 0; i < 4; i++) cp_async16(dst + b * STRIDE + i * 512, src + b * STRIDE + i * 512);
  cp_async_commit();
}
template <int NB, int STRIDE>
__device__ __forceinline__ bool gather_incomplete(uint32_t chk) {
  uint32_t m = 0;
#pragma unroll
  for (int b = 0; b < NB; b++) m = max(m, umax4(lds32(chk + b * STRIDE), lds32(chk + b * STRIDE + 512), lds32(chk + b * STRIDE + 1024), lds32(chk + b * STRIDE + 1536)));
  return warp_incomplete(m);
}
__device__ __forceinline__ uint32_t ld_relaxed1(const void* p) {
  uint32_t v;
  asm volatile("ld.relaxed.gpu.global.u32 %0, [%1];" : "=r"(v) : "l"(p) : "memory");
  return v;
}
__device__ __forceinline__ uint32_t gtime() { uint64_t g; asm volatile("mov.u64 %0, %%globaltimer;" : "=l"(g) :: "memory"); return (uint32_t)g; }
#define WAIT_UNTIL(t, ka, alive, id) do { \
    int _d = gtime() - (t); \
    if (__builtin_expect(_d > T_TOL, 0)) do { t += T_SLIP; _d -= T_SLIP; } while (_d > T_TOL); \
    if (alive) for (int _k = 64; _d < -96 && --_k; _d = gtime() - (t)) KEEPALIVE(ka, zr); \
    for (uint32_t _g = -128; (int)(_d & ++_g) < 0;) _d = gtime() - (t); } while (0)
__device__ __forceinline__ void issue_x(uint32_t sb, const CUtensorMap* map, int n, int part, int q = 0) {
  asm volatile("{.reg .pred p; elect.sync _|p, 0xffffffff;\n"
               "@p cp.async.bulk.tensor.3d.shared::cluster.global.mbarrier::complete_tx::bytes [%0], [%1, {%3, %4, %5}], [%2];}"
               ::"r"(sb + chain::OFF_X + part * 32768 + q * 16384), "l"(map), "r"(sb + chain::BAR_X + 8 * part), "r"(0), "r"(n * SEG), "r"(part * 8 + q * 4) : "memory");
}
__device__ __forceinline__ void issue_x_if(uint32_t sb, const CUtensorMap* map, int n, int part, uint32_t on) {
  asm volatile("{.reg .pred p, q; elect.sync _|p, 0xffffffff; setp.ne.and.u32 q, %6, 0, p;\n"
               "@q cp.async.bulk.tensor.3d.shared::cluster.global.mbarrier::complete_tx::bytes [%0], [%1, {%3, %4, %5}], [%2];}"
               ::"r"(sb + chain::OFF_X + part * 32768), "l"(map), "r"(sb + chain::BAR_X + 8 * part), "r"(0), "r"(n * SEG), "r"(part * 8), "r"(on) : "memory");
}
__device__ __forceinline__ void prefetch_l2(const char* p, uint32_t bytes) {
  asm volatile("{.reg .pred p; elect.sync _|p, 0xffffffff; @p cp.async.bulk.prefetch.L2.global [%0], %1;}" ::"l"(p), "r"(bytes) : "memory");
}
__device__ __forceinline__ void expect_elect(uint32_t bar, uint32_t bytes) {
  asm volatile("{.reg .pred p; elect.sync _|p, 0xffffffff; @p mbarrier.arrive.expect_tx.shared::cta.b64 _, [%0], %1;}" ::"r"(bar), "r"(bytes) : "memory");
}
template <int WG> __device__ __forceinline__ constexpr uint64_t xdesc(int ks) {
  return (uint64_t)(((chain::SB_LO + chain::OFF_X + WG * 32768 + (ks >> 2) * 4096 + (ks & 3) * 32) >> 4) + (1u << 16)) |
         ((uint64_t)(64u | (1u << 30)) << 32);
}
template <int WG> __device__ __forceinline__ constexpr uint64_t wdesc(int o, int ks) {
  return (uint64_t)(((chain::SB_LO + chain::OFF_WS + WG * 32768 + o * 16384 + ks * 2048) >> 4) + (1u << 16)) | ((uint64_t)(64u | (1u << 30)) << 32);
}
__device__ __forceinline__ void load_mem0(uint2 (&m)[8], const bf16* __restrict__ mem0) {
#pragma unroll
  for (int r = 0; r < 8; r++) m[r] = ld_relaxed2((const uint2*)(mem0 + r * DM) + threadIdx.x);
}
__device__ __forceinline__ void store_mem0(uint32_t sb, const uint2 (&m)[8]) {
  const uint32_t d = sb + chain::OFF_MEM + threadIdx.x * 64;
  sts128(d, make_uint4(__byte_perm(m[0].x, m[1].x, 0x5410), __byte_perm(m[2].x, m[3].x, 0x5410), __byte_perm(m[4].x, m[5].x, 0x5410), __byte_perm(m[6].x, m[7].x, 0x5410)));
  sts128(d + 16, make_uint4(__byte_perm(m[0].x, m[1].x, 0x7632), __byte_perm(m[2].x, m[3].x, 0x7632), __byte_perm(m[4].x, m[5].x, 0x7632), __byte_perm(m[6].x, m[7].x, 0x7632)));
  sts128(d + 32, make_uint4(__byte_perm(m[0].y, m[1].y, 0x5410), __byte_perm(m[2].y, m[3].y, 0x5410), __byte_perm(m[4].y, m[5].y, 0x5410), __byte_perm(m[6].y, m[7].y, 0x5410)));
  sts128(d + 48, make_uint4(__byte_perm(m[0].y, m[1].y, 0x7632), __byte_perm(m[2].y, m[3].y, 0x7632), __byte_perm(m[4].y, m[5].y, 0x7632), __byte_perm(m[6].y, m[7].y, 0x7632)));
}
template <int K> __device__ __forceinline__ uint32_t loop_zero(int n) { uint32_t z; asm volatile("shr.u32 %0, %1, %2;" : "=r"(z) : "r"(n), "n"(16 + K)); return z; }
#define NEWZ(k) zr = loop_zero<k>(n)

template <int WG>
__device__ __forceinline__ void role_a(const ChainMaps& maps, const bf16* __restrict__ mem0, const uint32_t sb, const uint32_t xbase_hi) {
  using namespace chain;
  const int h = blockIdx.x >> 2;
  const bool J = sb >= RANK_BIT;
  const uint32_t u16 = (threadIdx.x & 96) * 64 + (threadIdx.x & 31) * 16;
  const uint32_t t16 = keep(u16), l16 = keep((threadIdx.x & 31) * 16);
  const uint32_t a_wl = keep((((threadIdx.x >> 4) & 1) * 8 + (threadIdx.x & 7)) * 128 + (((((threadIdx.x >> 4) & 6) + ((threadIdx.x >> 3) & 1)) ^ (threadIdx.x & 7)) << 4));
  const uint32_t xhi = keep(xbase_hi + (t16 >> 16));
#define xh (lds32(sb + CT_HEAD) + t16)
#define xm (lds32(sb + CT_BASE) + t16 + xo::MEM)
#define last_warp __any_sync(0xffffffffu, tv >= 6144)
#define tv (t16 ^ zr)
  const CUtensorMap* wm = J ? &maps.wk : &maps.wq;

  uint32_t aW[2][24][4];
  uint2 m0[8];
  load_mem0(m0, mem0);
  mbar_wait(sb + BAR_P, 0);
#pragma unroll
  for (int ks = 0; ks < 24; ks++) ldsm_x4_t(aW[0][ks], sb + a_wl + OFF_X + WG * 49152 + ks * 2048);
  named_bar(0, 256);
  if (WG == 1 && __any_sync(0xffffffffu, t16 >= 6144)) {
    fence_async_smem();
    if (l16 == 0) {
      mbar_expect_tx(sb + BAR_P + 16, 2 * 16384);
      for (int q = 0; q < 2; q++) tma_load_2d(sb + OFF_X + (4 + q) * 16384, wm, h * DH + (q ^ 1) * 64, q * 512 + 256, sb + BAR_P + 16);
    }
    __syncwarp();
    expect_elect(sb + BAR_X, 32768); expect_elect(sb + BAR_X + 8, 32768); expect_elect(sb + BAR_TOK, 8192);
    issue_x(sb, &maps.x, 0, 0); issue_x(sb, &maps.x, 0, 1);
  }
  mbar_wait(sb + BAR_P + 8, 0);
#pragma unroll
  for (int ks = 0; ks < 16; ks++) ldsm_x4_t(aW[1][ks], sb + a_wl + OFF_X + 6 * 16384 + WG * 32768 + ks * 2048);
  mbar_wait(sb + BAR_P + 16, 0);
#pragma unroll
  for (int ks = 0; ks < 8; ks++) ldsm_x4_t(aW[1][16 + ks], sb + a_wl + OFF_X + (4 + WG) * 16384 + ks * 2048);
  named_bar(0, 256);
  cluster_arrive();
  store_mem0(sb, m0);
  mbar_wait(sb + BAR_P + 24, 0);
  cluster_wait();
  const uint32_t rsb = sb ^ RANK_BIT;
  const uint32_t a_ws = sb + a_wl + OFF_WS + WG * 32768;

  uint32_t ws[2][4][4];
  auto load_ws = [&]() {
#pragma unroll
    for (int q = 0; q < 2; q++) {
      const uint32_t a = a_ws + q * 4096;
      ldsm_x4_t(ws[q][0], a); ldsm_x4_t(ws[q][1], a + 16384); ldsm_x4_t(ws[q][2], a + 2048); ldsm_x4_t(ws[q][3], a + 16384 + 2048);
    }
  };
  uint32_t tref = 0;
#pragma unroll 1
  for (int n = 0; n <= (J ? NSEG : NSEG - 1); n++) {
#define s (n - 1)
#define sv ((int)(n ^ zr) - 1)
    const bool more = __builtin_expect(s + 1 < NSEG, 1);
    uint32_t zr = loop_zero<0>(n);
#define wq ((int)(tv >> 11))
#define lv (l16 ^ zr)
#define gh (xh + slot_off(sv))
    uint32_t tmp[NTMP][4];
    auto load_tmp = [&](int o) {
#pragma unroll
      for (int ks = 0; ks < NTMP; ks++) ldsm_x4_t(tmp[ks], a_ws + o * 16384 + ks * 2048);
    };
    auto wait_x = [&]() { mbar_wait<0>(sb + BAR_X + 8 * WG, n & 1); };
    if (__builtin_expect(s < 0, 0)) { load_tmp(1); wait_x(); }
    else {
      {
        if (WG == 1) { if (__builtin_expect(s > 0, 1)) {
          const uint32_t dst = sb + OFF_MEM + tv + t16 - l16, chk = dst + ((lv >> 5) & 12);
          uint32_t tries = zr;
#pragma unroll 1
          do {
            if (tries) {
              const char* src = gptr(xhi, xm + t16 - l16 + slot_off(sv));
              tref += T_SLIP;
              WAIT_UNTIL(tref, aW[0][0], 1, -1);
              gather_issue<2, 2048>(dst, src);
            }
            KEEPALIVE(aW[0][0], zr);
            cp_async_wait_group<0>();
          } while (gather_incomplete<2, 2048>(chk) && ++tries < POLL_LIMIT);
        } } else if (J == 0) {
          uint32_t tries = s == 0;
#pragma unroll 1
          do {
            if (tries) gather_issue(sb + OFF_VT + tv, gptr(xhi, gh) + xo::VT);
            cp_async_wait_group<0>();
          } while (gather_incomplete<1, 0>(sb + OFF_VT + t16 + ((lv >> 5) & 12)) && ++tries < POLL_LIMIT);
        }
        named_bar(1, 256);
      }
      float c[2][2][4];
#pragma unroll
      for (int i = 0; i < 4; i++) c[i >> 1][i & 1][0] = c[i >> 1][i & 1][1] = c[i >> 1][i & 1][2] = c[i >> 1][i & 1][3] = 0.f;
      {
        const uint32_t a_mem = sb + OFF_MEM + WG * 8192 + l16;
        uint32_t b[4][4];
        bool tok;
        constexpr int PR[16] = {12, 13, 0, 1, 2, 3, 4, 14, 5, 6, 7, 8, 9, 15, 10, 11};
        ldsm_x4_t(b[0], a_mem + PR[0] * 512); ldsm_x4_t(b[1], a_mem + PR[1] * 512);
#pragma unroll
        for (int i = 0; i < 16; i++) {
          if ((i & 1) == 0 && i < 14) {
            ldsm_x4_t(b[(i + 2) & 3], a_mem + PR[i + 2] * 512); ldsm_x4_t(b[(i + 3) & 3], a_mem + PR[i + 3] * 512);
            if (i == 2 || i == 8) { ldsm_x4_t(ws[1][0], a_ws + (i == 2 ? 2 : 3) * 4096); ldsm_x4_t(ws[1][1], a_ws + (i == 2 ? 2 : 3) * 4096 + 16384); }
            if (i == 4 || i == 10) { ldsm_x4_t(ws[1][2], a_ws + (i == 4 ? 2 : 3) * 4096 + 2048); ldsm_x4_t(ws[1][3], a_ws + (i == 4 ? 2 : 3) * 4096 + 16384 + 2048); }
          }
          const int p = PR[i];
          if (p >= 12) {
            const int z = i != 0;
            mma16816(c[0][0], ws[z][0], b[i & 3][0], b[i & 3][1]); mma16816(c[1][0], ws[z][1], b[i & 3][0], b[i & 3][1]);
            mma16816(c[0][1], ws[z][2], b[i & 3][2], b[i & 3][3]); mma16816(c[1][1], ws[z][3], b[i & 3][2], b[i & 3][3]);
          } else {
            mma16816(c[1][0], aW[1][2 * p], b[i & 3][0], b[i & 3][1]); mma16816(c[1][1], aW[1][2 * p + 1], b[i & 3][2], b[i & 3][3]);
            mma16816(c[0][0], aW[0][2 * p], b[i & 3][0], b[i & 3][1]); mma16816(c[0][1], aW[0][2 * p + 1], b[i & 3][2], b[i & 3][3]);
          }
          if (i == 12) tok = mbar_test(sb + BAR_TOK + 8 * (s & 1), (s >> 1) & 1);
          if (i == 15 && __builtin_expect(!tok, 0)) mbar_wait(sb + BAR_TOK + 8 * (s & 1), (s >> 1) & 1);
          if (i == X_POS + 4 * (1 - WG)) { issue_x_if(sb, &maps.x, s + 1, WG, t16 >= 6144 && more); if (WG) __syncwarp(); }
        }
      }
      sts128f(sb + OFF_PX + WG * 512 + t16, make_float4(c[1][0][0] + c[1][1][0], c[1][0][1] + c[1][1][1], c[1][0][2] + c[1][1][2], c[1][0][3] + c[1][1][3]));
      const float4 own = make_float4(c[0][0][0] + c[0][1][0], c[0][0][1] + c[0][1][1], c[0][0][2] + c[0][1][2], c[0][0][3] + c[0][1][3]);
      NEWZ(1);
      uint32_t a = (J ? OFF_KM : OFF_QM) + WG * 1024 + wq * 256 + (lv >> 2);
      uint32_t ra = rsb + a, ra2 = ra + 128, rx = rsb + BAR_EX + zr;
      PIN(a); PIN(ra); PIN(ra2); PIN(rx);
      SFENCE(16);
      named_bar(3, 256);
      {
        const float4 o = lds128f(sb + OFF_PX + (WG ^ 1) * 512 + t16);
        const uint32_t lo = pack_bf16(own.x + o.x, own.y + o.y), hi = pack_bf16(own.z + o.z, own.w + o.w);
        if (J == 1 && more) { st_async1(ra, lo, rx); st_async1(ra2, hi, rx); }
        sts32(sb + a, lo); sts32(sb + a + 128, hi);
      }
      const uint32_t kt = sb + OFF_KT + (s & 1) * 8192;
#define k_lane ((lv & 240) + ((lv & 256) << 2))
#define a_lane (((lv & 128) << 1) + ((lv & 256) >> 1) + (lv & 112))
      if (J == 0) {
        uint32_t am[4][4], kb[4][4];
        uint2 vm0, vm1;
        const char* pvm = WG == 0 ? gptr(xhi, gh - (lv >> 1)) + xo::VM : nullptr;
        if (WG == 0 && VM_POS == 0) { vm0 = ld_relaxed2(pvm); vm1 = ld_relaxed2(pvm + 256); }
        if (WG == 1) {
#pragma unroll
          for (int p = 0; p < 4; p++) ldsm_x4(kb[p], kt + wq * 256 + k_lane + p * 2048);
        }
        named_bar(7, 256);
#pragma unroll
        for (int p = 0; p < 4; p++) ldsm_x4_t(am[p], sb + OFF_QM + p * 512 + a_lane);
        auto scores = [&]() {
          float c0[2][4], c1[2][4];
#pragma unroll
          for (int i = 0; i < 2; i++) { c0[i][0] = c0[i][1] = c0[i][2] = c0[i][3] = 0.f; c1[i][0] = c1[i][1] = c1[i][2] = c1[i][3] = 0.f; }
#pragma unroll
          for (int p = 0; p < 4; p++) { mma16816(c0[p & 1], am[p], kb[p][0], kb[p][1]); mma16816(c1[p & 1], am[p], kb[p][2], kb[p][3]); }
          const uint32_t r1 = pack_bf16((c0[0][0] + c0[1][0]) + (c1[0][2] + c1[1][2]), (c0[0][1] + c0[1][1]) + (c1[0][3] + c1[1][3]));
          return pack_bf16(bf_lo(r1) * SCALE, bf_hi(r1) * SCALE);
        };
        if (WG == 1) {
          const uint32_t st = scores();
          uint32_t vb[4][4];
#pragma unroll
          for (int e = 0; e < 4; e++) lds128r(vb[e], sb + OFF_VT + t16 + e * 512);
          __syncwarp();
          sts32(sb + OFF_S4 + l16 + wq * 4, st);
          named_bar(8, 128);
          const uint4 sc = lds128(sb + OFF_S4 + l16);
          float x[8] = {bf_lo(sc.x), bf_hi(sc.x), bf_lo(sc.y), bf_hi(sc.y), bf_lo(sc.z), bf_hi(sc.z), bf_lo(sc.w), bf_hi(sc.w)};
          float mx = fmaxf(fmaxf(fmaxf(x[0], x[1]), fmaxf(x[2], x[3])), fmaxf(fmaxf(x[4], x[5]), fmaxf(x[6], x[7])));
          mx = quad_max(mx);
          const float mb = mx * L2E;
#pragma unroll
          for (int i = 0; i < 8; i++) x[i] = ex2(fmaf(x[i], L2E, -mb));
          uint32_t pa[4], pb[4];
          asm volatile("" : "=r"(pa[1]), "=r"(pa[3]), "=r"(pb[1]), "=r"(pb[3]));
          pa[0] = pack_bf16(x[0], x[1]); pa[2] = pack_bf16(x[2], x[3]);
          pb[0] = pack_bf16(x[4], x[5]); pb[2] = pack_bf16(x[6], x[7]);
          float oa[4][4];
#pragma unroll
          for (int e = 0; e < 4; e++) { oa[e][0] = oa[e][1] = oa[e][2] = oa[e][3] = 0.f; mma16816(oa[e], pa, vb[e][0], vb[e][1]); }
#pragma unroll
          for (int e = 0; e < 4; e++) mma16816(oa[e], pb, vb[e][2], vb[e][3]);
          sts64(sb + OFF_PX + 1024 + t16, __float_as_uint(mx), __float_as_uint(((x[0] + x[1]) + (x[2] + x[3])) + ((x[4] + x[5]) + (x[6] + x[7]))));
          sts128f(sb + OFF_PX + t16, make_float4(oa[0][0], oa[0][1], oa[1][0], oa[1][1]));
          sts128f(sb + OFF_PX + 512 + t16, make_float4(oa[2][0], oa[2][1], oa[3][0], oa[3][1]));
          named_bar_arrive(9, 256);
          wait_x();
          load_tmp(1);
        } else {
          if (VM_POS == 1) { pvm += am[3][0] & zr; vm0 = ld_relaxed2(pvm); vm1 = ld_relaxed2(pvm + 256); }
          const uint32_t xo0 = lds32(sb + CT_OM) + wq * 512 + l16;
          mbar_wait<0>(sb + BAR_EX, s & 1);
          if (VM_POS == 2) { vm0 = ld_relaxed2(pvm); vm1 = ld_relaxed2(pvm + 256); }
#pragma unroll
          for (int p = 0; p < 4; p++) ldsm_x4_t(kb[p], sb + OFF_KM + p * 512 + l16);
          const uint32_t sm = scores();
          float mx = quad_max(fmaxf(bf_lo(sm), bf_hi(sm)));
          SFENCE(25);
          named_bar(9, 256);
          const uint2 ms = lds64(sb + OFF_PX + 1024 + t16);
          const float4 t0 = lds128f(sb + OFF_PX + t16), t1 = lds128f(sb + OFF_PX + 512 + t16);
          mx = fmaxf(mx, __uint_as_float(ms.x));
          const float mb = mx * L2E;
          const float e0 = ex2(fmaf(bf_lo(sm), L2E, -mb)), e1 = ex2(fmaf(bf_hi(sm), L2E, -mb)), ct = ex2(fmaf(__uint_as_float(ms.x), L2E, -mb));
          uint32_t p4 = pack_bf16(e0, e1), p5;
          asm volatile("" : "=r"(p5));
          float sx = fmaf(ct, __uint_as_float(ms.y), e0 + e1);
          float oa[4][4] = {{t0.x * ct, t0.y * ct, 0.f, 0.f}, {t0.z * ct, t0.w * ct, 0.f, 0.f}, {t1.x * ct, t1.y * ct, 0.f, 0.f}, {t1.z * ct, t1.w * ct, 0.f, 0.f}};
          const float s1 = __shfl_xor_sync(~0u, sx, 1), s2 = __shfl_xor_sync(~0u, sx, 2), s3 = __shfl_xor_sync(~0u, sx, 3);
          if (__builtin_expect(warp_incomplete(max(vm0.x, vm1.x)), 0)) {
            uint32_t tries = zr;
#pragma unroll 1
            do { vm0 = ld_relaxed2(pvm); vm1 = ld_relaxed2(pvm + 256); } while (warp_incomplete(max(vm0.x, vm1.x)) && ++tries < POLL_LIMIT);
          }
          mma1688(oa[0], p4, p5, vm0.x); mma1688(oa[1], p4, p5, vm0.y); mma1688(oa[2], p4, p5, vm1.x); mma1688(oa[3], p4, p5, vm1.y);
          const float rx = rcp((sx + s1) + (s2 + s3));
          st_relaxed4(gptr(xhi, xo0 + slot_off(sv)), pack_bf16(oa[0][0] * rx, oa[0][1] * rx), pack_bf16(oa[1][0] * rx, oa[1][1] * rx),
                      pack_bf16(oa[2][0] * rx, oa[2][1] * rx), pack_bf16(oa[3][0] * rx, oa[3][1] * rx));
          SFENCE(24);
          named_bar_arrive(10, 256);
          st_relaxed4(gptr(xhi, xo0 + slot_off(sv + 3)), EMPTY, EMPTY, EMPTY, EMPTY);
          load_tmp(1);
          wait_x();
        }
      } else {
        bool xok;
        {
          const int mt = WG | (wq == 3), ktile = wq == 3 ? 2 + WG : wq - 1;
          const uint32_t qt = sb + OFF_QT + (s & 1) * 8192 + mt * 512 + a_lane;
          uint32_t kb[4][4], q[8][4];
          if (__any_sync(0xffffffffu, tv < 2048)) {
            named_bar(7, 256);
#pragma unroll
            for (int p = 0; p < 4; p++) ldsm_x4_t(kb[p], sb + OFF_KM + p * 512 + l16);
          } else {
            named_bar_arrive(7, 256);
#pragma unroll
            for (int p = 0; p < 4; p++) ldsm_x4(kb[p], kt + ktile * 256 + k_lane + p * 2048);
          }
#pragma unroll
          for (int i = 0; i < 8; i++) ldsm_x4(q[i], qt + i * 1024);
          __syncwarp();
          float c0[4][4];
#pragma unroll
          for (int i = 0; i < 4; i++) { c0[i][0] = c0[i][1] = c0[i][2] = c0[i][3] = 0.f; mma16816(c0[i], q[i], kb[i >> 1][(i & 1) * 2], kb[i >> 1][(i & 1) * 2 + 1]); }
#pragma unroll
          for (int i = 0; i < 4; i++) mma16816(c0[i], q[4 + i], kb[2 + (i >> 1)][(i & 1) * 2], kb[2 + (i >> 1)][(i & 1) * 2 + 1]);
          load_tmp(1);
          xok = mbar_test(sb + BAR_X + 8 * WG, n & 1);
          NEWZ(3);
          const uint32_t r0 = pack_bf16((c0[0][0] + c0[1][0]) + (c0[2][0] + c0[3][0]), (c0[0][1] + c0[1][1]) + (c0[2][1] + c0[3][1]));
          const uint32_t r1 = pack_bf16((c0[0][2] + c0[1][2]) + (c0[2][2] + c0[3][2]), (c0[0][3] + c0[1][3]) + (c0[2][3] + c0[3][3]));
          const uint32_t sa = wq == 0 ? sb + OFF_S1 + (lv >> 2) + mt * 256 : sb + OFF_S4 + l16 + mt * 4096 + ktile * 4;
          sts32(sa, pack_bf16(bf_lo(r0) * SCALE, bf_hi(r0) * SCALE));
          sts32(sa + (wq == 0 ? 128 : 2048), pack_bf16(bf_lo(r1) * SCALE, bf_hi(r1) * SCALE));
        }
        if (WG == 1) named_bar_arrive(8, 256);
        else {
          if (more) named_bar_arrive(10, 256);
          const uint32_t gp = gh;
          named_bar(8, 256);
          const uint4 sc = lds128(sb + OFF_S4 + t16); const uint32_t s1 = lds32(sb + OFF_S1 + wq * 128 + (lv >> 2));
          float y[10] = {bf_lo(s1), bf_hi(s1), bf_lo(sc.x), bf_hi(sc.x), bf_lo(sc.y), bf_hi(sc.y), bf_lo(sc.z), bf_hi(sc.z), bf_lo(sc.w), bf_hi(sc.w)};
          const int rel = wq * 8 + (int)(lv >> 6) - (int)((lv >> 3) & 6);
          const float NEG = -999292928.f;
#pragma unroll
          for (int e = 0; e < 4; e++) {
            if (e * 8 > rel) y[2 * e + 2] = NEG;
            if (e * 8 + 1 > rel) y[2 * e + 3] = NEG;
          }
          float my = fmaxf(fmaxf(fmaxf(y[0], y[1]), fmaxf(y[2], y[3])), fmaxf(fmaxf(y[4], y[5]), fmaxf(y[6], y[7])));
          my = quad_max(fmaxf(my, fmaxf(y[8], y[9])));
#pragma unroll
          for (int i = 0; i < 10; i++) y[i] = ex2((y[i] - my) * L2E);
          float sy = ((y[0] + y[1]) + (y[2] + y[3])) + ((y[4] + y[5]) + (y[6] + y[7])) + (y[8] + y[9]);
          const float ry = rcp((sy + __shfl_xor_sync(~0u, sy, 1)) + (__shfl_xor_sync(~0u, sy, 2) + __shfl_xor_sync(~0u, sy, 3)));
          st_relaxed4(gptr(xhi, gp) + xo::PT, pack_bf16(y[2] * ry, y[3] * ry), pack_bf16(y[4] * ry, y[5] * ry), pack_bf16(y[6] * ry, y[7] * ry), pack_bf16(y[8] * ry, y[9] * ry));
          const uint32_t l12 = lv - (lv >> 2);
          st_relaxed1(gptr(xhi, gp - l12) + xo::PM, pack_bf16(y[0] * ry, y[1] * ry));
        }
        if (!xok && more) wait_x();
      }
    }
    if (more) {
      float acc[16];
      const uint32_t xph = (s + 1) & 1;
      auto batch = [&](const uint32_t (&a)[24][4], int o) {
        wg_fence();
#pragma unroll
        for (int ks = NTMP; ks < 8; ks++) wgmma_m64n32_ss_ta(acc, wdesc<WG>(o, ks), xdesc<WG>(24 + ks), ks != NTMP);
#pragma unroll
        for (int ks = 0; ks < NTMP; ks++) wgmma_m64n32_rs(acc, tmp[ks], xdesc<WG>(24 + ks), 1);
#pragma unroll
        for (int ks = 0; ks < 24; ks++) wgmma_m64n32_rs(acc, a[ks], xdesc<WG>(ks), 1);
        wg_commit();
      };
      if (WG == 0) named_bar(12, 256);
      else if (__builtin_expect(s >= 0, 1)) named_bar(10, 256);
      batch(aW[1], 1);
      named_bar_arrive(WG ? 12 : 13, 256);
      wg_wait<0>();
      acc_fence(acc);
      load_tmp(0);
#pragma unroll
      for (int i = 0; i < 4; i++) sts128f(sb + OFF_FP + WG * 8192 + t16 + i * 512, make_float4(acc[4 * i], acc[4 * i + 1], acc[4 * i + 2], acc[4 * i + 3]));
      NEWZ(4);
      if (WG == 0 && s >= 0) {
        const uint32_t g1 = xh + slot_off(sv + 1);
        if (J == 0) gather_issue(sb + OFF_VT + tv, gptr(xhi, g1) + xo::VT);
        else {
          st_relaxed4(gptr(xhi, g1) + xo::PT, EMPTY, EMPTY, EMPTY, EMPTY);
          st_relaxed1(gptr(xhi, g1 - lv + (lv >> 2)) + xo::PM, EMPTY);
        }
      }
      uint32_t esrc = 0;
      if (WG == 1) { esrc = xm + t16 - l16 + 2048 + slot_off(sv + 1); tref += lds32(sb + CT_T); }
      named_bar(WG ? 13 : 14, 256);
      batch(aW[0], 0);
      NEWZ(5);
      if (WG == 1) {
        named_bar(14, 256);
        if (last_warp && s + 2 < NSEG) {
          expect_elect(sb + BAR_TOK + 8 * (xph ^ 1), 8192); expect_elect(sb + BAR_X, 32768); expect_elect(sb + BAR_X + 8, 32768);
          if (J == 0) expect_elect(sb + BAR_EX, 2048);
          if (s == NSEG - 3) asm volatile("griddepcontrol.launch_dependents;");
        }
      }
      const uint32_t tb = lds32(sb + CT_TT) + xph * 8192 + WG * 4096 + ((tv + l16) >> 1);
      float4 oth[4];
#pragma unroll
      for (int i = 0; i < 4; i++) oth[i] = lds128f(sb + OFF_FP + (WG ^ 1) * 8192 + t16 + i * 512);
      if (WG == 1 && __builtin_expect(s >= 0, 1)) {
        const uint32_t edst = sb + OFF_MEM + tv + t16 - l16;
        WAIT_UNTIL(tref, aW[0][0], 0, J ? 7 : 0);
        gather_issue<2, 2048>(edst, gptr(xhi, esrc) - 2048);
      }
      wg_wait<0>();
      acc_fence(acc);
      uint32_t lt[4], ht[4];
#pragma unroll
      for (int i = 0; i < 4; i++) {
        const float4 o = oth[i];
        lt[i] = pack_bf16(acc[4 * i] + o.x, acc[4 * i + 1] + o.y); ht[i] = pack_bf16(acc[4 * i + 2] + o.z, acc[4 * i + 3] + o.w);
      }
      stsm_x4_t(tb, lt[0], ht[0], lt[1], ht[1]); stsm_x4_t(tb + 512, lt[2], ht[2], lt[3], ht[3]);
      NEWZ(6);
      if (WG == 0 && last_warp) {
        load_ws();
        named_bar(11, 256);
        fence_async_smem();
        const uint32_t tt = (J ? OFF_KT : OFF_QT) + xph * 8192;
        asm volatile("{.reg .pred p; elect.sync _|p, 0xffffffff;\n"
                     "@p cp.async.bulk.shared::cluster.shared::cta.mbarrier::complete_tx::bytes [%0], [%1], 8192, [%2];}"
                     ::"r"(rsb + tt), "r"(sb + tt), "r"(rsb + BAR_TOK + 8 * xph) : "memory");
      } else {
        named_bar_arrive(11, 256);
        load_ws();
      }
    }
    if (!more) break;
    if (__builtin_expect(s < 0, 0)) {
      tref = gtime() / T_SLIP * T_SLIP - T_SLIP;
    }
  }
  cp_async_wait_group<0>();
  if (J == 0) mbar_wait(sb + BAR_TOK + 8, 1);
}

template <int WG>
__device__ __forceinline__ void role_v(const ChainMaps& maps, const bf16* __restrict__ mem0, const uint32_t sb, const uint32_t xbase_hi) {
  using namespace chain;
  const int h = blockIdx.x >> 2;
  const uint32_t u16 = (threadIdx.x & 96) * 64 + (threadIdx.x & 31) * 16;
  const uint32_t t16 = keep(u16), l16 = keep((threadIdx.x & 31) * 16);
  const uint32_t xhi = keep(xbase_hi + (t16 >> 16));
#define j (sb >> 24)
  auto wv_addr = [&](uint32_t t) { return WG * 32768 + ((t & 256) << 2) + ((t & 112) << 3) + ((((t >> 6) & 96) + ((t >> 3) & 16)) ^ (t & 112)); };
  auto wo_addr = [&](uint32_t t) { return OFF_WOR + WG * 32768 + ((t & 6144) << 2) + ((t & 256) << 1) + ((t & 112) << 2) + ((((j ^ 1) << 5) + ((t >> 3) & 16)) ^ ((t >> 1) & 48)); };
#define ovt (((tv + l16) >> 1) + (xo::VT + WG * 512 + j * 4096))
#define ovm (((tv & 4096) >> 1) + ((tv & 2048) >> 3) + (lv >> 1) + (xo::VM + j * 4096))
#define xvt (lds32(sb + CT_HEAD) + ovt)
#define xvm (lds32(sb + CT_HEAD) + ovm)
#define xom (lds32(sb + CT_OM) + t16 + WG * 8192)
#define warp_is(q) __any_sync(0xffffffffu, (tv >> 11) == (q))
#define upper_warps (WG == 1 || __any_sync(0xffffffffu, tv >= 4096))

  uint32_t aV[16][4];
  uint32_t aO[16][4];
  uint32_t bO[16][4];
  uint32_t rot[16][4];
  if (WG == 1 && __any_sync(0xffffffffu, t16 >= 6144)) {
    expect_elect(sb + BAR_X, 32768); expect_elect(sb + BAR_X + 8, 32768);
    issue_x(sb, &maps.x, 0, 0); issue_x(sb, &maps.x, 0, 1);
    prefetch_l2(maps.xp + 65536 + (h * 2 + j) * 3072, 3072);
  }
  cluster_arrive();
  { uint2 m0[8]; load_mem0(m0, mem0); store_mem0(sb, m0); }
  mbar_wait(sb + BAR_P, 0);
#pragma unroll
  for (int ks = 0; ks < 16; ks++) ldsm_x4_t(aV[ks], sb + wv_addr(t16) + OFF_WOR + ks * 2048);
  auto load_v = [&](uint32_t t) {
#pragma unroll
    for (int ks = 0; ks < 16; ks++) ldsm_x4_t(rot[ks], sb + wv_addr(t) + OFF_WVR + ks * 2048);
  };
  load_v(t16);
  named_bar(0, 256);
  if (threadIdx.x == 0) {
    fence_async_smem();
    mbar_expect_tx(sb + BAR_P + 8, 4 * 16384);
    for (int q = 0; q < 4; q++) tma_load_2d(sb + OFF_WOR + q * 16384, &maps.wo, h * 32, j * 2048 + q * 256, sb + BAR_P + 8);
    for (int q = 0; q < 4; q++) tma_prefetch_2d(&maps.wo, h * 32, j * 2048 + 1024 + q * 256);
  }
  __syncwarp();
  cluster_wait();
  const uint32_t rsb = sb ^ RANK_BIT;

  uint32_t tref = 0;
#pragma unroll 1
  for (int n = 0; n <= NSEG; n++) {
    const bool more = __builtin_expect(s + 1 < NSEG, 1);
    uint32_t zr = loop_zero<0>(n);
    bool xok = false;
    if (__builtin_expect(s >= 0, 1)) {
      if (__builtin_expect(s > 0, 1)) {
        const uint32_t dst = sb + OFF_MEM + WG * 8192 + t16 + ((lv >> 5) & 12);
        uint32_t tries = zr;
#pragma unroll 1
        do {
          if (tries) { const char* src = gptr(xhi, xm + WG * 8192 + slot_off(sv)); tref += T_SLIP; WAIT_UNTIL(tref, aV[0], 1, -1); gather_issue(sb + OFF_MEM + WG * 8192 + tv, src); }
          KEEPALIVE(aV[0], zr);
          cp_async_wait_group<0>();
        } while (gather_incomplete<1, 0>(dst) && ++tries < POLL_LIMIT);
        named_bar(1 + WG, 128);
      }
      const uint32_t a_mem = sb + OFF_MEM + WG * 8192 + l16;
      float c[2][4];
      c[0][0] = c[0][1] = c[0][2] = c[0][3] = c[1][0] = c[1][1] = c[1][2] = c[1][3] = 0.f;
      constexpr int NBUF = (48 - 8 - 4 * O_FIX) / 4;
      uint32_t b[NBUF][4];
#pragma unroll
      for (int p = 0; p < NBUF - 1; p++) ldsm_x4_t(b[p], a_mem + p * 512);
#pragma unroll
      for (int p = 0; p < 16; p++) {
        if (p + NBUF - 1 < 16) ldsm_x4_t(b[(p + NBUF - 1) % NBUF], a_mem + (p + NBUF - 1) * 512);
        if (p < 8) { mma16816(c[0], aV[2 * p], b[p % NBUF][0], b[p % NBUF][1]); mma16816(c[1], aV[2 * p + 1], b[p % NBUF][2], b[p % NBUF][3]); }
        else { mma16816(c[0], rot[2 * p - 16], b[p % NBUF][0], b[p % NBUF][1]); mma16816(c[1], rot[2 * p - 15], b[p % NBUF][2], b[p % NBUF][3]); }
      }
      xok = mbar_test(sb + BAR_X + 8 * WG, n & 1);
      SFENCE(15);
      const float4 own = make_float4(c[0][0] + c[1][0], c[0][1] + c[1][1], c[0][2] + c[1][2], c[0][3] + c[1][3]);
      NEWZ(1);
      const uint32_t pvm = WG == 0 ? xvm + slot_off(sv) : 0;
      if (WG == 1) sts128f(sb + OFF_VPX + wq * 512 + l16, own);
      named_bar(3, 256);
      if (WG == 0) {
        const float4 o = lds128f(sb + OFF_VPX + wq * 512 + l16);
        st_relaxed2(gptr(xhi, pvm), pack_bf16(own.x + o.x, own.y + o.y), pack_bf16(own.z + o.z, own.w + o.w));
      }
    }
    auto token_pv = [&](int seg, bool staged) {
      constexpr int NU = 2 - WG;
      uint4 pt0, pt1, v0[NU], v1[NU]; uint32_t pm0, pm1; uint2 vm[NU];
      const uint32_t ap = l16 + WG * 4096 + xo::PT, am = (lv >> 2) + WG * 4096 + xo::PM;
      const uint32_t at = ovt - WG * 512;
      if (staged) {
        const uint32_t b = sb + OFF_MEM;
        pt0 = lds128(b + ap); pt1 = lds128(b + ap + 2048); pm0 = lds32(b + am); pm1 = lds32(b + am + 2048);
#pragma unroll
        for (int u = 0; u < NU; u++) { v0[u] = lds128(b + at - u * 2048); v1[u] = lds128(b + at + 512 - u * 2048); vm[u] = lds64(b + ovm - u * 2048); }
      } else {
        const uint32_t b = lds32(sb + CT_HEAD) + slot_off(seg);
        pt0.x = EMPTY;
#pragma unroll
        for (int u = 0; u < NU; u++) {
          v0[u] = ld_relaxed4(gptr(xhi, b + at) - u * 2048); v1[u] = ld_relaxed4(gptr(xhi, b + at) + 512 - u * 2048);
          vm[u] = ld_relaxed2(gptr(xhi, b + ovm) - u * 2048);
        }
      }
      const bool odd = lv & 16;
      char* op = gptr(xhi, lds32(sb + CT_O) + (seg * SEG + WG * 16 + (lv >> 6)) * (HD * 2) + wq * 32 + (lv & 16) + ((lv >> 2) & 8));
      if (!staged || __builtin_expect(warp_incomplete(umax4(pt0.x, pt1.x, pm0, pm1)), 0)) {
        const uint32_t b = lds32(sb + CT_HEAD) + slot_off(seg);
        uint32_t tries = zr;
#pragma unroll 1
        do {
          pt0 = ld_relaxed4(gptr(xhi, b + ap)); pt1 = ld_relaxed4(gptr(xhi, b + ap) + 2048);
          pm0 = ld_relaxed1(gptr(xhi, b + am)); pm1 = ld_relaxed1(gptr(xhi, b + am) + 2048);
        } while (warp_incomplete(umax4(pt0.x, pt1.x, pm0, pm1)) && ++tries < POLL_LIMIT);
      }
      const uint32_t pa[4] = {pt0.x, pt1.x, pt0.y, pt1.y}, pb[4] = {pt0.z, pt1.z, pt0.w, pt1.w};
#pragma unroll
      for (int u = 0; u < NU; u++) {
        float o0[4] = {0.f, 0.f, 0.f, 0.f}, o1[4] = {0.f, 0.f, 0.f, 0.f};
        mma1688(o0, pm0, pm1, vm[u].x); mma1688(o1, pm0, pm1, vm[u].y);
        mma16816(o0, pa, v0[u].x, v0[u].y); mma16816(o1, pa, v1[u].x, v1[u].y);
        if (WG) { mma16816(o0, pb, v0[u].z, v0[u].w); mma16816(o1, pb, v1[u].z, v1[u].w); }
#pragma unroll
        for (int r = 0; r < 2; r++) {
          const uint32_t w0 = pack_bf16(o0[2 * r], o0[2 * r + 1]), w1 = pack_bf16(o1[2 * r], o1[2 * r + 1]);
          const uint32_t rv = __shfl_xor_sync(~0u, odd ? w0 : w1, 1);
          asm volatile("st.global.v2.u32 [%0], {%1, %2};" ::"l"(op + r * 8 * HD * 2 - u * 64), "r"(odd ? rv : w0), "r"(odd ? w1 : rv) : "memory");
        }
      }
    };
    if (!more) {
      named_bar(3, 256);
      if (upper_warps) {
#pragma unroll 1
        for (int seg = NSEG - 2; seg < NSEG; seg++) token_pv(seg, false);
      }
      break;
    }
    {
      if (__builtin_expect(s > 0, 1)) {
        const uint32_t o = WG ? ovt - 512 : tv + 512;
        const char* src = gptr(xhi, lds32(sb + CT_HEAD) + slot_off(sv - 1) + o);
#pragma unroll
        for (int i = 0; i < 3 - WG; i++) cp_async16(sb + OFF_MEM + o + i * 512, src + i * 512);
        cp_async_commit();
      }
      bool xw;
      {
        float acc[16];
        if (__builtin_expect(!xok, 0)) mbar_wait<0>(sb + BAR_X + 8 * WG, (s + 1) & 1);
        wg_fence();
#pragma unroll
        for (int ks = 0; ks < 16; ks++) wgmma_m64n32_rs(acc, rot[ks], xdesc<WG>(16 + ks), ks != 0);
        wg_commit();
#pragma unroll
        for (int ks = 0; ks < 16; ks++) wgmma_m64n32_rs(acc, aV[ks], xdesc<WG>(ks), 1);
        wg_commit();
        NEWZ(2);
        xw = warp_is(3) && s + 2 < NSEG;
        tref += lds32(sb + CT_T + 4) + (WG * T_LAG - T_SLIP);
        const uint32_t pvt = xvt + slot_off(sv + 1), awo = sb + wo_addr(tv);
        if (WG == 0 && warp_is(1) && s >= 0) expect_elect(sb + BAR_EX, 512);
        if (xw) {
          expect_elect(sb + BAR_X + 8 * WG, 32768);
          if (WG == 1 && s == NSEG - 3) asm volatile("griddepcontrol.launch_dependents;");
          if (WG == 1 && s + 5 < NSEG) prefetch_l2(maps.xp + (s + 5) * 65536 + lds32(sb + CT_PF), 1024);
        }
        wg_wait<1>();
        if (xw) { named_bar(4 + WG, 128); issue_x(sb, &maps.xq, s + 2, WG, 1); }
        else if (s + 2 < NSEG) named_bar_arrive(4 + WG, 128);
        if (__builtin_expect(s == 0, 0)) {
          mbar_wait(sb + BAR_P + 16, 0);
#pragma unroll
          for (int ks = 16 - O_FIX; ks < 16; ks++) ldsm_x4_t(bO[ks], (awo ^ 32) + (ks & 7) * 1024);
        }
#pragma unroll
        for (int ks = 0; ks < 16 - O_FIX; ks++) ldsm_x4_t(bO[ks], (ks < 8 ? awo : awo ^ 32) + (ks & 7) * 1024);
        wg_wait<0>();
        acc_fence(acc);
        constexpr int K = WG * 2, G = 2 - K;
        sts128f(sb + OFF_RED + WG * 1024 + t16, make_float4(acc[G], acc[G + 1], acc[4 + G], acc[5 + G]));
        sts128f(sb + OFF_RED + WG * 1024 + 512 + t16, make_float4(acc[8 + G], acc[9 + G], acc[12 + G], acc[13 + G]));
        cp_async_wait_group<0>();
        named_bar(3, 256);
        const float4 o0 = lds128f(sb + OFF_RED + (WG ^ 1) * 1024 + t16), o1 = lds128f(sb + OFF_RED + (WG ^ 1) * 1024 + 512 + t16);
        st_relaxed4(gptr(xhi, pvt),
                    pack_bf16(acc[K] + o0.x, acc[K + 1] + o0.y), pack_bf16(acc[4 + K] + o0.z, acc[5 + K] + o0.w),
                    pack_bf16(acc[8 + K] + o1.x, acc[9 + K] + o1.y), pack_bf16(acc[12 + K] + o1.z, acc[13 + K] + o1.w));
      }
      if (__builtin_expect(s >= 0, 1)) {
        uint32_t tries = 0;
#pragma unroll
        for (int ks = 0; ks < 16 - O_FIX; ks++) tries |= bO[ks][0];
        const char* po = gptr(xhi, xom + slot_off(sv) + (tries & zr));
        tries = zr;
        float d[2][2][4];
        uint32_t mx;
#pragma unroll 1
        do {
          tref += T_SLIP;
          WAIT_UNTIL(tref, aV[0], 1, 1);
          uint4 o[8];
#pragma unroll
          for (int i = 0; i < 4; i++) o[i] = ld_relaxed4(po + i * 512);
#pragma unroll
          for (int i = 0; i < 4; i++) o[4 + i] = ld_relaxed4(po + 16384 + i * 512);
          __syncwarp();
#pragma unroll
          for (int i = 0; i < 2; i++)
#pragma unroll
            for (int q = 0; q < 2; q++) { d[i][q][0] = d[i][q][1] = d[i][q][2] = d[i][q][3] = 0.f; }
#pragma unroll
          for (int i = 0; i < 4; i++) {
            mma16816(d[0][0], aO[2 * i], o[i].x, o[i].y); mma16816(d[1][0], aO[8 + 2 * i], o[i].x, o[i].y);
            mma16816(d[0][1], aO[2 * i + 1], o[i].z, o[i].w); mma16816(d[1][1], aO[9 + 2 * i], o[i].z, o[i].w);
          }
          mx = umax4(o[0].w, o[1].w, o[2].w, o[3].w);
          SFENCE(33 + tries);
#pragma unroll
          for (int i = 0; i < 4; i++) {
            mma16816(d[0][0], bO[2 * i], o[4 + i].x, o[4 + i].y); mma16816(d[1][0], bO[8 + 2 * i], o[4 + i].x, o[4 + i].y);
            mma16816(d[0][1], bO[2 * i + 1], o[4 + i].z, o[4 + i].w); mma16816(d[1][1], bO[9 + 2 * i], o[4 + i].z, o[4 + i].w);
          }
          mx = max(mx, umax4(o[4].w, o[5].w, o[6].w, o[7].w));
        } while (warp_incomplete(mx) && ++tries < POLL_LIMIT);
        NEWZ(3);
        const uint32_t rd = sb + OFF_RED + (WG ^ 1) * 1024 + t16;
        sts128f(rd, make_float4(d[0][0][0] + d[0][1][0], d[0][0][1] + d[0][1][1], d[0][0][2] + d[0][1][2], d[0][0][3] + d[0][1][3]));
        sts128f(rd + 512, make_float4(d[1][0][0] + d[1][1][0], d[1][0][1] + d[1][1][1], d[1][0][2] + d[1][1][2], d[1][0][3] + d[1][1][3]));
        if (upper_warps) {
          named_bar_arrive(7, 256);
          if (xw) issue_x(sb, &maps.xq, s + 2, WG, 0);
          if (__builtin_expect(s > 0, 1)) token_pv(sv - 1, true);
        } else {
          uint32_t mp = lds32(sb + CT_MP) + (lv >> 2);
          named_bar(7, 256);
          float4 p[8];
#pragma unroll
          for (int i = 0; i < 8; i++) p[i] = lds128f(sb + OFF_RED + lv + wq * 512 + i * 1024);
          float4 r;
          r.x = ((p[0].x + p[1].x) + (p[2].x + p[3].x)) + ((p[4].x + p[5].x) + (p[6].x + p[7].x));
          r.y = ((p[0].y + p[1].y) + (p[2].y + p[3].y)) + ((p[4].y + p[5].y) + (p[6].y + p[7].y));
          r.z = ((p[0].z + p[1].z) + (p[2].z + p[3].z)) + ((p[4].z + p[5].z) + (p[6].z + p[7].z));
          r.w = ((p[0].w + p[1].w) + (p[2].w + p[3].w)) + ((p[4].w + p[5].w) + (p[6].w + p[7].w));
          const bool w0 = warp_is(0);
          if (w0) st_async4(rsb + OFF_RX + lv, __float_as_uint(r.x), __float_as_uint(r.y), __float_as_uint(r.z), __float_as_uint(r.w), rsb + BAR_EX);
          if (!w0) {
            char* pp = gptr(xhi, mp + slot_off(sv + 1));
            mbar_wait(sb + BAR_EX, s & 1);
            const float4 q = lds128f(sb + OFF_RX + l16);
            st_relaxed1(pp, pack_bf16(r.x + q.x, r.y + q.y)); st_relaxed1(pp + 128, pack_bf16(r.z + q.z, r.w + q.w));
            pp = gptr(xhi, mp + slot_off(sv + 3));
            st_relaxed1(pp, EMPTY); st_relaxed1(pp + 128, EMPTY);
          }
        }
        NEWZ(4);
        const char* src = gptr(xhi, xm + WG * 8192 + slot_off(sv + 1));
        const uint32_t awv = sb + wv_addr(tv) + OFF_WVR;
        tref += lds32(sb + CT_T + 8) - WG * T_LAG;
        named_bar(8, 256);
#pragma unroll
        for (int ks = 0; ks < V_PRE; ks++) ldsm_x4_t(rot[ks], awv + ks * 2048);
        WAIT_UNTIL(tref, aV[0], 1, 2);
        gather_issue(sb + OFF_MEM + WG * 8192 + tv, src);
#pragma unroll
        for (int ks = V_PRE; ks < 16; ks++) ldsm_x4_t(rot[ks], awv + ks * 2048);
        NEWZ(6);
        st_relaxed4(gptr(xhi, xvt + slot_off(sv + 2)), EMPTY, EMPTY, EMPTY, EMPTY);
        if (WG == 0) st_relaxed2(gptr(xhi, xvm + slot_off(sv + 2)), EMPTY, EMPTY);
      } else {
        load_v(tv);
        if (xw) issue_x(sb, &maps.xq, s + 2, WG, 0);
        mbar_wait(sb + BAR_P + 8, 0);
#pragma unroll
        for (int ks = 0; ks < 8; ks++) { ldsm_x4_t(aO[ks], sb + wo_addr(tv) + ks * 1024); ldsm_x4_t(aO[8 + ks], sb + (wo_addr(tv) ^ 32) + ks * 1024); }
        named_bar(0, 256);
        if (threadIdx.x == 0) {
          fence_async_smem();
          mbar_expect_tx(sb + BAR_P + 16, 4 * 16384);
          for (int q = 0; q < 4; q++) tma_load_2d(sb + OFF_WOR + q * 16384, &maps.wo, h * 32, j * 2048 + 1024 + q * 256, sb + BAR_P + 16);
        }
        __syncwarp();
        tref = gtime() / T_SLIP * T_SLIP - T_SLIP;
      }
    }
  }
}

#undef j
#undef s
#undef sv
#undef xm
#undef wq

__global__ void __launch_bounds__(256, 1) __cluster_dims__(2, 1, 1)
chain_kernel(const __grid_constant__ ChainMaps maps, const bf16* __restrict__ mem0, const uint64_t xbase) {
  using namespace chain;
  extern __shared__ uint8_t smem_raw[];
  uint32_t sb = smem_u32(smem_raw);
  PIN(sb);
  if (sb != SB_LO + (blockIdx.x & 1) * RANK_BIT || mapa(sb, (blockIdx.x & 1) ^ 1) != (sb ^ RANK_BIT)) __trap();
  const int tid = threadIdx.x;
  const int h = blockIdx.x >> 2, role = (blockIdx.x >> 1) & 1, j = blockIdx.x & 1;
  if (tid == 0) {
    for (int i = 0; i < 9; i++) mbar_init(sb + OFF_BAR + 8 * i, 1);
    asm volatile("fence.mbarrier_init.release.cluster;" ::: "memory");
    const uint32_t xl = (uint32_t)xbase;
    sts32(sb + CT_BASE, xl); sts32(sb + CT_HEAD, xl + h * xo::HEAD); sts32(sb + CT_OM, xl + xo::OM + (role ? j * 32768 : h * 2048));
    sts32(sb + CT_MP, xl + xo::MEM + (h * 2 + j) * 256); sts32(sb + CT_O, xl + xo::O + (h * 2 + j) * 128); sts32(sb + CT_PF, (h * 2 + j) * 1024);
    sts32(sb + CT_TT, sb + (j ? OFF_KT : OFF_QT));
    if (role == 0) {
      const CUtensorMap* wm = j ? &maps.wk : &maps.wq;
      mbar_expect_tx(sb + BAR_P, 6 * 16384);
      for (int c = 0; c < 3; c++)
        for (int q = 0; q < 2; q++) tma_load_2d(sb + OFF_X + (q * 3 + c) * 16384, wm, h * DH + q * 64, q * 512 + c * 128, sb + BAR_P);
      mbar_expect_tx(sb + BAR_P + 8, 4 * 16384);
      for (int c = 0; c < 2; c++)
        for (int q = 0; q < 2; q++) tma_load_2d(sb + OFF_X + (6 + q * 2 + c) * 16384, wm, h * DH + (q ^ 1) * 64, q * 512 + c * 128, sb + BAR_P + 8);
      mbar_expect_tx(sb + BAR_P + 24, 4 * 16384);
      for (int q = 0; q < 2; q++)
        for (int o = 0; o < 2; o++) tma_load_2d(sb + OFF_WS + (q * 2 + o) * 16384, wm, h * DH + (q ^ o) * 64, q * 512 + 384, sb + BAR_P + 24);
      for (int q = 0; q < 2; q++) tma_prefetch_2d(wm, h * DH + (q ^ 1) * 64, q * 512 + 256);
    } else {
      mbar_expect_tx(sb + BAR_P, 8 * 16384);
      for (int q = 0; q < 4; q++) tma_load_2d(sb + OFF_WOR + q * 16384, &maps.wv, h * DH + j * 64, (q >> 1) * 512 + (q & 1) * 128, sb + BAR_P);
      for (int q = 0; q < 4; q++) tma_load_2d(sb + OFF_WVR + q * 16384, &maps.wv, h * DH + j * 64, (q >> 1) * 512 + 256 + (q & 1) * 128, sb + BAR_P);
    }
  }
  for (int r = 0; r < RING; r++) {
    char* p = (char*)xbase + r * xo::SLOT;
    const int wq = (tid >> 5) & 3;
    if (role == 1) st_relaxed4(p + h * xo::HEAD + xo::VT + (8 * j + 2 * wq + (tid >> 7)) * 512 + (tid & 31) * 16, EMPTY, EMPTY, EMPTY, EMPTY);
    else if (j == 0) st_relaxed4(p + (tid < 128 ? xo::OM + h * 2048 + tid * 16 : h * xo::HEAD + wq * 2048 + xo::VM + (tid & 31) * 16), EMPTY, EMPTY, EMPTY, EMPTY);
    else {
      st_relaxed4(p + h * xo::HEAD + (tid >> 6) * 2048 + 1024 + (tid & 63) * 16, EMPTY, EMPTY, EMPTY, EMPTY);
      if (tid < 32) st_relaxed4(p + xo::MEM + h * 512 + tid * 16, EMPTY, EMPTY, EMPTY, EMPTY);
    }
  }
  __syncthreads();
  if (__shfl_sync(0xffffffffu, tid >> 5, 0) == 0) {
    uint32_t t[2], c[2], ka[4] = {0, 0, 0, 0};
    const uint32_t z = maps.t_step >> 24;
#pragma unroll
    for (int i = 0; i < 2; i++) {
      const uint32_t end = (gtime() & ~31u) + (i ? 2048 : 1024);
      for (int g = z; g < 256 && (int)(gtime() - (end - 96)) < 0; g++) KEEPALIVE(ka, z);
      for (int g = z; g < 256 && (int)((t[i] = gtime()) - end) < 0; g++) {}
      c[i] = (uint32_t)clock64();
    }
    uint32_t v = 0, target = 0;
    if (tid == 0) {
      st_relaxed1(&g_rate[blockIdx.x], (t[1] - t[0]) * 4096u / (c[1] - c[0]));
      __threadfence();
      target = (atomicAdd(&g_epoch, 1u) & ~127u) + 128u;
    }
    target = __shfl_sync(0xffffffffu, target, 0);
    int guard = 0;
    do { asm volatile("ld.acquire.gpu.global.u32 %0, [%1];" : "=r"(v) : "l"(&g_epoch) : "memory"); }
    while (__any_sync(0xffffffffu, (int)(v - target) < 0) && ++guard < (1 << 20));
    const uint4 r4 = ld_relaxed4(&g_rate[tid * 4]);
    uint32_t r = min(__reduce_max_sync(0xffffffffu, umax4(r4.x, r4.y, r4.z, r4.w)), 4 * RATE0);
    if (r < RATE0 + 28) r = RATE0;
    const uint32_t a = (maps.t_step * r / RATE0 + 31) & ~31u, b = (maps.t_phase * r / RATE0 + 31) & ~31u;
    sts128(sb + CT_T, make_uint4(a, b, a - b, r));
  }
  const uint32_t xhi = (uint32_t)(xbase >> 32);
  const int wg = __shfl_sync(0xffffffffu, tid >> 7, 0);
  if (role == 0) {
    if (wg == 0) role_a<0>(maps, mem0, sb, xhi); else role_a<1>(maps, mem0, sb, xhi);
  } else {
    if (wg == 0) role_v<0>(maps, mem0, sb, xhi); else role_v<1>(maps, mem0, sb, xhi);
  }
  __syncwarp();
  cluster_arrive();
  cluster_wait();
}

struct BMaps {
  CUtensorMap q, k, v, out, k8;
  const bf16 *shift_k, *ssm_k, *ssm_D;
};

#define B_SLEEP 200
namespace bp {
constexpr int U_PITCH = (2048 + 128) * 2 + 16;
constexpr int KR_WORDS = 1048;
constexpr int KR_PITCH = 8704;
constexpr int OFF_U = 0;
constexpr int OFF_KR = (8 * U_PITCH + 127) / 128 * 128;
constexpr int Q_OFF = 4352;
constexpr int OFF_BAR = OFF_KR + 8 * KR_PITCH;
constexpr int GROUP_BYTES = OFF_BAR + 128;
constexpr int SMEM = 2 * GROUP_BYTES + 128;
constexpr int NTASK = DM / 8;
static_assert(Q_OFF >= 4224 && Q_OFF + 4096 <= KR_PITCH, "staging does not fit");
}

__device__ __forceinline__ uint32_t bmul2(uint32_t a, uint32_t b) { uint32_t r; asm("mul.rn.bf16x2 %0, %1, %2;" : "=r"(r) : "r"(a), "r"(b)); return r; }
__device__ __forceinline__ uint32_t badd2(uint32_t a, uint32_t b) { uint32_t r; asm("add.rn.bf16x2 %0, %1, %2;" : "=r"(r) : "r"(a), "r"(b)); return r; }

__device__ __forceinline__ void mbar_wait_sleep(uint32_t bar, uint32_t parity) {
  int guard = 0;
  while (!mbar_try(bar, parity)) { __nanosleep(B_SLEEP); if (++guard > (1 << 22)) __trap(); }
}

__device__ __forceinline__ void bpart_body(const BMaps& maps, int first, int stride, int end) {
  using namespace bp;
  extern __shared__ uint8_t smem_all[];
  const int grp = __shfl_sync(0xffffffffu, threadIdx.x >> 8, 0);
  const int lane = keep(threadIdx.x & 31), g = lane >> 2, t = lane & 3;
  const int w = __shfl_sync(0xffffffffu, (threadIdx.x >> 5) & 7, 0);
  const uint32_t sb = ((smem_u32(smem_all) + 127) & ~127u) + grp * GROUP_BYTES;
  const uint32_t kr = sb + OFF_KR + w * KR_PITCH, bar_k = sb + OFF_BAR + 8 * w, bar_q = bar_k + 64;
  if (lane == 0) { mbar_init(bar_k, 1); mbar_init(bar_q, 1); asm volatile("fence.mbarrier_init.release.cluster;" ::: "memory"); }
  if (lane < 16) sts128(sb + OFF_U + w * U_PITCH + lane * 16, make_uint4(0, 0, 0, 0));
  __syncwarp();
  if (grp == 1) { named_bar_arrive(3, 512); named_bar(5, 512); }
  const int lm = lane >> 3, lr = lane & 7;
  uint32_t ph = 0;
  for (int task = first + grp; task < end; task += stride, ph ^= 1) {
    const int d0 = task * 8;
    uint4 x[8];
    {
      const uint4* kf = (const uint4*)(maps.ssm_k + (size_t)(d0 + w) * S_LEN);
#pragma unroll
      for (int it = 0; it < 8; it++) x[it] = __ldg(kf + it * 32 + lane);
    }
    const uint4 ska = __ldg((const uint4*)(maps.shift_k + (d0 + 2 * t) * 4));
    __syncwarp();
    if (lane == 0) {
      mbar_expect_tx(bar_k, 2 * 4096 + 128);
      tma_load_2d(kr + 4096, &maps.k8, d0, w * 256 + 248, bar_k);
      tma_load_2d(kr, &maps.k, d0, w * 256 - 8, bar_k);
      bulk_wait_read<0>();
      tma_load_2d(kr + Q_OFF, &maps.v, d0, w * 256, bar_k);
    }
    __syncwarp();
    if (task == first) named_bar_arrive(5, 512);
    const uint32_t sk[4] = {__byte_perm(ska.x, ska.z, 0x5410), __byte_perm(ska.x, ska.z, 0x7632), __byte_perm(ska.y, ska.w, 0x5410), __byte_perm(ska.y, ska.w, 0x7632)};
    mbar_wait_sleep(bar_k, ph);
    {
      const uint32_t ka = kr + (lane + 8) * 16;
#pragma unroll
      for (int i = 0; i < 8; i++) {
        uint32_t k0[4], k1[4], k2[4], k3[4], v[4], r[4];
        ldsm_x4(k3, ka + i * 512 - 48); ldsm_x4(k2, ka + i * 512 - 32); ldsm_x4(k1, ka + i * 512 - 16); ldsm_x4(k0, ka + i * 512);
        ldsm_x4(v, ka + (Q_OFF - 128) + i * 512);
#pragma unroll
        for (int b = 0; b < 4; b++) {
          uint32_t acc = bmul2(k3[b], sk[3]);
          acc = badd2(acc, bmul2(k2[b], sk[2]));
          acc = badd2(acc, bmul2(k1[b], sk[1]));
          acc = badd2(acc, bmul2(k0[b], sk[0]));
          r[b] = bmul2(acc, v[b]);
        }
        const int ch = 16 + w * 32 + i * 4 + lm;
        stsm_x4_t(sb + OFF_U + lr * U_PITCH + ((ch ^ ((ch >> 3) & 1)) << 4), r[0], r[1], r[2], r[3]);
      }
    }
    __syncwarp();
    {
      const uint32_t c0 = kr, c1 = c0 + (KR_WORDS + 16) * 4;
      uint32_t carry = 0;
#pragma unroll
      for (int it = 0; it < 8; it++) {
        const int blk = it * 32 + lane;
        uint32_t prev = __shfl_up_sync(0xffffffffu, x[it].w, 1);
        if (lane == 0) prev = carry;
        carry = __shfl_sync(0xffffffffu, x[it].w, 31);
        sts128(c0 + (1028 - 4 * blk) * 4, make_uint4(__byte_perm(x[it].w, 0, 0x1032), __byte_perm(x[it].z, 0, 0x1032),
                                                     __byte_perm(x[it].y, 0, 0x1032), __byte_perm(x[it].x, 0, 0x1032)));
        sts128(c1 + (1028 - 4 * blk) * 4, make_uint4(__byte_perm(x[it].w, x[it].z, 0x7610), __byte_perm(x[it].z, x[it].y, 0x7610),
                                                     __byte_perm(x[it].y, x[it].x, 0x7610), __byte_perm(x[it].x, prev, 0x7610)));
      }
      if (lane < 4) { sts128(c0 + (1032 + 4 * lane) * 4, make_uint4(0, 0, 0, 0)); sts128(c1 + (1032 + 4 * lane) * 4, make_uint4(0, 0, 0, 0)); }
      __syncwarp();
    }
    named_bar(3 + grp, 512);
    float acc[16][4];
#pragma unroll
    for (int jn = 0; jn < 16; jn++) { acc[jn][0] = acc[jn][1] = acc[jn][2] = acc[jn][3] = 0.f; }
    {
      const uint32_t ub = sb + OFF_U + w * U_PITCH;
      uint32_t kd = kr + (((g & 1) ? 0 : KR_WORDS + 16) + ((((g & 1) ? 2063 : 2062) - (g - 2 * t)) >> 1)) * 4;
      uint32_t uc = 2 * (8 + lr + (lm >> 1) * 8) + (lm & 1);
#pragma unroll 1
      for (int d0s = 0; d0s < 8; d0s++, kd -= 32, uc -= 2) {
        const uint32_t uf = ub + ((uc ^ ((uc >> 3) & 1)) << 4);
        uint32_t A[3][4];
        A[0][0] = lds32v(kd); A[0][1] = lds32v(kd - 16); A[0][2] = lds32v(kd + 16); A[0][3] = lds32v(kd);
        uint32_t F[8][4];
#pragma unroll
        for (int m = 7; m >= 0; m--) ldsm_x4(F[m], uf + m * 512);
#pragma unroll
        for (int i = 0; i < 16; i++) {
          if (i + 1 < 16) {
            A[(i + 1) % 3][0] = lds32v(kd - 256 * (i + 1)); A[(i + 1) % 3][1] = lds32v(kd - 256 * (i + 1) - 16);
            A[(i + 1) % 3][2] = lds32v(kd - 256 * (i + 1) + 16); A[(i + 1) % 3][3] = lds32v(kd - 256 * (i + 1));
          }
#pragma unroll
          for (int jn = 15; jn >= i; jn--) mma16816(acc[jn], A[i % 3], F[(jn - i) >> 1][((jn - i) & 1) * 2], F[(jn - i) >> 1][((jn - i) & 1) * 2 + 1]);
        }
      }
    }
    named_bar_arrive(3 + (grp ^ 1), 512);
    __syncwarp();
    fence_async_smem();
    __syncwarp();
    if (lane == 0) { mbar_expect_tx(bar_q, 4096); tma_load_2d(kr + Q_OFF, &maps.q, d0, w * 256, bar_q); }
    const uint32_t dpair = __ldg((const uint32_t*)(maps.ssm_D + d0) + t);
    {
      const uint32_t ya = kr + w * 16 + (((lm >> 1) * 8 + lr) * 32) + (lm & 1) * 16;
#pragma unroll
      for (int jn = 0; jn < 16; jn += 2)
        stsm_x4_t(ya + jn * 256, pack_bf16(acc[jn][0], acc[jn][1]), pack_bf16(acc[jn][2], acc[jn][3]),
                  pack_bf16(acc[jn + 1][0], acc[jn + 1][1]), pack_bf16(acc[jn + 1][2], acc[jn + 1][3]));
    }
    named_bar(1 + grp, 256);
    mbar_wait_sleep(bar_q, ph);
    {
      const uint32_t ya = sb + OFF_KR + lr * (KR_PITCH + 16) + (w * 256 + lm * 8) * 2;
#pragma unroll
      for (int i = 0; i < 8; i++) {
        uint32_t y[4], u[4], q[4], r[4];
        ldsm_x4(q, kr + Q_OFF + lane * 16 + i * 512);
        ldsm_x4_t(y, ya + i * 64);
        const int ch = 16 + w * 32 + i * 4 + lm;
        ldsm_x4_t(u, sb + OFF_U + lr * U_PITCH + ((ch ^ ((ch >> 3) & 1)) << 4));
#pragma unroll
        for (int b = 0; b < 4; b++) r[b] = bmul2(q[b], badd2(y[b], bmul2(u[b], dpair)));
        stsm_x4(kr + Q_OFF + lane * 16 + i * 512, r[0], r[1], r[2], r[3]);
      }
      fence_async_smem();
      __syncwarp();
      if (lane == 0) { tma_store_2d(&maps.out, kr + Q_OFF, DM + d0, w * 256); bulk_commit(); }
    }
    named_bar(1 + grp, 256);
  }
  if (lane == 0) bulk_wait<0>();
}

__global__ void __launch_bounds__(512, 1) __cluster_dims__(2, 1, 1) bpart_kernel(const __grid_constant__ BMaps maps, int end) {
  bpart_body(maps, blockIdx.x * 2, gridDim.x * 2, end);
}

struct GemmMaps {
  CUtensorMap o;
  CUtensorMap w;
  CUtensorMap c;
};
namespace k3 {
constexpr int STAGES = 6;
constexpr int W_BYTES = 2 * 8192, O_BYTES = K3_N * 128, STAGE_BYTES = W_BYTES + O_BYTES;
constexpr int TT = (S_LEN + K3_N - 1) / K3_N, NGEMM = TT * (DM / 128), NB = 128 - NGEMM, KSTEPS = HD / 64;
constexpr int SMEM_G = STAGES * STAGE_BYTES + 1024 + 256;
constexpr int SMEM = SMEM_G > bp::SMEM ? SMEM_G : bp::SMEM;
static_assert(STAGE_BYTES % 1024 == 0, "swizzle atoms");
}

__global__ void __launch_bounds__(512, 1)
tail_kernel(const __grid_constant__ GemmMaps maps, const __grid_constant__ BMaps bmaps) {
  using namespace k3;
  if (blockIdx.x < NB) {
    bpart_body(bmaps, bp::NTASK - 2 * NB + 2 * blockIdx.x, bp::NTASK, bp::NTASK);
    return;
  }
  extern __shared__ uint8_t smem_raw[];
  const uint32_t sbase = (smem_u32(smem_raw) + 1023) & ~1023u;
  const uint32_t bars = sbase + STAGES * STAGE_BYTES;
  const int tid = threadIdx.x, warp = tid >> 5;
  const int tt = (blockIdx.x - NB) / 8, ct = (blockIdx.x - NB) % 8;

  if (tid == 0) {
    for (int s = 0; s < STAGES; s++) { mbar_init(bars + 8 * s, 1); mbar_init(bars + 8 * (STAGES + s), 2); }
    asm volatile("fence.mbarrier_init.release.cluster;" ::: "memory");
  }
  __syncthreads();

  if (warp >= 8) {
    if (tid == 256) {
      tma_prefetch_desc(&maps.o);
      for (int k = 0; k < STAGES; k++) {
        const uint32_t full = bars + 8 * k, sa = sbase + k * STAGE_BYTES;
        mbar_expect_tx(full, STAGE_BYTES);
#pragma unroll
        for (int j = 0; j < 2; j++) tma_load_2d(sa + j * 8192, &maps.w, ct * 128 + j * 64, k * 64, full);
      }
      asm volatile("griddepcontrol.wait;" ::: "memory");
      int stage = 0; uint32_t ph = 1;
      for (int k = 0; k < KSTEPS; k++) {
        mbar_wait(bars + 8 * (STAGES + stage), ph);
        const uint32_t full = bars + 8 * stage, sa = sbase + stage * STAGE_BYTES;
        const bool pre = k < STAGES;
        if (!pre) mbar_expect_tx(full, STAGE_BYTES);
        tma_load_2d(sa + W_BYTES, &maps.o, k * 64, tt * K3_N, full);
        if (!pre) {
#pragma unroll
          for (int j = 0; j < 2; j++) tma_load_2d(sa + j * 8192, &maps.w, ct * 128 + j * 64, k * 64, full);
        }
        if (++stage == STAGES) { stage = 0; ph ^= 1; }
      }
    }
  } else {
    const int wg = warp >> 2, lane = tid & 31, wq = warp & 3;
    int stage = 0; uint32_t ph = 0;
    float acc[K3_N / 2];
    int prev = -1;
    for (int k = 0; k < KSTEPS; k++) {
      mbar_wait(bars + 8 * stage, ph);
      const uint32_t sa = sbase + stage * STAGE_BYTES;
      wg_fence();
#pragma unroll
      for (int kk = 0; kk < 4; kk++) {
        const uint64_t da = make_desc(sa + wg * 8192 + kk * 2048, 16, 1024, 1);
        const uint64_t db = make_desc(sa + W_BYTES + kk * 32, 16, 1024, 1);
        wgmma_k3_ss_ta(acc, da, db, (k | kk) != 0);
      }
      wg_commit();
      if (prev >= 0) { wg_wait<1>(); if ((tid & 127) == 0) mbar_arrive(bars + 8 * (STAGES + prev)); }
      prev = stage;
      if (++stage == STAGES) { stage = 0; ph ^= 1; }
    }
    wg_wait<0>();
#pragma unroll
    for (int i = 0; i < K3_N / 2; i++) asm volatile("" : "+f"(acc[i]) :: "memory");
    named_bar(1, 256);
    const uint32_t ebuf = sbase + wg * STAGE_BYTES;
    const uint32_t ea = ebuf + ((lane >> 4) * 8 + (lane & 7)) * 128 + (((2 * wq + ((lane >> 3) & 1)) ^ (lane & 7)) << 4);
#pragma unroll
    for (int i = 0; i < K3_N / 8; i += 2) {
      const int i1 = i + 1 < K3_N / 8 ? i + 1 : i;
      stsm_x4_t(ea + i * 1024, pack_bf16(acc[4 * i], acc[4 * i + 1]), pack_bf16(acc[4 * i + 2], acc[4 * i + 3]),
                pack_bf16(acc[4 * i1], acc[4 * i1 + 1]), pack_bf16(acc[4 * i1 + 2], acc[4 * i1 + 3]));
    }
    fence_async_smem();
    named_bar(2 + wg, 128);
    if ((tid & 127) == 0) {
      tma_store_2d(&maps.c, ebuf, ct * 128 + wg * 64, tt * K3_N);
      bulk_commit();
      bulk_wait<0>();
    }
  }
}

typedef CUresult (*EncodeFn)(CUtensorMap*, CUtensorMapDataType, cuuint32_t, void*, const cuuint64_t*, const cuuint64_t*,
                             const cuuint32_t*, const cuuint32_t*, CUtensorMapInterleave, CUtensorMapSwizzle,
                             CUtensorMapL2promotion, CUtensorMapFloatOOBfill);

void make_map(EncodeFn enc, CUtensorMap* m, const void* ptr, uint64_t cols, uint64_t rows, uint64_t pitch_elems,
              uint32_t box_cols, uint32_t box_rows, CUtensorMapSwizzle swz,
              CUtensorMapL2promotion promo = CU_TENSOR_MAP_L2_PROMOTION_L2_128B) {
  cuuint64_t dims[2] = {cols, rows};
  cuuint64_t strides[1] = {pitch_elems * 2};
  cuuint32_t box[2] = {box_cols, box_rows};
  cuuint32_t es[2] = {1, 1};
  enc(m, CU_TENSOR_MAP_DATA_TYPE_BFLOAT16, 2, const_cast<void*>(ptr), dims, strides, box, es, CU_TENSOR_MAP_INTERLEAVE_NONE, swz,
      promo, CU_TENSOR_MAP_FLOAT_OOB_FILL_NONE);
}

void make_map_nd(EncodeFn enc, CUtensorMap* m, const void* ptr, int rank, const uint64_t* dims, const uint64_t* strides_elems,
                 const uint32_t* box, CUtensorMapSwizzle swz) {
  cuuint64_t d[5], st[4]; cuuint32_t b[5], es[5];
  for (int i = 0; i < rank; i++) { d[i] = dims[i]; b[i] = box[i]; es[i] = 1; if (i) st[i - 1] = strides_elems[i] * 2; }
  enc(m, CU_TENSOR_MAP_DATA_TYPE_BFLOAT16, rank, const_cast<void*>(ptr), d, st, b, es, CU_TENSOR_MAP_INTERLEAVE_NONE, swz,
      CU_TENSOR_MAP_L2_PROMOTION_L2_128B, CU_TENSOR_MAP_FLOAT_OOB_FILL_NONE);
}

}

extern "C" void kernel_launch(void* const* d_in, const int* in_sizes, int n_in, void* d_out, int out_size) {
  (void)in_sizes; (void)n_in; (void)out_size;
  const bf16* x = (const bf16*)d_in[0];
  const bf16* mem0 = (const bf16*)d_in[1];
  const bf16* Wq = (const bf16*)d_in[2];
  const bf16* Wk = (const bf16*)d_in[3];
  const bf16* Wv = (const bf16*)d_in[4];
  const bf16* Wo = (const bf16*)d_in[5];
  const bf16* Bq = (const bf16*)d_in[7];
  const bf16* Bk = (const bf16*)d_in[8];
  const bf16* Bv = (const bf16*)d_in[9];
  const bf16* shift_k = (const bf16*)d_in[10];
  const bf16* ssm_k = (const bf16*)d_in[11];
  const bf16* ssm_D = (const bf16*)d_in[12];
  bf16* out = (bf16*)d_out;

  static EncodeFn enc = nullptr;
  static uint64_t xbase;
  static int nsm = 132;
  static cudaStream_t s1;
  static cudaEvent_t ev_fork, ev_join;
  if (!enc) {
    cudaDriverEntryPointQueryResult qr;
    void* fn = nullptr;
    cudaGetDriverEntryPoint("cuTensorMapEncodeTiled", &fn, cudaEnableDefault, &qr);
    enc = (EncodeFn)fn;
    void* ps = nullptr;
    cudaGetSymbolAddress(&ps, g_scratch);
    xbase = (uint64_t)ps;
    if ((xbase >> 32) != ((xbase + xo::BYTES - 1) >> 32)) xbase += xo::BYTES;
    cudaFuncSetAttribute(tail_kernel, cudaFuncAttributeMaxDynamicSharedMemorySize, k3::SMEM);
    cudaFuncSetAttribute(chain_kernel, cudaFuncAttributeMaxDynamicSharedMemorySize, chain::SMEM);
    cudaFuncSetAttribute(bpart_kernel, cudaFuncAttributeMaxDynamicSharedMemorySize, bp::SMEM);
    cudaStreamCreateWithFlags(&s1, cudaStreamNonBlocking);
    cudaEventCreateWithFlags(&ev_fork, cudaEventDisableTiming);
    cudaEventCreateWithFlags(&ev_join, cudaEventDisableTiming);
    int dev = 0; cudaGetDevice(&dev);
    cudaDeviceGetAttribute(&nsm, cudaDevAttrMultiProcessorCount, dev);
  }
  const CUtensorMapSwizzle SW128 = CU_TENSOR_MAP_SWIZZLE_128B, SW64 = CU_TENSOR_MAP_SWIZZLE_64B;
  GemmMaps m3; ChainMaps mc;
  make_map(enc, &m3.o, (void*)(xbase + xo::O), HD, S_LEN, HD, 64, K3_N, SW128);
  make_map(enc, &m3.w, Wo, DM, HD, DM, 64, 64, SW128);
  make_map(enc, &m3.c, out, DM, S_LEN, OUT_LD, 64, K3_N, SW128);
  const CUtensorMapL2promotion P256 = CU_TENSOR_MAP_L2_PROMOTION_L2_256B;
  make_map(enc, &mc.wq, Wq, HD, DM, HD, 64, 128, SW128, P256);
  make_map(enc, &mc.wk, Wk, HD, DM, HD, 64, 128, SW128, P256);
  make_map(enc, &mc.wv, Wv, HD, DM, HD, 64, 128, SW128, P256);
  make_map(enc, &mc.wo, Wo, DM, HD, DM, 32, 256, SW64, P256);
  {
    const uint64_t dx[3] = {64, S_LEN, DM / 64}, sx[3] = {1, DM, 64};
    const uint32_t bx[3] = {64, SEG, 8};
    make_map_nd(enc, &mc.x, x, 3, dx, sx, bx, SW128);
    const uint32_t bq[3] = {64, SEG, 4};
    make_map_nd(enc, &mc.xq, x, 3, dx, sx, bq, SW128);
    mc.xp = (const char*)x;
  }

  const int skip = 0;
  mc.t_step = T_STEP; mc.t_phase = T_PHASE;
  BMaps mb;
  const CUtensorMapSwizzle SWN = CU_TENSOR_MAP_SWIZZLE_NONE;
  make_map(enc, &mb.k, Bk, DM, S_LEN, DM, 8, 256, SWN);
  make_map(enc, &mb.q, Bq, DM, S_LEN, DM, 8, 256, SWN);
  make_map(enc, &mb.v, Bv, DM, S_LEN, DM, 8, 256, SWN);
  mb.shift_k = shift_k; mb.ssm_k = ssm_k; mb.ssm_D = ssm_D;
  make_map(enc, &mb.out, out, OUT_LD, S_LEN, OUT_LD, 8, 256, SWN);
  make_map(enc, &mb.k8, Bk, DM, S_LEN, DM, 8, 8, SWN);
  cudaStream_t s0 = cudaStreamPerThread;
  const int nb = nsm >= 132 ? 4 : 2, ntask1 = bp::NTASK - 2 * k3::NB;
  const bool fork = nsm >= 130 && !(skip & 16);
  if (fork) {
    cudaEventRecord(ev_fork, s0);
    cudaStreamWaitEvent(s1, ev_fork, 0);
    if (!(skip & 1)) bpart_kernel<<<nb, 512, bp::SMEM, s1>>>(mb, ntask1);
    cudaEventRecord(ev_join, s1);
  } else if (!(skip & 1)) {
    bpart_kernel<<<ntask1 / 2, 512, bp::SMEM, s0>>>(mb, ntask1);
  }
  if (!(skip & 4)) chain_kernel<<<128, 256, chain::SMEM, s0>>>(mc, mem0, xbase);
  if (!(skip & 8)) {
    cudaLaunchAttribute pdl[1];
    pdl[0].id = cudaLaunchAttributeProgrammaticStreamSerialization;
    pdl[0].val.programmaticStreamSerializationAllowed = 1;
    cudaLaunchConfig_t cfg = {};
    cfg.gridDim = dim3(128); cfg.blockDim = dim3(512); cfg.dynamicSmemBytes = k3::SMEM; cfg.stream = s0;
    cfg.attrs = pdl; cfg.numAttrs = 1;
    cudaLaunchKernelEx(&cfg, tail_kernel, m3, mb);
  }
  if (fork) cudaStreamWaitEvent(s0, ev_join, 0);
}
```

```cpp
#include <cuda_runtime.h>
#include <cuda_bf16.h>
#include <cuda.h>
#include <stdint.h>

namespace {

constexpr int S_LEN = 2048;
constexpr int DM = 1024;
constexpr int NH = 32;
constexpr int DH = 128;
constexpr int HD = NH * DH;
constexpr int SEG = 32;
constexpr int NSEG = S_LEN / SEG;
constexpr int OUT_LD = 2048;

typedef __nv_bfloat16 bf16;
#define K3_N 160

__device__ __forceinline__ uint32_t smem_u32(const void* p) { return (uint32_t)__cvta_generic_to_shared(p); }

__device__ __forceinline__ void mbar_init(uint32_t bar, uint32_t count) {
  asm volatile("mbarrier.init.shared::cta.b64 [%0], %1;" ::"r"(bar), "r"(count) : "memory");
}
__device__ __forceinline__ void mbar_expect_tx(uint32_t bar, uint32_t bytes) {
  asm volatile("mbarrier.arrive.expect_tx.shared::cta.b64 _, [%0], %1;" ::"r"(bar), "r"(bytes) : "memory");
}
__device__ __forceinline__ void mbar_arrive(uint32_t bar) {
  asm volatile("mbarrier.arrive.shared::cta.b64 _, [%0];" ::"r"(bar) : "memory");
}
__device__ __forceinline__ bool mbar_try(uint32_t bar, uint32_t parity) {
  uint32_t ok;
  asm volatile("{.reg .pred p; mbarrier.try_wait.parity.shared::cta.b64 p, [%1], %2; selp.u32 %0, 1, 0, p;}"
               : "=r"(ok) : "r"(bar), "r"(parity) : "memory");
  return ok;
}
__device__ __forceinline__ bool mbar_test(uint32_t bar, uint32_t parity) {
  uint32_t ok;
  asm volatile("{.reg .pred p; mbarrier.test_wait.parity.shared::cta.b64 p, [%1], %2; selp.u32 %0, 1, 0, p;}"
               : "=r"(ok) : "r"(bar), "r"(parity) : "memory");
  return ok;
}
template <int HINT = 1>
__device__ __forceinline__ void mbar_wait(uint32_t bar, uint32_t parity) {
  int guard = 0;
  while (__builtin_expect(!mbar_try(bar, parity), HINT)) { if (++guard > (1 << 22)) __trap(); }
}
__device__ __forceinline__ void tma_load_2d(uint32_t dst, const CUtensorMap* map, int c0, int c1, uint32_t bar) {
  asm volatile("cp.async.bulk.tensor.2d.shared::cluster.global.mbarrier::complete_tx::bytes [%0], [%1, {%3, %4}], [%2];"
               ::"r"(dst), "l"(map), "r"(bar), "r"(c0), "r"(c1) : "memory");
}
__device__ __forceinline__ void tma_load_3d(uint32_t dst, const CUtensorMap* map, int c0, int c1, int c2, uint32_t bar) {
  asm volatile("cp.async.bulk.tensor.3d.shared::cluster.global.mbarrier::complete_tx::bytes [%0], [%1, {%3, %4, %5}], [%2];"
               ::"r"(dst), "l"(map), "r"(bar), "r"(c0), "r"(c1), "r"(c2) : "memory");
}
__device__ __forceinline__ void tma_load_4d(uint32_t dst, const CUtensorMap* map, int c0, int c1, int c2, int c3, uint32_t bar) {
  asm volatile("cp.async.bulk.tensor.4d.shared::cluster.global.mbarrier::complete_tx::bytes [%0], [%1, {%3, %4, %5, %6}], [%2];"
               ::"r"(dst), "l"(map), "r"(bar), "r"(c0), "r"(c1), "r"(c2), "r"(c3) : "memory");
}
__device__ __forceinline__ void tma_store_2d(const CUtensorMap* map, uint32_t src, int c0, int c1) {
  asm volatile("cp.async.bulk.tensor.2d.global.shared::cta.bulk_group [%0, {%2, %3}], [%1];"
               ::"l"(map), "r"(src), "r"(c0), "r"(c1) : "memory");
}
__device__ __forceinline__ void tma_prefetch_2d(const CUtensorMap* map, int c0, int c1) {
  asm volatile("cp.async.bulk.prefetch.tensor.2d.L2.global [%0, {%1, %2}];" ::"l"(map), "r"(c0), "r"(c1) : "memory");
}
__device__ __forceinline__ void tma_prefetch_desc(const CUtensorMap* map) {
  asm volatile("prefetch.tensormap [%0];" ::"l"(map) : "memory");
}
__device__ __forceinline__ void fence_async_smem() { asm volatile("fence.proxy.async.shared::cta;" ::: "memory"); }
__device__ __forceinline__ void bulk_commit() { asm volatile("cp.async.bulk.commit_group;" ::: "memory"); }
template <int N> __device__ __forceinline__ void bulk_wait_read() { asm volatile("cp.async.bulk.wait_group.read %0;" ::"n"(N) : "memory"); }
template <int N> __device__ __forceinline__ void bulk_wait() { asm volatile("cp.async.bulk.wait_group %0;" ::"n"(N) : "memory"); }
__device__ __forceinline__ void named_bar(int id, int n) { asm volatile("bar.sync %0, %1;" ::"r"(id), "r"(n) : "memory"); }

__device__ __forceinline__ void named_bar_arrive(int id, int n) { asm volatile("bar.arrive %0, %1;" ::"r"(id), "r"(n) : "memory"); }
__device__ __forceinline__ float ex2(float x) { float y; asm("ex2.approx.ftz.f32 %0, %1;" : "=f"(y) : "f"(x)); return y; }
__device__ __forceinline__ float rcp(float x) { float y; asm("rcp.approx.ftz.f32 %0, %1;" : "=f"(y) : "f"(x)); return y; }

__device__ __forceinline__ void sts32(uint32_t a, uint32_t x) { asm volatile("st.shared.b32 [%0], %1;" ::"r"(a), "r"(x) : "memory"); }
__device__ __forceinline__ uint32_t lds32(uint32_t a) { uint32_t x; asm volatile("ld.shared.b32 %0, [%1];" : "=r"(x) : "r"(a) : "memory"); return x; }
__device__ __forceinline__ uint32_t lds32v(uint32_t a) { uint32_t x; asm volatile("ld.volatile.shared.b32 %0, [%1];" : "=r"(x) : "r"(a) : "memory"); return x; }
__device__ __forceinline__ void sts128(uint32_t a, const uint4& v) { asm volatile("st.shared.v4.b32 [%0], {%1,%2,%3,%4};" ::"r"(a), "r"(v.x), "r"(v.y), "r"(v.z), "r"(v.w) : "memory"); }
__device__ __forceinline__ void sts128f(uint32_t a, const float4& v) { asm volatile("st.shared.v4.f32 [%0], {%1,%2,%3,%4};" ::"r"(a), "f"(v.x), "f"(v.y), "f"(v.z), "f"(v.w) : "memory"); }
__device__ __forceinline__ uint4 lds128(uint32_t a) { uint4 v; asm volatile("ld.shared.v4.b32 {%0,%1,%2,%3}, [%4];" : "=r"(v.x), "=r"(v.y), "=r"(v.z), "=r"(v.w) : "r"(a) : "memory"); return v; }
__device__ __forceinline__ float4 lds128f(uint32_t a) { float4 v; asm volatile("ld.shared.v4.f32 {%0,%1,%2,%3}, [%4];" : "=f"(v.x), "=f"(v.y), "=f"(v.z), "=f"(v.w) : "r"(a) : "memory"); return v; }

__device__ __forceinline__ void cp_async16(uint32_t dst, const void* src) { asm volatile("cp.async.cg.shared.global [%0], [%1], 16;" ::"r"(dst), "l"(src) : "memory"); }
__device__ __forceinline__ void cp_async_commit() { asm volatile("cp.async.commit_group;" ::: "memory"); }
template <int N> __device__ __forceinline__ void cp_async_wait_group() { asm volatile("cp.async.wait_group %0;" ::"n"(N) : "memory"); }

__device__ __forceinline__ void wg_fence() { asm volatile("wgmma.fence.sync.aligned;" ::: "memory"); }
__device__ __forceinline__ void wg_commit() { asm volatile("wgmma.commit_group.sync.aligned;" ::: "memory"); }
template <int N> __device__ __forceinline__ void wg_wait() { asm volatile("wgmma.wait_group.sync.aligned %0;" ::"n"(N) : "memory"); }
__device__ __forceinline__ uint64_t make_desc(uint32_t addr, uint32_t lbo, uint32_t sbo, uint32_t swz) {
  return (uint64_t)((addr & 0x3FFFF) >> 4) | ((uint64_t)(lbo >> 4) << 16) | ((uint64_t)(sbo >> 4) << 32) | ((uint64_t)swz << 62);
}

__device__ __forceinline__ void ldsm_x4(uint32_t (&r)[4], uint32_t addr) {
  asm volatile("ldmatrix.sync.aligned.m8n8.x4.shared.b16 {%0,%1,%2,%3}, [%4];"
               : "=r"(r[0]), "=r"(r[1]), "=r"(r[2]), "=r"(r[3]) : "r"(addr) : "memory");
}
__device__ __forceinline__ void ldsm_x4_t(uint32_t (&r)[4], uint32_t addr) {
  asm volatile("ldmatrix.sync.aligned.m8n8.x4.trans.shared.b16 {%0,%1,%2,%3}, [%4];"
               : "=r"(r[0]), "=r"(r[1]), "=r"(r[2]), "=r"(r[3]) : "r"(addr) : "memory");
}
__device__ __forceinline__ void ldsm_x2(uint32_t& r0, uint32_t& r1, uint32_t addr) {
  asm volatile("ldmatrix.sync.aligned.m8n8.x2.shared.b16 {%0,%1}, [%2];" : "=r"(r0), "=r"(r1) : "r"(addr) : "memory");
}
__device__ __forceinline__ void stsm_x4(uint32_t addr, uint32_t r0, uint32_t r1, uint32_t r2, uint32_t r3) {
  asm volatile("stmatrix.sync.aligned.m8n8.x4.shared.b16 [%0], {%1,%2,%3,%4};"
               ::"r"(addr), "r"(r0), "r"(r1), "r"(r2), "r"(r3) : "memory");
}
__device__ __forceinline__ void stsm_x4_t(uint32_t addr, uint32_t r0, uint32_t r1, uint32_t r2, uint32_t r3) {
  asm volatile("stmatrix.sync.aligned.m8n8.x4.trans.shared.b16 [%0], {%1,%2,%3,%4};" ::"r"(addr), "r"(r0), "r"(r1), "r"(r2), "r"(r3) : "memory");
}
__device__ __forceinline__ void mma16816(float (&c)[4], const uint32_t (&a)[4], uint32_t b0, uint32_t b1) {
  asm volatile("mma.sync.aligned.m16n8k16.row.col.f32.bf16.bf16.f32 {%0,%1,%2,%3}, {%4,%5,%6,%7}, {%8,%9}, {%0,%1,%2,%3};"
               : "+f"(c[0]), "+f"(c[1]), "+f"(c[2]), "+f"(c[3])
               : "r"(a[0]), "r"(a[1]), "r"(a[2]), "r"(a[3]), "r"(b0), "r"(b1));
}
__device__ __forceinline__ void mma1688(float (&c)[4], uint32_t a0, uint32_t a1, uint32_t b0) {
  asm volatile("mma.sync.aligned.m16n8k8.row.col.f32.bf16.bf16.f32 {%0,%1,%2,%3}, {%4,%5}, {%6}, {%0,%1,%2,%3};"
               : "+f"(c[0]), "+f"(c[1]), "+f"(c[2]), "+f"(c[3]) : "r"(a0), "r"(a1), "r"(b0));
}
__device__ __forceinline__ uint32_t pack_bf16(float lo, float hi) {
  uint32_t r;
  asm("cvt.rn.bf16x2.f32 %0, %1, %2;" : "=r"(r) : "f"(hi), "f"(lo));
  return r;
}
__device__ __forceinline__ float bf_lo(uint32_t w) { return __uint_as_float(w << 16); }
__device__ __forceinline__ float bf_hi(uint32_t w) { return __uint_as_float(w & 0xFFFF0000u); }

__device__ __forceinline__ uint4 ld_relaxed4(const void* p) {
  uint4 v;
  asm volatile("ld.relaxed.gpu.global.v4.u32 {%0,%1,%2,%3}, [%4];" : "=r"(v.x), "=r"(v.y), "=r"(v.z), "=r"(v.w) : "l"(p) : "memory");
  return v;
}
__device__ __forceinline__ void st_relaxed4(void* p, uint32_t a, uint32_t b, uint32_t c, uint32_t d) {
  asm volatile("st.relaxed.gpu.global.v4.u32 [%0], {%1,%2,%3,%4};" ::"l"(p), "r"(a), "r"(b), "r"(c), "r"(d) : "memory");
}
__device__ __forceinline__ void st_relaxed2(void* p, uint32_t a, uint32_t b) {
  asm volatile("st.relaxed.gpu.global.v2.u32 [%0], {%1,%2};" ::"l"(p), "r"(a), "r"(b) : "memory");
}
__device__ __forceinline__ void st_relaxed1(void* p, uint32_t a) {
  asm volatile("st.relaxed.gpu.global.u32 [%0], %1;" ::"l"(p), "r"(a) : "memory");
}

__device__ __forceinline__ uint2 ld_relaxed2(const void* p) {
  uint2 v;
  asm volatile("ld.relaxed.gpu.global.v2.u32 {%0,%1}, [%2];" : "=r"(v.x), "=r"(v.y) : "l"(p) : "memory");
  return v;
}
__device__ __forceinline__ void sts64(uint32_t a, uint32_t x, uint32_t y) { asm volatile("st.shared.v2.b32 [%0], {%1,%2};" ::"r"(a), "r"(x), "r"(y) : "memory"); }
__device__ __forceinline__ uint2 lds64(uint32_t a) { uint2 v; asm volatile("ld.shared.v2.b32 {%0,%1}, [%2];" : "=r"(v.x), "=r"(v.y) : "r"(a) : "memory"); return v; }
__device__ __forceinline__ void lds128r(uint32_t (&r)[4], uint32_t a) {
  asm volatile("ld.shared.v4.b32 {%0,%1,%2,%3}, [%4];" : "=r"(r[0]), "=r"(r[1]), "=r"(r[2]), "=r"(r[3]) : "r"(a) : "memory");
}
__device__ __forceinline__ uint32_t movmat(uint32_t a) { uint32_t d; asm volatile("movmatrix.sync.aligned.m8n8.trans.b16 %0, %1;" : "=r"(d) : "r"(a)); return d; }
__device__ __forceinline__ uint32_t mapa(uint32_t addr, uint32_t rank) { uint32_t r; asm volatile("mapa.shared::cluster.u32 %0, %1, %2;" : "=r"(r) : "r"(addr), "r"(rank)); return r; }
__device__ __forceinline__ void st_async1(uint32_t dst, uint32_t a, uint32_t bar) {
  asm volatile("st.async.weak.shared::cluster.mbarrier::complete_tx::bytes.b32 [%0], %1, [%2];" ::"r"(dst), "r"(a), "r"(bar) : "memory");
}
__device__ __forceinline__ void st_async2(uint32_t dst, uint32_t a, uint32_t b, uint32_t bar) {
  asm volatile("st.async.weak.shared::cluster.mbarrier::complete_tx::bytes.v2.b32 [%0], {%1,%2}, [%3];" ::"r"(dst), "r"(a), "r"(b), "r"(bar) : "memory");
}
__device__ __forceinline__ void st_async4(uint32_t dst, uint32_t a, uint32_t b, uint32_t c, uint32_t d, uint32_t bar) {
  asm volatile("st.async.weak.shared::cluster.mbarrier::complete_tx::bytes.v4.b32 [%0], {%1,%2,%3,%4}, [%5];" ::"r"(dst), "r"(a), "r"(b), "r"(c), "r"(d), "r"(bar) : "memory");
}
__device__ __forceinline__ void cluster_arrive() { asm volatile("barrier.cluster.arrive.relaxed.aligned;" ::: "memory"); }
__device__ __forceinline__ void cluster_wait() { asm volatile("barrier.cluster.wait.acquire.aligned;" ::: "memory"); }

__device__ __forceinline__ void wgmma_k3_ss_ta(float (&d)[80], uint64_t da, uint64_t db, int scale_d) {
  asm volatile("{.reg .pred p; setp.ne.b32 p, %82, 0;\n"
    "wgmma.mma_async.sync.aligned.m64n160k16.f32.bf16.bf16 {%0, %1, %2, %3, %4, %5, %6, %7, %8, %9, %10, %11, %12, %13, %14, %15, %16, %17, %18, %19, %20, %21, %22, %23, %24, %25, %26, %27, %28, %29, %30, %31, %32, %33, %34, %35, %36, %37, %38, %39, %40, %41, %42, %43, %44, %45, %46, %47, %48, %49, %50, %51, %52, %53, %54, %55, %56, %57, %58, %59, %60, %61, %62, %63, %64, %65, %66, %67, %68, %69, %70, %71, %72, %73, %74, %75, %76, %77, %78, %79}, %80, %81, p, 1, 1, 1, 0;}"
    : "+f"(d[0]), "+f"(d[1]), "+f"(d[2]), "+f"(d[3]), "+f"(d[4]), "+f"(d[5]), "+f"(d[6]), "+f"(d[7]), "+f"(d[8]), "+f"(d[9]), "+f"(d[10]), "+f"(d[11]), "+f"(d[12]), "+f"(d[13]), "+f"(d[14]), "+f"(d[15]), "+f"(d[16]), "+f"(d[17]), "+f"(d[18]), "+f"(d[19]), "+f"(d[20]), "+f"(d[21]), "+f"(d[22]), "+f"(d[23]), "+f"(d[24]), "+f"(d[25]), "+f"(d[26]), "+f"(d[27]), "+f"(d[28]), "+f"(d[29]), "+f"(d[30]), "+f"(d[31]), "+f"(d[32]), "+f"(d[33]), "+f"(d[34]), "+f"(d[35]), "+f"(d[36]), "+f"(d[37]), "+f"(d[38]), "+f"(d[39]), "+f"(d[40]), "+f"(d[41]), "+f"(d[42]), "+f"(d[43]), "+f"(d[44]), "+f"(d[45]), "+f"(d[46]), "+f"(d[47]), "+f"(d[48]), "+f"(d[49]), "+f"(d[50]), "+f"(d[51]), "+f"(d[52]), "+f"(d[53]), "+f"(d[54]), "+f"(d[55]), "+f"(d[56]), "+f"(d[57]), "+f"(d[58]), "+f"(d[59]), "+f"(d[60]), "+f"(d[61]), "+f"(d[62]), "+f"(d[63]), "+f"(d[64]), "+f"(d[65]), "+f"(d[66]), "+f"(d[67]), "+f"(d[68]), "+f"(d[69]), "+f"(d[70]), "+f"(d[71]), "+f"(d[72]), "+f"(d[73]), "+f"(d[74]), "+f"(d[75]), "+f"(d[76]), "+f"(d[77]), "+f"(d[78]), "+f"(d[79])
    : "l"(da), "l"(db), "r"(scale_d));
}
__device__ __forceinline__ void wgmma_m64n32_ss_ta(float (&d)[16], uint64_t da, uint64_t db, int scale_d) {
  asm volatile("{.reg .pred p; setp.ne.b32 p, %18, 0;\n"
    "wgmma.mma_async.sync.aligned.m64n32k16.f32.bf16.bf16 {%0, %1, %2, %3, %4, %5, %6, %7, %8, %9, %10, %11, %12, %13, %14, %15}, %16, %17, p, 1, 1, 1, 0;}"
    : "+f"(d[0]), "+f"(d[1]), "+f"(d[2]), "+f"(d[3]), "+f"(d[4]), "+f"(d[5]), "+f"(d[6]), "+f"(d[7]), "+f"(d[8]), "+f"(d[9]), "+f"(d[10]), "+f"(d[11]), "+f"(d[12]), "+f"(d[13]), "+f"(d[14]), "+f"(d[15])
    : "l"(da), "l"(db), "r"(scale_d));
}

__device__ __forceinline__ void wgmma_m64n32_rs(float (&d)[16], const uint32_t (&a)[4], uint64_t db, int scale_d) {
  asm volatile("{.reg .pred p; setp.ne.b32 p, %21, 0;\n"
    "wgmma.mma_async.sync.aligned.m64n32k16.f32.bf16.bf16 {%0, %1, %2, %3, %4, %5, %6, %7, %8, %9, %10, %11, %12, %13, %14, %15}, {%16, %17, %18, %19}, %20, p, 1, 1, 0;}"
    : "+f"(d[0]), "+f"(d[1]), "+f"(d[2]), "+f"(d[3]), "+f"(d[4]), "+f"(d[5]), "+f"(d[6]), "+f"(d[7]), "+f"(d[8]), "+f"(d[9]), "+f"(d[10]), "+f"(d[11]), "+f"(d[12]), "+f"(d[13]), "+f"(d[14]), "+f"(d[15])
    : "r"(a[0]), "r"(a[1]), "r"(a[2]), "r"(a[3]), "l"(db), "r"(scale_d));
}

#define X_POS 5
#define T_STEP 2816
#define T_PHASE 1760
#define RATE0 2295
#define T_LAG 32
#define T_TOL 192
#define T_SLIP 640
#define O_FIX 5
#define VM_POS 2
#define NTMP 4
#define V_PRE 6
#define SFENCE(i) asm volatile("{.reg .pred p; setp.eq.u32 p, %0, %1; @p trap;}" ::"r"(n), "r"(4096 + (i)) : "memory")
constexpr int RING = 4;
constexpr uint32_t EMPTY = 0xFFFFFFFFu;
namespace xo {
constexpr uint32_t SLOT = 1u << 20, HEAD = 16384;
constexpr uint32_t VM = 512;
constexpr uint32_t PT = 1024;
constexpr uint32_t PM = 1536;
constexpr uint32_t VT = 8192;
constexpr uint32_t MEM = NH * HEAD;
constexpr uint32_t OM = MEM + 16384;
constexpr uint32_t O = RING * SLOT;
constexpr uint32_t BYTES = O + S_LEN * HD * 2;
}
__device__ __align__(1024) uint4 g_scratch[2 * (xo::BYTES / 16)];
__device__ unsigned g_epoch;
__device__ __align__(16) unsigned g_rate[128];

struct ChainMaps {
  CUtensorMap wq, wk, wv;
  CUtensorMap wo;
  CUtensorMap x, xq;
  const char* xp;
  uint32_t t_step, t_phase;
};

namespace chain {
constexpr int OFF_X = 65536;
constexpr int OFF_MEM = 131072;
constexpr int OFF_WS = 0;
constexpr int OFF_FP = 147456;
constexpr int OFF_KT = 163840;
constexpr int OFF_QT = 180224;
constexpr int OFF_VT = 196608;
constexpr int OFF_PX = 204800;
constexpr int OFF_S4 = OFF_PX + 1536;
constexpr int OFF_QM = 212992;
constexpr int OFF_KM = 215040;
constexpr int OFF_S1 = 217088;
constexpr int OFF_WVR = 0;
constexpr int OFF_WOR = 147456;
constexpr int OFF_RED = 212992;
constexpr int OFF_VPX = 221184;
constexpr int OFF_RX = 223232;
constexpr int OFF_TR = 225280;
constexpr int OFF_BAR = 229376;
constexpr int BAR_X = OFF_BAR, BAR_TOK = OFF_BAR + 16, BAR_EX = OFF_BAR + 32, BAR_P = OFF_BAR + 40, GRID_TGT = OFF_BAR + 128;
constexpr int CT_BASE = GRID_TGT + 4, CT_HEAD = GRID_TGT + 8, CT_OM = GRID_TGT + 12, CT_MP = GRID_TGT + 16, CT_O = GRID_TGT + 20, CT_PF = GRID_TGT + 24;
constexpr int CT_TT = GRID_TGT + 28, CT_T = GRID_TGT + 32;
constexpr uint32_t RANK_BIT = 1u << 24;
constexpr int SMEM = OFF_BAR + 256;
constexpr uint32_t SB_LO = 1024;
constexpr float SCALE = 0.08838834764831845f, L2E = 1.4426950408889634f;
}

__device__ __forceinline__ uint32_t umax4(uint32_t a, uint32_t b, uint32_t c, uint32_t d) { return max(max(a, b), max(c, d)); }
__device__ __forceinline__ bool warp_incomplete(uint32_t m) { return __any_sync(0xffffffffu, m == EMPTY); }
#define PIN(x) asm volatile("" : "+r"(x))
#define KEEPALIVE(a, z) do { float _d0, _d1, _d2, _d3; asm volatile("mma.sync.aligned.m16n8k16.row.col.f32.bf16.bf16.f32 {%0,%1,%2,%3}, {%4,%5,%6,%7}, {%4,%5}, {%8,%8,%8,%8};" \
    : "=f"(_d0), "=f"(_d1), "=f"(_d2), "=f"(_d3) : "r"(a[0]), "r"(a[1]), "r"(a[2]), "r"(a[3]), "f"(0.f)); \
      \
    asm volatile("{.reg .pred p; setp.ne.u32 p, %0, 0; @p st.shared.f32 [%0], %1;}" ::"r"(z), "f"(_d0 + _d3) : "memory"); } while (0)
constexpr int POLL_LIMIT = 1 << 17;

__device__ __forceinline__ uint32_t keep(uint32_t x) { return __shfl_sync(0xffffffffu, x, threadIdx.x & 31); }
__device__ __forceinline__ char* gptr(uint32_t hi, uint32_t lo) { return (char*)(((uint64_t)hi << 32) | lo); }
__device__ __forceinline__ uint32_t slot_off(int n) { return ((uint32_t)n & (RING - 1)) * xo::SLOT; }
__device__ __forceinline__ float quad_max(float x) {
  const float a = __shfl_xor_sync(~0u, x, 1), b = __shfl_xor_sync(~0u, x, 2), c = __shfl_xor_sync(~0u, x, 3);
  return fmaxf(fmaxf(x, a), fmaxf(b, c));
}
__device__ __forceinline__ void acc_fence(float (&a)[16]) {
#pragma unroll
  for (int i = 0; i < 16; i++) asm volatile("" : "+f"(a[i]) :: "memory");
}
template <int NB = 1, int STRIDE = 0>
__device__ __forceinline__ void gather_issue(uint32_t dst, const char* src) {
#pragma unroll
  for (int b = 0; b < NB; b++)
#pragma unroll
    for (int i = 0; i < 4; i++) cp_async16(dst + b * STRIDE + i * 512, src + b * STRIDE + i * 512);
  cp_async_commit();
}
template <int NB, int STRIDE>
__device__ __forceinline__ bool gather_incomplete(uint32_t chk) {
  uint32_t m = 0;
#pragma unroll
  for (int b = 0; b < NB; b++) m = max(m, umax4(lds32(chk + b * STRIDE), lds32(chk + b * STRIDE + 512), lds32(chk + b * STRIDE + 1024), lds32(chk + b * STRIDE + 1536)));
  return warp_incomplete(m);
}
__device__ __forceinline__ uint32_t ld_relaxed1(const void* p) {
  uint32_t v;
  asm volatile("ld.relaxed.gpu.global.u32 %0, [%1];" : "=r"(v) : "l"(p) : "memory");
  return v;
}
__device__ __forceinline__ uint32_t gtime() { uint64_t g; asm volatile("mov.u64 %0, %%globaltimer;" : "=l"(g) :: "memory"); return (uint32_t)g; }
#define WAIT_UNTIL(t, ka, alive, id) do { \
    int _d = gtime() - (t); \
    if (__builtin_expect(_d > T_TOL, 0)) do { t += T_SLIP; _d -= T_SLIP; } while (_d > T_TOL); \
    if (alive) for (int _k = 64; _d < -96 && --_k; _d = gtime() - (t)) KEEPALIVE(ka, zr); \
    for (uint32_t _g = -128; (int)(_d & ++_g) < 0;) _d = gtime() - (t); } while (0)
__device__ __forceinline__ void issue_x(uint32_t sb, const CUtensorMap* map, int n, int part, int q = 0) {
  asm volatile("{.reg .pred p; elect.sync _|p, 0xffffffff;\n"
               "@p cp.async.bulk.tensor.3d.shared::cluster.global.mbarrier::complete_tx::bytes [%0], [%1, {%3, %4, %5}], [%2];}"
               ::"r"(sb + chain::OFF_X + part * 32768 + q * 16384), "l"(map), "r"(sb + chain::BAR_X + 8 * part), "r"(0), "r"(n * SEG), "r"(part * 8 + q * 4) : "memory");
}
__device__ __forceinline__ void issue_x_if(uint32_t sb, const CUtensorMap* map, int n, int part, uint32_t on) {
  asm volatile("{.reg .pred p, q; elect.sync _|p, 0xffffffff; setp.ne.and.u32 q, %6, 0, p;\n"
               "@q cp.async.bulk.tensor.3d.shared::cluster.global.mbarrier::complete_tx::bytes [%0], [%1, {%3, %4, %5}], [%2];}"
               ::"r"(sb + chain::OFF_X + part * 32768), "l"(map), "r"(sb + chain::BAR_X + 8 * part), "r"(0), "r"(n * SEG), "r"(part * 8), "r"(on) : "memory");
}
__device__ __forceinline__ void prefetch_l2(const char* p, uint32_t bytes) {
  asm volatile("{.reg .pred p; elect.sync _|p, 0xffffffff; @p cp.async.bulk.prefetch.L2.global [%0], %1;}" ::"l"(p), "r"(bytes) : "memory");
}
__device__ __forceinline__ void expect_elect(uint32_t bar, uint32_t bytes) {
  asm volatile("{.reg .pred p; elect.sync _|p, 0xffffffff; @p mbarrier.arrive.expect_tx.shared::cta.b64 _, [%0], %1;}" ::"r"(bar), "r"(bytes) : "memory");
}
template <int WG> __device__ __forceinline__ constexpr uint64_t xdesc(int ks) {
  return (uint64_t)(((chain::SB_LO + chain::OFF_X + WG * 32768 + (ks >> 2) * 4096 + (ks & 3) * 32) >> 4) + (1u << 16)) |
         ((uint64_t)(64u | (1u << 30)) << 32);
}
template <int WG> __device__ __forceinline__ constexpr uint64_t wdesc(int o, int ks) {
  return (uint64_t)(((chain::SB_LO + chain::OFF_WS + WG * 32768 + o * 16384 + ks * 2048) >> 4) + (1u << 16)) | ((uint64_t)(64u | (1u << 30)) << 32);
}
__device__ __forceinline__ void load_mem0(uint2 (&m)[8], const bf16* __restrict__ mem0) {
#pragma unroll
  for (int r = 0; r < 8; r++) m[r] = ld_relaxed2((const uint2*)(mem0 + r * DM) + threadIdx.x);
}
__device__ __forceinline__ void store_mem0(uint32_t sb, const uint2 (&m)[8]) {
  const uint32_t d = sb + chain::OFF_MEM + threadIdx.x * 64;
  sts128(d, make_uint4(__byte_perm(m[0].x, m[1].x, 0x5410), __byte_perm(m[2].x, m[3].x, 0x5410), __byte_perm(m[4].x, m[5].x, 0x5410), __byte_perm(m[6].x, m[7].x, 0x5410)));
  sts128(d + 16, make_uint4(__byte_perm(m[0].x, m[1].x, 0x7632), __byte_perm(m[2].x, m[3].x, 0x7632), __byte_perm(m[4].x, m[5].x, 0x7632), __byte_perm(m[6].x, m[7].x, 0x7632)));
  sts128(d + 32, make_uint4(__byte_perm(m[0].y, m[1].y, 0x5410), __byte_perm(m[2].y, m[3].y, 0x5410), __byte_perm(m[4].y, m[5].y, 0x5410), __byte_perm(m[6].y, m[7].y, 0x5410)));
  sts128(d + 48, make_uint4(__byte_perm(m[0].y, m[1].y, 0x7632), __byte_perm(m[2].y, m[3].y, 0x7632), __byte_perm(m[4].y, m[5].y, 0x7632), __byte_perm(m[6].y, m[7].y, 0x7632)));
}
template <int K> __device__ __forceinline__ uint32_t loop_zero(int n) { uint32_t z; asm volatile("shr.u32 %0, %1, %2;" : "=r"(z) : "r"(n), "n"(16 + K)); return z; }
#define NEWZ(k) zr = loop_zero<k>(n)

template <int WG>
__device__ __forceinline__ void role_a(const ChainMaps& maps, const bf16* __restrict__ mem0, const uint32_t sb, const uint32_t xbase_hi) {
  using namespace chain;
  const int h = blockIdx.x >> 2;
  const bool J = sb >= RANK_BIT;
  const uint32_t u16 = (threadIdx.x & 96) * 64 + (threadIdx.x & 31) * 16;
  const uint32_t t16 = keep(u16), l16 = keep((threadIdx.x & 31) * 16);
  const uint32_t a_wl = keep((((threadIdx.x >> 4) & 1) * 8 + (threadIdx.x & 7)) * 128 + (((((threadIdx.x >> 4) & 6) + ((threadIdx.x >> 3) & 1)) ^ (threadIdx.x & 7)) << 4));
  const uint32_t xhi = keep(xbase_hi + (t16 >> 16));
#define xh (lds32(sb + CT_HEAD) + t16)
#define xm (lds32(sb + CT_BASE) + t16 + xo::MEM)
#define last_warp __any_sync(0xffffffffu, tv >= 6144)
#define tv (t16 ^ zr)
  const CUtensorMap* wm = J ? &maps.wk : &maps.wq;

  uint32_t aW[2][24][4];
  uint2 m0[8];
  load_mem0(m0, mem0);
  mbar_wait(sb + BAR_P, 0);
#pragma unroll
  for (int ks = 0; ks < 24; ks++) ldsm_x4_t(aW[0][ks], sb + a_wl + OFF_X + WG * 49152 + ks * 2048);
  named_bar(0, 256);
  if (WG == 1 && __any_sync(0xffffffffu, t16 >= 6144)) {
    fence_async_smem();
    if (l16 == 0) {
      mbar_expect_tx(sb + BAR_P + 16, 2 * 16384);
      for (int q = 0; q < 2; q++) tma_load_2d(sb + OFF_X + (4 + q) * 16384, wm, h * DH + (q ^ 1) * 64, q * 512 + 256, sb + BAR_P + 16);
    }
    __syncwarp();
    expect_elect(sb + BAR_X, 32768); expect_elect(sb + BAR_X + 8, 32768); expect_elect(sb + BAR_TOK, 8192);
    issue_x(sb, &maps.x, 0, 0); issue_x(sb, &maps.x, 0, 1);
  }
  mbar_wait(sb + BAR_P + 8, 0);
#pragma unroll
  for (int ks = 0; ks < 16; ks++) ldsm_x4_t(aW[1][ks], sb + a_wl + OFF_X + 6 * 16384 + WG * 32768 + ks * 2048);
  mbar_wait(sb + BAR_P + 16, 0);
#pragma unroll
  for (int ks = 0; ks < 8; ks++) ldsm_x4_t(aW[1][16 + ks], sb + a_wl + OFF_X + (4 + WG) * 16384 + ks * 2048);
  named_bar(0, 256);
  cluster_arrive();
  store_mem0(sb, m0);
  mbar_wait(sb + BAR_P + 24, 0);
  cluster_wait();
  const uint32_t rsb = sb ^ RANK_BIT;
  const uint32_t a_ws = sb + a_wl + OFF_WS + WG * 32768;

  uint32_t ws[2][4][4];
  auto load_ws = [&]() {
#pragma unroll
    for (int q = 0; q < 2; q++) {
      const uint32_t a = a_ws + q * 4096;
      ldsm_x4_t(ws[q][0], a); ldsm_x4_t(ws[q][1], a + 16384); ldsm_x4_t(ws[q][2], a + 2048); ldsm_x4_t(ws[q][3], a + 16384 + 2048);
    }
  };
  uint32_t tref = 0;
#pragma unroll 1
  for (int n = 0; n <= (J ? NSEG : NSEG - 1); n++) {
#define s (n - 1)
#define sv ((int)(n ^ zr) - 1)
    const bool more = __builtin_expect(s + 1 < NSEG, 1);
    uint32_t zr = loop_zero<0>(n);
#define wq ((int)(tv >> 11))
#define lv (l16 ^ zr)
#define gh (xh + slot_off(sv))
    uint32_t tmp[NTMP][4];
    auto load_tmp = [&](int o) {
#pragma unroll
      for (int ks = 0; ks < NTMP; ks++) ldsm_x4_t(tmp[ks], a_ws + o * 16384 + ks * 2048);
    };
    auto wait_x = [&]() { mbar_wait<0>(sb + BAR_X + 8 * WG, n & 1); };
    if (__builtin_expect(s < 0, 0)) { load_tmp(1); wait_x(); }
    else {
      {
        if (WG == 1) { if (__builtin_expect(s > 0, 1)) {
          const uint32_t dst = sb + OFF_MEM + tv + t16 - l16, chk = dst + ((lv >> 5) & 12);
          uint32_t tries = zr;
#pragma unroll 1
          do {
            if (tries) {
              const char* src = gptr(xhi, xm + t16 - l16 + slot_off(sv));
              tref += T_SLIP;
              WAIT_UNTIL(tref, aW[0][0], 1, -1);
              gather_issue<2, 2048>(dst, src);
            }
            KEEPALIVE(aW[0][0], zr);
            cp_async_wait_group<0>();
          } while (gather_incomplete<2, 2048>(chk) && ++tries < POLL_LIMIT);
        } } else if (J == 0) {
          uint32_t tries = s == 0;
#pragma unroll 1
          do {
            if (tries) gather_issue(sb + OFF_VT + tv, gptr(xhi, gh) + xo::VT);
            cp_async_wait_group<0>();
          } while (gather_incomplete<1, 0>(sb + OFF_VT + t16 + ((lv >> 5) & 12)) && ++tries < POLL_LIMIT);
        }
        named_bar(1, 256);
      }
      float c[2][2][4];
#pragma unroll
      for (int i = 0; i < 4; i++) c[i >> 1][i & 1][0] = c[i >> 1][i & 1][1] = c[i >> 1][i & 1][2] = c[i >> 1][i & 1][3] = 0.f;
      {
        const uint32_t a_mem = sb + OFF_MEM + WG * 8192 + l16;
        uint32_t b[4][4];
        bool tok;
        constexpr int PR[16] = {12, 13, 0, 1, 2, 3, 4, 14, 5, 6, 7, 8, 9, 15, 10, 11};
        ldsm_x4_t(b[0], a_mem + PR[0] * 512); ldsm_x4_t(b[1], a_mem + PR[1] * 512);
#pragma unroll
        for (int i = 0; i < 16; i++) {
          if ((i & 1) == 0 && i < 14) {
            ldsm_x4_t(b[(i + 2) & 3], a_mem + PR[i + 2] * 512); ldsm_x4_t(b[(i + 3) & 3], a_mem + PR[i + 3] * 512);
            if (i == 2 || i == 8) { ldsm_x4_t(ws[1][0], a_ws + (i == 2 ? 2 : 3) * 4096); ldsm_x4_t(ws[1][1], a_ws + (i == 2 ? 2 : 3) * 4096 + 16384); }
            if (i == 4 || i == 10) { ldsm_x4_t(ws[1][2], a_ws + (i == 4 ? 2 : 3) * 4096 + 2048); ldsm_x4_t(ws[1][3], a_ws + (i == 4 ? 2 : 3) * 4096 + 16384 + 2048); }
          }
          const int p = PR[i];
          if (p >= 12) {
            const int z = i != 0;
            mma16816(c[0][0], ws[z][0], b[i & 3][0], b[i & 3][1]); mma16816(c[1][0], ws[z][1], b[i & 3][0], b[i & 3][1]);
            mma16816(c[0][1], ws[z][2], b[i & 3][2], b[i & 3][3]); mma16816(c[1][1], ws[z][3], b[i & 3][2], b[i & 3][3]);
          } else {
            mma16816(c[1][0], aW[1][2 * p], b[i & 3][0], b[i & 3][1]); mma16816(c[1][1], aW[1][2 * p + 1], b[i & 3][2], b[i & 3][3]);
            mma16816(c[0][0], aW[0][2 * p], b[i & 3][0], b[i & 3][1]); mma16816(c[0][1], aW[0][2 * p + 1], b[i & 3][2], b[i & 3][3]);
          }
          if (i == 12) tok = mbar_test(sb + BAR_TOK + 8 * (s & 1), (s >> 1) & 1);
          if (i == 15 && __builtin_expect(!tok, 0)) mbar_wait(sb + BAR_TOK + 8 * (s & 1), (s >> 1) & 1);
          if (i == X_POS + 4 * (1 - WG)) { issue_x_if(sb, &maps.x, s + 1, WG, t16 >= 6144 && more); if (WG) __syncwarp(); }
        }
      }
      sts128f(sb + OFF_PX + WG * 512 + t16, make_float4(c[1][0][0] + c[1][1][0], c[1][0][1] + c[1][1][1], c[1][0][2] + c[1][1][2], c[1][0][3] + c[1][1][3]));
      const float4 own = make_float4(c[0][0][0] + c[0][1][0], c[0][0][1] + c[0][1][1], c[0][0][2] + c[0][1][2], c[0][0][3] + c[0][1][3]);
      NEWZ(1);
      uint32_t a = (J ? OFF_KM : OFF_QM) + WG * 1024 + wq * 256 + (lv >> 2);
      uint32_t ra = rsb + a, ra2 = ra + 128, rx = rsb + BAR_EX + zr;
      PIN(a); PIN(ra); PIN(ra2); PIN(rx);
      SFENCE(16);
      named_bar(3, 256);
      {
        const float4 o = lds128f(sb + OFF_PX + (WG ^ 1) * 512 + t16);
        const uint32_t lo = pack_bf16(own.x + o.x, own.y + o.y), hi = pack_bf16(own.z + o.z, own.w + o.w);
        if (J == 1 && more) { st_async1(ra, lo, rx); st_async1(ra2, hi, rx); }
        sts32(sb + a, lo); sts32(sb + a + 128, hi);
      }
      const uint32_t kt = sb + OFF_KT + (s & 1) * 8192;
#define k_lane ((lv & 240) + ((lv & 256) << 2))
#define a_lane (((lv & 128) << 1) + ((lv & 256) >> 1) + (lv & 112))
      if (J == 0) {
        uint32_t am[4][4], kb[4][4];
        uint2 vm0, vm1;
        const char* pvm = WG == 0 ? gptr(xhi, gh - (lv >> 1)) + xo::VM : nullptr;
        if (WG == 0 && VM_POS == 0) { vm0 = ld_relaxed2(pvm); vm1 = ld_relaxed2(pvm + 256); }
        if (WG == 1) {
#pragma unroll
          for (int p = 0; p < 4; p++) ldsm_x4(kb[p], kt + wq * 256 + k_lane + p * 2048);
        }
        named_bar(7, 256);
#pragma unroll
        for (int p = 0; p < 4; p++) ldsm_x4_t(am[p], sb + OFF_QM + p * 512 + a_lane);
        auto scores = [&]() {
          float c0[2][4], c1[2][4];
#pragma unroll
          for (int i = 0; i < 2; i++) { c0[i][0] = c0[i][1] = c0[i][2] = c0[i][3] = 0.f; c1[i][0] = c1[i][1] = c1[i][2] = c1[i][3] = 0.f; }
#pragma unroll
          for (int p = 0; p < 4; p++) { mma16816(c0[p & 1], am[p], kb[p][0], kb[p][1]); mma16816(c1[p & 1], am[p], kb[p][2], kb[p][3]); }
          const uint32_t r1 = pack_bf16((c0[0][0] + c0[1][0]) + (c1[0][2] + c1[1][2]), (c0[0][1] + c0[1][1]) + (c1[0][3] + c1[1][3]));
          return pack_bf16(bf_lo(r1) * SCALE, bf_hi(r1) * SCALE);
        };
        if (WG == 1) {
          const uint32_t st = scores();
          uint32_t vb[4][4];
#pragma unroll
          for (int e = 0; e < 4; e++) lds128r(vb[e], sb + OFF_VT + t16 + e * 512);
          __syncwarp();
          sts32(sb + OFF_S4 + l16 + wq * 4, st);
          named_bar(8, 128);
          const uint4 sc = lds128(sb + OFF_S4 + l16);
          float x[8] = {bf_lo(sc.x), bf_hi(sc.x), bf_lo(sc.y), bf_hi(sc.y), bf_lo(sc.z), bf_hi(sc.z), bf_lo(sc.w), bf_hi(sc.w)};
          float mx = fmaxf(fmaxf(fmaxf(x[0], x[1]), fmaxf(x[2], x[3])), fmaxf(fmaxf(x[4], x[5]), fmaxf(x[6], x[7])));
          mx = quad_max(mx);
          const float mb = mx * L2E;
#pragma unroll
          for (int i = 0; i < 8; i++) x[i] = ex2(fmaf(x[i], L2E, -mb));
          uint32_t pa[4], pb[4];
          asm volatile("" : "=r"(pa[1]), "=r"(pa[3]), "=r"(pb[1]), "=r"(pb[3]));
          pa[0] = pack_bf16(x[0], x[1]); pa[2] = pack_bf16(x[2], x[3]);
          pb[0] = pack_bf16(x[4], x[5]); pb[2] = pack_bf16(x[6], x[7]);
          float oa[4][4];
#pragma unroll
          for (int e = 0; e < 4; e++) { oa[e][0] = oa[e][1] = oa[e][2] = oa[e][3] = 0.f; mma16816(oa[e], pa, vb[e][0], vb[e][1]); }
#pragma unroll
          for (int e = 0; e < 4; e++) mma16816(oa[e], pb, vb[e][2], vb[e][3]);
          sts64(sb + OFF_PX + 1024 + t16, __float_as_uint(mx), __float_as_uint(((x[0] + x[1]) + (x[2] + x[3])) + ((x[4] + x[5]) + (x[6] + x[7]))));
          sts128f(sb + OFF_PX + t16, make_float4(oa[0][0], oa[0][1], oa[1][0], oa[1][1]));
          sts128f(sb + OFF_PX + 512 + t16, make_float4(oa[2][0], oa[2][1], oa[3][0], oa[3][1]));
          named_bar_arrive(9, 256);
          wait_x();
          load_tmp(1);
        } else {
          if (VM_POS == 1) { pvm += am[3][0] & zr; vm0 = ld_relaxed2(pvm); vm1 = ld_relaxed2(pvm + 256); }
          const uint32_t xo0 = lds32(sb + CT_OM) + wq * 512 + l16;
          mbar_wait<0>(sb + BAR_EX, s & 1);
          if (VM_POS == 2) { vm0 = ld_relaxed2(pvm); vm1 = ld_relaxed2(pvm + 256); }
#pragma unroll
          for (int p = 0; p < 4; p++) ldsm_x4_t(kb[p], sb + OFF_KM + p * 512 + l16);
          const uint32_t sm = scores();
          float mx = quad_max(fmaxf(bf_lo(sm), bf_hi(sm)));
          SFENCE(25);
          named_bar(9, 256);
          const uint2 ms = lds64(sb + OFF_PX + 1024 + t16);
          const float4 t0 = lds128f(sb + OFF_PX + t16), t1 = lds128f(sb + OFF_PX + 512 + t16);
          mx = fmaxf(mx, __uint_as_float(ms.x));
          const float mb = mx * L2E;
          const float e0 = ex2(fmaf(bf_lo(sm), L2E, -mb)), e1 = ex2(fmaf(bf_hi(sm), L2E, -mb)), ct = ex2(fmaf(__uint_as_float(ms.x), L2E, -mb));
          uint32_t p4 = pack_bf16(e0, e1), p5;
          asm volatile("" : "=r"(p5));
          float sx = fmaf(ct, __uint_as_float(ms.y), e0 + e1);
          float oa[4][4] = {{t0.x * ct, t0.y * ct, 0.f, 0.f}, {t0.z * ct, t0.w * ct, 0.f, 0.f}, {t1.x * ct, t1.y * ct, 0.f, 0.f}, {t1.z * ct, t1.w * ct, 0.f, 0.f}};
          const float s1 = __shfl_xor_sync(~0u, sx, 1), s2 = __shfl_xor_sync(~0u, sx, 2), s3 = __shfl_xor_sync(~0u, sx, 3);
          if (__builtin_expect(warp_incomplete(max(vm0.x, vm1.x)), 0)) {
            uint32_t tries = zr;
#pragma unroll 1
            do { vm0 = ld_relaxed2(pvm); vm1 = ld_relaxed2(pvm + 256); } while (warp_incomplete(max(vm0.x, vm1.x)) && ++tries < POLL_LIMIT);
          }
          mma1688(oa[0], p4, p5, vm0.x); mma1688(oa[1], p4, p5, vm0.y); mma1688(oa[2], p4, p5, vm1.x); mma1688(oa[3], p4, p5, vm1.y);
          const float rx = rcp((sx + s1) + (s2 + s3));
          st_relaxed4(gptr(xhi, xo0 + slot_off(sv)), pack_bf16(oa[0][0] * rx, oa[0][1] * rx), pack_bf16(oa[1][0] * rx, oa[1][1] * rx),
                      pack_bf16(oa[2][0] * rx, oa[2][1] * rx), pack_bf16(oa[3][0] * rx, oa[3][1] * rx));
          SFENCE(24);
          named_bar_arrive(10, 256);
          st_relaxed4(gptr(xhi, xo0 + slot_off(sv + 3)), EMPTY, EMPTY, EMPTY, EMPTY);
          load_tmp(1);
          wait_x();
        }
      } else {
        bool xok;
        {
          const int mt = WG | (wq == 3), ktile = wq == 3 ? 2 + WG : wq - 1;
          const uint32_t qt = sb + OFF_QT + (s & 1) * 8192 + mt * 512 + a_lane;
          uint32_t kb[4][4], q[8][4];
          if (__any_sync(0xffffffffu, tv < 2048)) {
            named_bar(7, 256);
#pragma unroll
            for (int p = 0; p < 4; p++) ldsm_x4_t(kb[p], sb + OFF_KM + p * 512 + l16);
          } else {
            named_bar_arrive(7, 256);
#pragma unroll
            for (int p = 0; p < 4; p++) ldsm_x4(kb[p], kt + ktile * 256 + k_lane + p * 2048);
          }
#pragma unroll
          for (int i = 0; i < 8; i++) ldsm_x4(q[i], qt + i * 1024);
          __syncwarp();
          float c0[4][4];
#pragma unroll
          for (int i = 0; i < 4; i++) { c0[i][0] = c0[i][1] = c0[i][2] = c0[i][3] = 0.f; mma16816(c0[i], q[i], kb[i >> 1][(i & 1) * 2], kb[i >> 1][(i & 1) * 2 + 1]); }
#pragma unroll
          for (int i = 0; i < 4; i++) mma16816(c0[i], q[4 + i], kb[2 + (i >> 1)][(i & 1) * 2], kb[2 + (i >> 1)][(i & 1) * 2 + 1]);
          load_tmp(1);
          xok = mbar_test(sb + BAR_X + 8 * WG, n & 1);
          NEWZ(3);
          const uint32_t r0 = pack_bf16((c0[0][0] + c0[1][0]) + (c0[2][0] + c0[3][0]), (c0[0][1] + c0[1][1]) + (c0[2][1] + c0[3][1]));
          const uint32_t r1 = pack_bf16((c0[0][2] + c0[1][2]) + (c0[2][2] + c0[3][2]), (c0[0][3] + c0[1][3]) + (c0[2][3] + c0[3][3]));
          const uint32_t sa = wq == 0 ? sb + OFF_S1 + (lv >> 2) + mt * 256 : sb + OFF_S4 + l16 + mt * 4096 + ktile * 4;
          sts32(sa, pack_bf16(bf_lo(r0) * SCALE, bf_hi(r0) * SCALE));
          sts32(sa + (wq == 0 ? 128 : 2048), pack_bf16(bf_lo(r1) * SCALE, bf_hi(r1) * SCALE));
        }
        if (WG == 1) named_bar_arrive(8, 256);
        else {
          if (more) named_bar_arrive(10, 256);
          const uint32_t gp = gh;
          named_bar(8, 256);
          const uint4 sc = lds128(sb + OFF_S4 + t16); const uint32_t s1 = lds32(sb + OFF_S1 + wq * 128 + (lv >> 2));
          float y[10] = {bf_lo(s1), bf_hi(s1), bf_lo(sc.x), bf_hi(sc.x), bf_lo(sc.y), bf_hi(sc.y), bf_lo(sc.z), bf_hi(sc.z), bf_lo(sc.w), bf_hi(sc.w)};
          const int rel = wq * 8 + (int)(lv >> 6) - (int)((lv >> 3) & 6);
          const float NEG = -999292928.f;
#pragma unroll
          for (int e = 0; e < 4; e++) {
            if (e * 8 > rel) y[2 * e + 2] = NEG;
            if (e * 8 + 1 > rel) y[2 * e + 3] = NEG;
          }
          float my = fmaxf(fmaxf(fmaxf(y[0], y[1]), fmaxf(y[2], y[3])), fmaxf(fmaxf(y[4], y[5]), fmaxf(y[6], y[7])));
          my = quad_max(fmaxf(my, fmaxf(y[8], y[9])));
#pragma unroll
          for (int i = 0; i < 10; i++) y[i] = ex2((y[i] - my) * L2E);
          float sy = ((y[0] + y[1]) + (y[2] + y[3])) + ((y[4] + y[5]) + (y[6] + y[7])) + (y[8] + y[9]);
          const float ry = rcp((sy + __shfl_xor_sync(~0u, sy, 1)) + (__shfl_xor_sync(~0u, sy, 2) + __shfl_xor_sync(~0u, sy, 3)));
          st_relaxed4(gptr(xhi, gp) + xo::PT, pack_bf16(y[2] * ry, y[3] * ry), pack_bf16(y[4] * ry, y[5] * ry), pack_bf16(y[6] * ry, y[7] * ry), pack_bf16(y[8] * ry, y[9] * ry));
          const uint32_t l12 = lv - (lv >> 2);
          st_relaxed1(gptr(xhi, gp - l12) + xo::PM, pack_bf16(y[0] * ry, y[1] * ry));
        }
        if (!xok && more) wait_x();
      }
    }
    if (more) {
      float acc[16];
      const uint32_t xph = (s + 1) & 1;
      auto batch = [&](const uint32_t (&a)[24][4], int o) {
        wg_fence();
#pragma unroll
        for (int ks = NTMP; ks < 8; ks++) wgmma_m64n32_ss_ta(acc, wdesc<WG>(o, ks), xdesc<WG>(24 + ks), ks != NTMP);
#pragma unroll
        for (int ks = 0; ks < NTMP; ks++) wgmma_m64n32_rs(acc, tmp[ks], xdesc<WG>(24 + ks), 1);
#pragma unroll
        for (int ks = 0; ks < 24; ks++) wgmma_m64n32_rs(acc, a[ks], xdesc<WG>(ks), 1);
        wg_commit();
        SFENCE(50 + o);
      };
      if (WG == 0) named_bar(12, 256);
      else if (__builtin_expect(s >= 0, 1)) named_bar(10, 256);
      batch(aW[1], 1);
      named_bar_arrive(WG ? 12 : 13, 256);
      wg_wait<0>();
      acc_fence(acc);
      load_tmp(0);
#pragma unroll
      for (int i = 0; i < 4; i++) sts128f(sb + OFF_FP + WG * 8192 + t16 + i * 512, make_float4(acc[4 * i], acc[4 * i + 1], acc[4 * i + 2], acc[4 * i + 3]));
      NEWZ(4);
      if (WG == 0 && s >= 0) {
        const uint32_t g1 = xh + slot_off(sv + 1);
        if (J == 0) gather_issue(sb + OFF_VT + tv, gptr(xhi, g1) + xo::VT);
        else {
          st_relaxed4(gptr(xhi, g1) + xo::PT, EMPTY, EMPTY, EMPTY, EMPTY);
          st_relaxed1(gptr(xhi, g1 - lv + (lv >> 2)) + xo::PM, EMPTY);
        }
      }
      uint32_t esrc = 0;
      if (WG == 1) { esrc = xm + t16 - l16 + 2048 + slot_off(sv + 1); tref += lds32(sb + CT_T); }
      named_bar(WG ? 13 : 14, 256);
      batch(aW[0], 0);
      NEWZ(5);
      if (WG == 1) {
        named_bar(14, 256);
        if (last_warp && s + 2 < NSEG) {
          expect_elect(sb + BAR_TOK + 8 * (xph ^ 1), 8192); expect_elect(sb + BAR_X, 32768); expect_elect(sb + BAR_X + 8, 32768);
          if (J == 0) expect_elect(sb + BAR_EX, 2048);
          if (s == NSEG - 3) asm volatile("griddepcontrol.launch_dependents;");
        }
      }
      const uint32_t tb = lds32(sb + CT_TT) + xph * 8192 + WG * 4096 + ((tv + l16) >> 1);
      float4 oth[4];
#pragma unroll
      for (int i = 0; i < 4; i++) oth[i] = lds128f(sb + OFF_FP + (WG ^ 1) * 8192 + t16 + i * 512);
      if (WG == 1 && __builtin_expect(s >= 0, 1)) {
        const uint32_t edst = sb + OFF_MEM + tv + t16 - l16;
        WAIT_UNTIL(tref, aW[0][0], 0, J ? 7 : 0);
        gather_issue<2, 2048>(edst, gptr(xhi, esrc) - 2048);
      }
      wg_wait<0>();
      acc_fence(acc);
      uint32_t lt[4], ht[4];
#pragma unroll
      for (int i = 0; i < 4; i++) {
        const float4 o = oth[i];
        lt[i] = pack_bf16(acc[4 * i] + o.x, acc[4 * i + 1] + o.y); ht[i] = pack_bf16(acc[4 * i + 2] + o.z, acc[4 * i + 3] + o.w);
      }
      stsm_x4_t(tb, lt[0], ht[0], lt[1], ht[1]); stsm_x4_t(tb + 512, lt[2], ht[2], lt[3], ht[3]);
      NEWZ(6);
      if (WG == 0 && last_warp) {
        load_ws();
        named_bar(11, 256);
        fence_async_smem();
        const uint32_t tt = (J ? OFF_KT : OFF_QT) + xph * 8192;
        asm volatile("{.reg .pred p; elect.sync _|p, 0xffffffff;\n"
                     "@p cp.async.bulk.shared::cluster.shared::cta.mbarrier::complete_tx::bytes [%0], [%1], 8192, [%2];}"
                     ::"r"(rsb + tt), "r"(sb + tt), "r"(rsb + BAR_TOK + 8 * xph) : "memory");
      } else {
        named_bar_arrive(11, 256);
        load_ws();
      }
    }
    if (!more) break;
    if (__builtin_expect(s < 0, 0)) {
      tref = gtime() / T_SLIP * T_SLIP - T_SLIP;
    }
  }
  cp_async_wait_group<0>();
  if (J == 0) mbar_wait(sb + BAR_TOK + 8, 1);
}

template <int WG>
__device__ __forceinline__ void role_v(const ChainMaps& maps, const bf16* __restrict__ mem0, const uint32_t sb, const uint32_t xbase_hi) {
  using namespace chain;
  const int h = blockIdx.x >> 2;
  const uint32_t u16 = (threadIdx.x & 96) * 64 + (threadIdx.x & 31) * 16;
  const uint32_t t16 = keep(u16), l16 = keep((threadIdx.x & 31) * 16);
  const uint32_t xhi = keep(xbase_hi + (t16 >> 16));
#define j (sb >> 24)
  auto wv_addr = [&](uint32_t t) { return WG * 32768 + ((t & 256) << 2) + ((t & 112) << 3) + ((((t >> 6) & 96) + ((t >> 3) & 16)) ^ (t & 112)); };
  auto wo_addr = [&](uint32_t t) { return OFF_WOR + WG * 32768 + ((t & 6144) << 2) + ((t & 256) << 1) + ((t & 112) << 2) + ((((j ^ 1) << 5) + ((t >> 3) & 16)) ^ ((t >> 1) & 48)); };
#define ovt (((tv + l16) >> 1) + (xo::VT + WG * 512 + j * 4096))
#define ovm (((tv & 4096) >> 1) + ((tv & 2048) >> 3) + (lv >> 1) + (xo::VM + j * 4096))
#define xvt (lds32(sb + CT_HEAD) + ovt)
#define xvm (lds32(sb + CT_HEAD) + ovm)
#define xom (lds32(sb + CT_OM) + t16 + WG * 8192)
#define warp_is(q) __any_sync(0xffffffffu, (tv >> 11) == (q))
#define upper_warps (WG == 1 || __any_sync(0xffffffffu, tv >= 4096))

  uint32_t aV[16][4];
  uint32_t aO[16][4];
  uint32_t bO[16][4];
  uint32_t rot[16][4];
  if (WG == 1 && __any_sync(0xffffffffu, t16 >= 6144)) {
    expect_elect(sb + BAR_X, 32768); expect_elect(sb + BAR_X + 8, 32768);
    issue_x(sb, &maps.x, 0, 0); issue_x(sb, &maps.x, 0, 1);
    prefetch_l2(maps.xp + 65536 + (h * 2 + j) * 3072, 3072);
  }
  cluster_arrive();
  { uint2 m0[8]; load_mem0(m0, mem0); store_mem0(sb, m0); }
  mbar_wait(sb + BAR_P, 0);
#pragma unroll
  for (int ks = 0; ks < 16; ks++) ldsm_x4_t(aV[ks], sb + wv_addr(t16) + OFF_WOR + ks * 2048);
  auto load_v = [&](uint32_t t) {
#pragma unroll
    for (int ks = 0; ks < 16; ks++) ldsm_x4_t(rot[ks], sb + wv_addr(t) + OFF_WVR + ks * 2048);
  };
  load_v(t16);
  named_bar(0, 256);
  if (threadIdx.x == 0) {
    fence_async_smem();
    mbar_expect_tx(sb + BAR_P + 8, 4 * 16384);
    for (int q = 0; q < 4; q++) tma_load_2d(sb + OFF_WOR + q * 16384, &maps.wo, h * 32, j * 2048 + q * 256, sb + BAR_P + 8);
    for (int q = 0; q < 4; q++) tma_prefetch_2d(&maps.wo, h * 32, j * 2048 + 1024 + q * 256);
  }
  __syncwarp();
  cluster_wait();
  const uint32_t rsb = sb ^ RANK_BIT;

  uint32_t tref = 0;
#pragma unroll 1
  for (int n = 0; n <= NSEG; n++) {
    const bool more = __builtin_expect(s + 1 < NSEG, 1);
    uint32_t zr = loop_zero<0>(n);
    bool xok = false;
    if (__builtin_expect(s >= 0, 1)) {
      if (__builtin_expect(s > 0, 1)) {
        const uint32_t dst = sb + OFF_MEM + WG * 8192 + t16 + ((lv >> 5) & 12);
        uint32_t tries = zr;
#pragma unroll 1
        do {
          if (tries) { const char* src = gptr(xhi, xm + WG * 8192 + slot_off(sv)); tref += T_SLIP; WAIT_UNTIL(tref, aV[0], 1, -1); gather_issue(sb + OFF_MEM + WG * 8192 + tv, src); }
          KEEPALIVE(aV[0], zr);
          cp_async_wait_group<0>();
        } while (gather_incomplete<1, 0>(dst) && ++tries < POLL_LIMIT);
        named_bar(1 + WG, 128);
      }
      const uint32_t a_mem = sb + OFF_MEM + WG * 8192 + l16;
      float c[2][4];
      c[0][0] = c[0][1] = c[0][2] = c[0][3] = c[1][0] = c[1][1] = c[1][2] = c[1][3] = 0.f;
      constexpr int NBUF = (48 - 8 - 4 * O_FIX) / 4;
      uint32_t b[NBUF][4];
#pragma unroll
      for (int p = 0; p < NBUF - 1; p++) ldsm_x4_t(b[p], a_mem + p * 512);
#pragma unroll
      for (int p = 0; p < 16; p++) {
        if (p + NBUF - 1 < 16) ldsm_x4_t(b[(p + NBUF - 1) % NBUF], a_mem + (p + NBUF - 1) * 512);
        if (p < 8) { mma16816(c[0], aV[2 * p], b[p % NBUF][0], b[p % NBUF][1]); mma16816(c[1], aV[2 * p + 1], b[p % NBUF][2], b[p % NBUF][3]); }
        else { mma16816(c[0], rot[2 * p - 16], b[p % NBUF][0], b[p % NBUF][1]); mma16816(c[1], rot[2 * p - 15], b[p % NBUF][2], b[p % NBUF][3]); }
      }
      xok = mbar_test(sb + BAR_X + 8 * WG, n & 1);
      SFENCE(15);
      const float4 own = make_float4(c[0][0] + c[1][0], c[0][1] + c[1][1], c[0][2] + c[1][2], c[0][3] + c[1][3]);
      NEWZ(1);
      const uint32_t pvm = WG == 0 ? xvm + slot_off(sv) : 0;
      if (WG == 1) sts128f(sb + OFF_VPX + wq * 512 + l16, own);
      named_bar(3, 256);
      if (WG == 0) {
        const float4 o = lds128f(sb + OFF_VPX + wq * 512 + l16);
        st_relaxed2(gptr(xhi, pvm), pack_bf16(own.x + o.x, own.y + o.y), pack_bf16(own.z + o.z, own.w + o.w));
      }
    }
    auto token_pv = [&](int seg, bool staged) {
      constexpr int NU = 2 - WG;
      uint4 pt0, pt1, v0[NU], v1[NU]; uint32_t pm0, pm1; uint2 vm[NU];
      const uint32_t ap = l16 + WG * 4096 + xo::PT, am = (lv >> 2) + WG * 4096 + xo::PM;
      const uint32_t at = ovt - WG * 512;
      if (staged) {
        const uint32_t b = sb + OFF_MEM;
        pt0 = lds128(b + ap); pt1 = lds128(b + ap + 2048); pm0 = lds32(b + am); pm1 = lds32(b + am + 2048);
#pragma unroll
        for (int u = 0; u < NU; u++) { v0[u] = lds128(b + at - u * 2048); v1[u] = lds128(b + at + 512 - u * 2048); vm[u] = lds64(b + ovm - u * 2048); }
      } else {
        const uint32_t b = lds32(sb + CT_HEAD) + slot_off(seg);
        pt0.x = EMPTY;
#pragma unroll
        for (int u = 0; u < NU; u++) {
          v0[u] = ld_relaxed4(gptr(xhi, b + at) - u * 2048); v1[u] = ld_relaxed4(gptr(xhi, b + at) + 512 - u * 2048);
          vm[u] = ld_relaxed2(gptr(xhi, b + ovm) - u * 2048);
        }
      }
      const bool odd = lv & 16;
      char* op = gptr(xhi, lds32(sb + CT_O) + (seg * SEG + WG * 16 + (lv >> 6)) * (HD * 2) + wq * 32 + (lv & 16) + ((lv >> 2) & 8));
      if (!staged || __builtin_expect(warp_incomplete(umax4(pt0.x, pt1.x, pm0, pm1)), 0)) {
        const uint32_t b = lds32(sb + CT_HEAD) + slot_off(seg);
        uint32_t tries = zr;
#pragma unroll 1
        do {
          pt0 = ld_relaxed4(gptr(xhi, b + ap)); pt1 = ld_relaxed4(gptr(xhi, b + ap) + 2048);
          pm0 = ld_relaxed1(gptr(xhi, b + am)); pm1 = ld_relaxed1(gptr(xhi, b + am) + 2048);
        } while (warp_incomplete(umax4(pt0.x, pt1.x, pm0, pm1)) && ++tries < POLL_LIMIT);
      }
      const uint32_t pa[4] = {pt0.x, pt1.x, pt0.y, pt1.y}, pb[4] = {pt0.z, pt1.z, pt0.w, pt1.w};
#pragma unroll
      for (int u = 0; u < NU; u++) {
        float o0[4] = {0.f, 0.f, 0.f, 0.f}, o1[4] = {0.f, 0.f, 0.f, 0.f};
        mma1688(o0, pm0, pm1, vm[u].x); mma1688(o1, pm0, pm1, vm[u].y);
        mma16816(o0, pa, v0[u].x, v0[u].y); mma16816(o1, pa, v1[u].x, v1[u].y);
        if (WG) { mma16816(o0, pb, v0[u].z, v0[u].w); mma16816(o1, pb, v1[u].z, v1[u].w); }
#pragma unroll
        for (int r = 0; r < 2; r++) {
          const uint32_t w0 = pack_bf16(o0[2 * r], o0[2 * r + 1]), w1 = pack_bf16(o1[2 * r], o1[2 * r + 1]);
          const uint32_t rv = __shfl_xor_sync(~0u, odd ? w0 : w1, 1);
          asm volatile("st.global.v2.u32 [%0], {%1, %2};" ::"l"(op + r * 8 * HD * 2 - u * 64), "r"(odd ? rv : w0), "r"(odd ? w1 : rv) : "memory");
        }
      }
    };
    if (!more) {
      named_bar(3, 256);
      if (upper_warps) {
#pragma unroll 1
        for (int seg = NSEG - 2; seg < NSEG; seg++) token_pv(seg, false);
      }
      break;
    }
    {
      if (__builtin_expect(s > 0, 1)) {
        const uint32_t o = WG ? ovt - 512 : tv + 512;
        const char* src = gptr(xhi, lds32(sb + CT_HEAD) + slot_off(sv - 1) + o);
#pragma unroll
        for (int i = 0; i < 3 - WG; i++) cp_async16(sb + OFF_MEM + o + i * 512, src + i * 512);
        cp_async_commit();
      }
      bool xw;
      {
        float acc[16];
        if (__builtin_expect(!xok, 0)) mbar_wait<0>(sb + BAR_X + 8 * WG, (s + 1) & 1);
        wg_fence();
#pragma unroll
        for (int ks = 0; ks < 16; ks++) wgmma_m64n32_rs(acc, rot[ks], xdesc<WG>(16 + ks), ks != 0);
        wg_commit();
#pragma unroll
        for (int ks = 0; ks < 16; ks++) wgmma_m64n32_rs(acc, aV[ks], xdesc<WG>(ks), 1);
        wg_commit();
        SFENCE(50);
        NEWZ(2);
        xw = warp_is(3) && s + 2 < NSEG;
        tref += lds32(sb + CT_T + 4) + (WG * T_LAG - T_SLIP);
        const uint32_t pvt = xvt + slot_off(sv + 1), awo = sb + wo_addr(tv);
        if (WG == 0 && warp_is(1) && s >= 0) expect_elect(sb + BAR_EX, 512);
        if (xw) {
          expect_elect(sb + BAR_X + 8 * WG, 32768);
          if (WG == 1 && s == NSEG - 3) asm volatile("griddepcontrol.launch_dependents;");
          if (WG == 1 && s + 5 < NSEG) prefetch_l2(maps.xp + (s + 5) * 65536 + lds32(sb + CT_PF), 1024);
        }
        wg_wait<1>();
        if (xw) { named_bar(4 + WG, 128); issue_x(sb, &maps.xq, s + 2, WG, 1); }
        else if (s + 2 < NSEG) named_bar_arrive(4 + WG, 128);
        if (__builtin_expect(s == 0, 0)) {
          mbar_wait(sb + BAR_P + 16, 0);
#pragma unroll
          for (int ks = 16 - O_FIX; ks < 16; ks++) ldsm_x4_t(bO[ks], (awo ^ 32) + (ks & 7) * 1024);
        }
#pragma unroll
        for (int ks = 0; ks < 16 - O_FIX; ks++) ldsm_x4_t(bO[ks], (ks < 8 ? awo : awo ^ 32) + (ks & 7) * 1024);
        wg_wait<0>();
        acc_fence(acc);
        constexpr int K = WG * 2, G = 2 - K;
        sts128f(sb + OFF_RED + WG * 1024 + t16, make_float4(acc[G], acc[G + 1], acc[4 + G], acc[5 + G]));
        sts128f(sb + OFF_RED + WG * 1024 + 512 + t16, make_float4(acc[8 + G], acc[9 + G], acc[12 + G], acc[13 + G]));
        cp_async_wait_group<0>();
        named_bar(3, 256);
        const float4 o0 = lds128f(sb + OFF_RED + (WG ^ 1) * 1024 + t16), o1 = lds128f(sb + OFF_RED + (WG ^ 1) * 1024 + 512 + t16);
        st_relaxed4(gptr(xhi, pvt),
                    pack_bf16(acc[K] + o0.x, acc[K + 1] + o0.y), pack_bf16(acc[4 + K] + o0.z, acc[5 + K] + o0.w),
                    pack_bf16(acc[8 + K] + o1.x, acc[9 + K] + o1.y), pack_bf16(acc[12 + K] + o1.z, acc[13 + K] + o1.w));
      }
      if (__builtin_expect(s >= 0, 1)) {
        uint32_t tries = 0;
#pragma unroll
        for (int ks = 0; ks < 16 - O_FIX; ks++) tries |= bO[ks][0];
        const char* po = gptr(xhi, xom + slot_off(sv) + (tries & zr));
        tries = zr;
        float d[2][2][4];
        uint32_t mx;
#pragma unroll 1
        do {
          tref += T_SLIP;
          WAIT_UNTIL(tref, aV[0], 1, 1);
          uint4 o[8];
#pragma unroll
          for (int i = 0; i < 4; i++) o[i] = ld_relaxed4(po + i * 512);
#pragma unroll
          for (int i = 0; i < 4; i++) o[4 + i] = ld_relaxed4(po + 16384 + i * 512);
          __syncwarp();
#pragma unroll
          for (int i = 0; i < 2; i++)
#pragma unroll
            for (int q = 0; q < 2; q++) { d[i][q][0] = d[i][q][1] = d[i][q][2] = d[i][q][3] = 0.f; }
#pragma unroll
          for (int i = 0; i < 4; i++) {
            mma16816(d[0][0], aO[2 * i], o[i].x, o[i].y); mma16816(d[1][0], aO[8 + 2 * i], o[i].x, o[i].y);
            mma16816(d[0][1], aO[2 * i + 1], o[i].z, o[i].w); mma16816(d[1][1], aO[9 + 2 * i], o[i].z, o[i].w);
          }
          mx = umax4(o[0].w, o[1].w, o[2].w, o[3].w);
          SFENCE(33 + tries);
#pragma unroll
          for (int i = 0; i < 4; i++) {
            mma16816(d[0][0], bO[2 * i], o[4 + i].x, o[4 + i].y); mma16816(d[1][0], bO[8 + 2 * i], o[4 + i].x, o[4 + i].y);
            mma16816(d[0][1], bO[2 * i + 1], o[4 + i].z, o[4 + i].w); mma16816(d[1][1], bO[9 + 2 * i], o[4 + i].z, o[4 + i].w);
          }
          mx = max(mx, umax4(o[4].w, o[5].w, o[6].w, o[7].w));
        } while (warp_incomplete(mx) && ++tries < POLL_LIMIT);
        NEWZ(3);
        const uint32_t rd = sb + OFF_RED + (WG ^ 1) * 1024 + t16;
        sts128f(rd, make_float4(d[0][0][0] + d[0][1][0], d[0][0][1] + d[0][1][1], d[0][0][2] + d[0][1][2], d[0][0][3] + d[0][1][3]));
        sts128f(rd + 512, make_float4(d[1][0][0] + d[1][1][0], d[1][0][1] + d[1][1][1], d[1][0][2] + d[1][1][2], d[1][0][3] + d[1][1][3]));
        if (upper_warps) {
          named_bar_arrive(7, 256);
          if (xw) issue_x(sb, &maps.xq, s + 2, WG, 0);
          if (__builtin_expect(s > 0, 1)) token_pv(sv - 1, true);
        } else {
          uint32_t mp = lds32(sb + CT_MP) + (lv >> 2);
          named_bar(7, 256);
          float4 p[8];
#pragma unroll
          for (int i = 0; i < 8; i++) p[i] = lds128f(sb + OFF_RED + lv + wq * 512 + i * 1024);
          float4 r;
          r.x = ((p[0].x + p[1].x) + (p[2].x + p[3].x)) + ((p[4].x + p[5].x) + (p[6].x + p[7].x));
          r.y = ((p[0].y + p[1].y) + (p[2].y + p[3].y)) + ((p[4].y + p[5].y) + (p[6].y + p[7].y));
          r.z = ((p[0].z + p[1].z) + (p[2].z + p[3].z)) + ((p[4].z + p[5].z) + (p[6].z + p[7].z));
          r.w = ((p[0].w + p[1].w) + (p[2].w + p[3].w)) + ((p[4].w + p[5].w) + (p[6].w + p[7].w));
          const bool w0 = warp_is(0);
          if (w0) st_async4(rsb + OFF_RX + lv, __float_as_uint(r.x), __float_as_uint(r.y), __float_as_uint(r.z), __float_as_uint(r.w), rsb + BAR_EX);
          if (!w0) {
            char* pp = gptr(xhi, mp + slot_off(sv + 1));
            mbar_wait(sb + BAR_EX, s & 1);
            const float4 q = lds128f(sb + OFF_RX + l16);
            st_relaxed1(pp, pack_bf16(r.x + q.x, r.y + q.y)); st_relaxed1(pp + 128, pack_bf16(r.z + q.z, r.w + q.w));
            pp = gptr(xhi, mp + slot_off(sv + 3));
            st_relaxed1(pp, EMPTY); st_relaxed1(pp + 128, EMPTY);
          }
        }
        NEWZ(4);
        const char* src = gptr(xhi, xm + WG * 8192 + slot_off(sv + 1));
        const uint32_t awv = sb + wv_addr(tv) + OFF_WVR;
        tref += lds32(sb + CT_T + 8) - WG * T_LAG;
        named_bar(8, 256);
#pragma unroll
        for (int ks = 0; ks < V_PRE; ks++) ldsm_x4_t(rot[ks], awv + ks * 2048);
        WAIT_UNTIL(tref, aV[0], 1, 2);
        gather_issue(sb + OFF_MEM + WG * 8192 + tv, src);
#pragma unroll
        for (int ks = V_PRE; ks < 16; ks++) ldsm_x4_t(rot[ks], awv + ks * 2048);
        NEWZ(6);
        st_relaxed4(gptr(xhi, xvt + slot_off(sv + 2)), EMPTY, EMPTY, EMPTY, EMPTY);
        if (WG == 0) st_relaxed2(gptr(xhi, xvm + slot_off(sv + 2)), EMPTY, EMPTY);
      } else {
        load_v(tv);
        if (xw) issue_x(sb, &maps.xq, s + 2, WG, 0);
        mbar_wait(sb + BAR_P + 8, 0);
#pragma unroll
        for (int ks = 0; ks < 8; ks++) { ldsm_x4_t(aO[ks], sb + wo_addr(tv) + ks * 1024); ldsm_x4_t(aO[8 + ks], sb + (wo_addr(tv) ^ 32) + ks * 1024); }
        named_bar(0, 256);
        if (threadIdx.x == 0) {
          fence_async_smem();
          mbar_expect_tx(sb + BAR_P + 16, 4 * 16384);
          for (int q = 0; q < 4; q++) tma_load_2d(sb + OFF_WOR + q * 16384, &maps.wo, h * 32, j * 2048 + 1024 + q * 256, sb + BAR_P + 16);
        }
        __syncwarp();
        tref = gtime() / T_SLIP * T_SLIP - T_SLIP;
      }
    }
  }
}

#undef j
#undef s
#undef sv
#undef xm
#undef wq

__global__ void __launch_bounds__(256, 1) __cluster_dims__(2, 1, 1)
chain_kernel(const __grid_constant__ ChainMaps maps, const bf16* __restrict__ mem0, const uint64_t xbase) {
  using namespace chain;
  extern __shared__ uint8_t smem_raw[];
  uint32_t sb = smem_u32(smem_raw);
  PIN(sb);
  if (sb != SB_LO + (blockIdx.x & 1) * RANK_BIT || mapa(sb, (blockIdx.x & 1) ^ 1) != (sb ^ RANK_BIT)) __trap();
  const int tid = threadIdx.x;
  const int h = blockIdx.x >> 2, role = (blockIdx.x >> 1) & 1, j = blockIdx.x & 1;
  if (tid == 0) {
    for (int i = 0; i < 9; i++) mbar_init(sb + OFF_BAR + 8 * i, 1);
    asm volatile("fence.mbarrier_init.release.cluster;" ::: "memory");
    const uint32_t xl = (uint32_t)xbase;
    sts32(sb + CT_BASE, xl); sts32(sb + CT_HEAD, xl + h * xo::HEAD); sts32(sb + CT_OM, xl + xo::OM + (role ? j * 32768 : h * 2048));
    sts32(sb + CT_MP, xl + xo::MEM + (h * 2 + j) * 256); sts32(sb + CT_O, xl + xo::O + (h * 2 + j) * 128); sts32(sb + CT_PF, (h * 2 + j) * 1024);
    sts32(sb + CT_TT, sb + (j ? OFF_KT : OFF_QT));
    if (role == 0) {
      const CUtensorMap* wm = j ? &maps.wk : &maps.wq;
      mbar_expect_tx(sb + BAR_P, 6 * 16384);
      for (int c = 0; c < 3; c++)
        for (int q = 0; q < 2; q++) tma_load_2d(sb + OFF_X + (q * 3 + c) * 16384, wm, h * DH + q * 64, q * 512 + c * 128, sb + BAR_P);
      mbar_expect_tx(sb + BAR_P + 8, 4 * 16384);
      for (int c = 0; c < 2; c++)
        for (int q = 0; q < 2; q++) tma_load_2d(sb + OFF_X + (6 + q * 2 + c) * 16384, wm, h * DH + (q ^ 1) * 64, q * 512 + c * 128, sb + BAR_P + 8);
      mbar_expect_tx(sb + BAR_P + 24, 4 * 16384);
      for (int q = 0; q < 2; q++)
        for (int o = 0; o < 2; o++) tma_load_2d(sb + OFF_WS + (q * 2 + o) * 16384, wm, h * DH + (q ^ o) * 64, q * 512 + 384, sb + BAR_P + 24);
      for (int q = 0; q < 2; q++) tma_prefetch_2d(wm, h * DH + (q ^ 1) * 64, q * 512 + 256);
    } else {
      mbar_expect_tx(sb + BAR_P, 8 * 16384);
      for (int q = 0; q < 4; q++) tma_load_2d(sb + OFF_WOR + q * 16384, &maps.wv, h * DH + j * 64, (q >> 1) * 512 + (q & 1) * 128, sb + BAR_P);
      for (int q = 0; q < 4; q++) tma_load_2d(sb + OFF_WVR + q * 16384, &maps.wv, h * DH + j * 64, (q >> 1) * 512 + 256 + (q & 1) * 128, sb + BAR_P);
    }
  }
  for (int r = 0; r < RING; r++) {
    char* p = (char*)xbase + r * xo::SLOT;
    const int wq = (tid >> 5) & 3;
    if (role == 1) st_relaxed4(p + h * xo::HEAD + xo::VT + (8 * j + 2 * wq + (tid >> 7)) * 512 + (tid & 31) * 16, EMPTY, EMPTY, EMPTY, EMPTY);
    else if (j == 0) st_relaxed4(p + (tid < 128 ? xo::OM + h * 2048 + tid * 16 : h * xo::HEAD + wq * 2048 + xo::VM + (tid & 31) * 16), EMPTY, EMPTY, EMPTY, EMPTY);
    else {
      st_relaxed4(p + h * xo::HEAD + (tid >> 6) * 2048 + 1024 + (tid & 63) * 16, EMPTY, EMPTY, EMPTY, EMPTY);
      if (tid < 32) st_relaxed4(p + xo::MEM + h * 512 + tid * 16, EMPTY, EMPTY, EMPTY, EMPTY);
    }
  }
  __syncthreads();
  if (__shfl_sync(0xffffffffu, tid >> 5, 0) == 0) {
    uint32_t t[2], c[2], ka[4] = {0, 0, 0, 0};
    const uint32_t z = maps.t_step >> 24;
#pragma unroll
    for (int i = 0; i < 2; i++) {
      const uint32_t end = (gtime() & ~31u) + (i ? 2048 : 1024);
      for (int g = z; g < 256 && (int)(gtime() - (end - 96)) < 0; g++) KEEPALIVE(ka, z);
      for (int g = z; g < 256 && (int)((t[i] = gtime()) - end) < 0; g++) {}
      c[i] = (uint32_t)clock64();
    }
    uint32_t v = 0, target = 0;
    if (tid == 0) {
      st_relaxed1(&g_rate[blockIdx.x], (t[1] - t[0]) * 4096u / (c[1] - c[0]));
      __threadfence();
      target = (atomicAdd(&g_epoch, 1u) & ~127u) + 128u;
    }
    target = __shfl_sync(0xffffffffu, target, 0);
    int guard = 0;
    do { asm volatile("ld.acquire.gpu.global.u32 %0, [%1];" : "=r"(v) : "l"(&g_epoch) : "memory"); }
    while (__any_sync(0xffffffffu, (int)(v - target) < 0) && ++guard < (1 << 20));
    const uint4 r4 = ld_relaxed4(&g_rate[tid * 4]);
    uint32_t r = min(__reduce_max_sync(0xffffffffu, umax4(r4.x, r4.y, r4.z, r4.w)), 4 * RATE0);
    if (r < RATE0 + 28) r = RATE0;
    const uint32_t a = (maps.t_step * r / RATE0 + 31) & ~31u, b = (maps.t_phase * r / RATE0 + 31) & ~31u;
    sts128(sb + CT_T, make_uint4(a, b, a - b, r));
  }
  const uint32_t xhi = (uint32_t)(xbase >> 32);
  const int wg = __shfl_sync(0xffffffffu, tid >> 7, 0);
  if (role == 0) {
    if (wg == 0) role_a<0>(maps, mem0, sb, xhi); else role_a<1>(maps, mem0, sb, xhi);
  } else {
    if (wg == 0) role_v<0>(maps, mem0, sb, xhi); else role_v<1>(maps, mem0, sb, xhi);
  }
  __syncwarp();
  cluster_arrive();
  cluster_wait();
}

struct BMaps {
  CUtensorMap q, k, v, out, k8;
  const bf16 *shift_k, *ssm_k, *ssm_D;
};

#define B_SLEEP 200
namespace bp {
constexpr int U_PITCH = (2048 + 128) * 2 + 16;
constexpr int KR_WORDS = 1048;
constexpr int KR_PITCH = 8704;
constexpr int OFF_U = 0;
constexpr int OFF_KR = (8 * U_PITCH + 127) / 128 * 128;
constexpr int Q_OFF = 4352;
constexpr int OFF_BAR = OFF_KR + 8 * KR_PITCH;
constexpr int GROUP_BYTES = OFF_BAR + 128;
constexpr int SMEM = 2 * GROUP_BYTES + 128;
constexpr int NTASK = DM / 8;
static_assert(Q_OFF >= 4224 && Q_OFF + 4096 <= KR_PITCH, "staging does not fit");
}

__device__ __forceinline__ uint32_t bmul2(uint32_t a, uint32_t b) { uint32_t r; asm("mul.rn.bf16x2 %0, %1, %2;" : "=r"(r) : "r"(a), "r"(b)); return r; }
__device__ __forceinline__ uint32_t badd2(uint32_t a, uint32_t b) { uint32_t r; asm("add.rn.bf16x2 %0, %1, %2;" : "=r"(r) : "r"(a), "r"(b)); return r; }

__device__ __forceinline__ void mbar_wait_sleep(uint32_t bar, uint32_t parity) {
  int guard = 0;
  while (!mbar_try(bar, parity)) { __nanosleep(B_SLEEP); if (++guard > (1 << 22)) __trap(); }
}

__device__ __forceinline__ void bpart_body(const BMaps& maps, int first, int stride, int end) {
  using namespace bp;
  extern __shared__ uint8_t smem_all[];
  const int grp = __shfl_sync(0xffffffffu, threadIdx.x >> 8, 0);
  const int lane = keep(threadIdx.x & 31), g = lane >> 2, t = lane & 3;
  const int w = __shfl_sync(0xffffffffu, (threadIdx.x >> 5) & 7, 0);
  const uint32_t sb = ((smem_u32(smem_all) + 127) & ~127u) + grp * GROUP_BYTES;
  const uint32_t kr = sb + OFF_KR + w * KR_PITCH, bar_k = sb + OFF_BAR + 8 * w, bar_q = bar_k + 64;
  if (lane == 0) { mbar_init(bar_k, 1); mbar_init(bar_q, 1); asm volatile("fence.mbarrier_init.release.cluster;" ::: "memory"); }
  if (lane < 16) sts128(sb + OFF_U + w * U_PITCH + lane * 16, make_uint4(0, 0, 0, 0));
  __syncwarp();
  if (grp == 1) { named_bar_arrive(3, 512); named_bar(5, 512); }
  const int lm = lane >> 3, lr = lane & 7;
  uint32_t ph = 0;
  for (int task = first + grp; task < end; task += stride, ph ^= 1) {
    const int d0 = task * 8;
    uint4 x[8];
    {
      const uint4* kf = (const uint4*)(maps.ssm_k + (size_t)(d0 + w) * S_LEN);
#pragma unroll
      for (int it = 0; it < 8; it++) x[it] = __ldg(kf + it * 32 + lane);
    }
    const uint4 ska = __ldg((const uint4*)(maps.shift_k + (d0 + 2 * t) * 4));
    __syncwarp();
    if (lane == 0) {
      mbar_expect_tx(bar_k, 2 * 4096 + 128);
      tma_load_2d(kr + 4096, &maps.k8, d0, w * 256 + 248, bar_k);
      tma_load_2d(kr, &maps.k, d0, w * 256 - 8, bar_k);
      bulk_wait_read<0>();
      tma_load_2d(kr + Q_OFF, &maps.v, d0, w * 256, bar_k);
    }
    __syncwarp();
    if (task == first) named_bar_arrive(5, 512);
    const uint32_t sk[4] = {__byte_perm(ska.x, ska.z, 0x5410), __byte_perm(ska.x, ska.z, 0x7632), __byte_perm(ska.y, ska.w, 0x5410), __byte_perm(ska.y, ska.w, 0x7632)};
    mbar_wait_sleep(bar_k, ph);
    {
      const uint32_t ka = kr + (lane + 8) * 16;
#pragma unroll
      for (int i = 0; i < 8; i++) {
        uint32_t k0[4], k1[4], k2[4], k3[4], v[4], r[4];
        ldsm_x4(k3, ka + i * 512 - 48); ldsm_x4(k2, ka + i * 512 - 32); ldsm_x4(k1, ka + i * 512 - 16); ldsm_x4(k0, ka + i * 512);
        ldsm_x4(v, ka + (Q_OFF - 128) + i * 512);
#pragma unroll
        for (int b = 0; b < 4; b++) {
          uint32_t acc = bmul2(k3[b], sk[3]);
          acc = badd2(acc, bmul2(k2[b], sk[2]));
          acc = badd2(acc, bmul2(k1[b], sk[1]));
          acc = badd2(acc, bmul2(k0[b], sk[0]));
          r[b] = bmul2(acc, v[b]);
        }
        const int ch = 16 + w * 32 + i * 4 + lm;
        stsm_x4_t(sb + OFF_U + lr * U_PITCH + ((ch ^ ((ch >> 3) & 1)) << 4), r[0], r[1], r[2], r[3]);
      }
    }
    __syncwarp();
    {
      const uint32_t c0 = kr, c1 = c0 + (KR_WORDS + 16) * 4;
      uint32_t carry = 0;
#pragma unroll
      for (int it = 0; it < 8; it++) {
        const int blk = it * 32 + lane;
        uint32_t prev = __shfl_up_sync(0xffffffffu, x[it].w, 1);
        if (lane == 0) prev = carry;
        carry = __shfl_sync(0xffffffffu, x[it].w, 31);
        sts128(c0 + (1028 - 4 * blk) * 4, make_uint4(__byte_perm(x[it].w, 0, 0x1032), __byte_perm(x[it].z, 0, 0x1032),
                                                     __byte_perm(x[it].y, 0, 0x1032), __byte_perm(x[it].x, 0, 0x1032)));
        sts128(c1 + (1028 - 4 * blk) * 4, make_uint4(__byte_perm(x[it].w, x[it].z, 0x7610), __byte_perm(x[it].z, x[it].y, 0x7610),
                                                     __byte_perm(x[it].y, x[it].x, 0x7610), __byte_perm(x[it].x, prev, 0x7610)));
      }
      if (lane < 4) { sts128(c0 + (1032 + 4 * lane) * 4, make_uint4(0, 0, 0, 0)); sts128(c1 + (1032 + 4 * lane) * 4, make_uint4(0, 0, 0, 0)); }
      __syncwarp();
    }
    named_bar(3 + grp, 512);
    float acc[16][4];
#pragma unroll
    for (int jn = 0; jn < 16; jn++) { acc[jn][0] = acc[jn][1] = acc[jn][2] = acc[jn][3] = 0.f; }
    {
      const uint32_t ub = sb + OFF_U + w * U_PITCH;
      uint32_t kd = kr + (((g & 1) ? 0 : KR_WORDS + 16) + ((((g & 1) ? 2063 : 2062) - (g - 2 * t)) >> 1)) * 4;
      uint32_t uc = 2 * (8 + lr + (lm >> 1) * 8) + (lm & 1);
#pragma unroll 1
      for (int d0s = 0; d0s < 8; d0s++, kd -= 32, uc -= 2) {
        const uint32_t uf = ub + ((uc ^ ((uc >> 3) & 1)) << 4);
        uint32_t A[3][4];
        A[0][0] = lds32v(kd); A[0][1] = lds32v(kd - 16); A[0][2] = lds32v(kd + 16); A[0][3] = lds32v(kd);
        uint32_t F[8][4];
#pragma unroll
        for (int m = 7; m >= 0; m--) ldsm_x4(F[m], uf + m * 512);
#pragma unroll
        for (int i = 0; i < 16; i++) {
          if (i + 1 < 16) {
            A[(i + 1) % 3][0] = lds32v(kd - 256 * (i + 1)); A[(i + 1) % 3][1] = lds32v(kd - 256 * (i + 1) - 16);
            A[(i + 1) % 3][2] = lds32v(kd - 256 * (i + 1) + 16); A[(i + 1) % 3][3] = lds32v(kd - 256 * (i + 1));
          }
#pragma unroll
          for (int jn = 15; jn >= i; jn--) mma16816(acc[jn], A[i % 3], F[(jn - i) >> 1][((jn - i) & 1) * 2], F[(jn - i) >> 1][((jn - i) & 1) * 2 + 1]);
        }
      }
    }
    named_bar_arrive(3 + (grp ^ 1), 512);
    __syncwarp();
    fence_async_smem();
    __syncwarp();
    if (lane == 0) { mbar_expect_tx(bar_q, 4096); tma_load_2d(kr + Q_OFF, &maps.q, d0, w * 256, bar_q); }
    const uint32_t dpair = __ldg((const uint32_t*)(maps.ssm_D + d0) + t);
    {
      const uint32_t ya = kr + w * 16 + (((lm >> 1) * 8 + lr) * 32) + (lm & 1) * 16;
#pragma unroll
      for (int jn = 0; jn < 16; jn += 2)
        stsm_x4_t(ya + jn * 256, pack_bf16(acc[jn][0], acc[jn][1]), pack_bf16(acc[jn][2], acc[jn][3]),
                  pack_bf16(acc[jn + 1][0], acc[jn + 1][1]), pack_bf16(acc[jn + 1][2], acc[jn + 1][3]));
    }
    named_bar(1 + grp, 256);
    mbar_wait_sleep(bar_q, ph);
    {
      const uint32_t ya = sb + OFF_KR + lr * (KR_PITCH + 16) + (w * 256 + lm * 8) * 2;
#pragma unroll
      for (int i = 0; i < 8; i++) {
        uint32_t y[4], u[4], q[4], r[4];
        ldsm_x4(q, kr + Q_OFF + lane * 16 + i * 512);
        ldsm_x4_t(y, ya + i * 64);
        const int ch = 16 + w * 32 + i * 4 + lm;
        ldsm_x4_t(u, sb + OFF_U + lr * U_PITCH + ((ch ^ ((ch >> 3) & 1)) << 4));
#pragma unroll
        for (int b = 0; b < 4; b++) r[b] = bmul2(q[b], badd2(y[b], bmul2(u[b], dpair)));
        stsm_x4(kr + Q_OFF + lane * 16 + i * 512, r[0], r[1], r[2], r[3]);
      }
      fence_async_smem();
      __syncwarp();
      if (lane == 0) { tma_store_2d(&maps.out, kr + Q_OFF, DM + d0, w * 256); bulk_commit(); }
    }
    named_bar(1 + grp, 256);
  }
  if (lane == 0) bulk_wait<0>();
}

__global__ void __launch_bounds__(512, 1) __cluster_dims__(2, 1, 1) bpart_kernel(const __grid_constant__ BMaps maps, int end) {
  bpart_body(maps, blockIdx.x * 2, gridDim.x * 2, end);
}

struct GemmMaps {
  CUtensorMap o;
  CUtensorMap w;
  CUtensorMap c;
};
namespace k3 {
constexpr int STAGES = 6;
constexpr int W_BYTES = 2 * 8192, O_BYTES = K3_N * 128, STAGE_BYTES = W_BYTES + O_BYTES;
constexpr int TT = (S_LEN + K3_N - 1) / K3_N, NGEMM = TT * (DM / 128), NB = 128 - NGEMM, KSTEPS = HD / 64;
constexpr int SMEM_G = STAGES * STAGE_BYTES + 1024 + 256;
constexpr int SMEM = SMEM_G > bp::SMEM ? SMEM_G : bp::SMEM;
static_assert(STAGE_BYTES % 1024 == 0, "swizzle atoms");
}

__global__ void __launch_bounds__(512, 1)
tail_kernel(const __grid_constant__ GemmMaps maps, const __grid_constant__ BMaps bmaps) {
  using namespace k3;
  if (blockIdx.x < NB) {
    bpart_body(bmaps, bp::NTASK - 2 * NB + 2 * blockIdx.x, bp::NTASK, bp::NTASK);
    return;
  }
  extern __shared__ uint8_t smem_raw[];
  const uint32_t sbase = (smem_u32(smem_raw) + 1023) & ~1023u;
  const uint32_t bars = sbase + STAGES * STAGE_BYTES;
  const int tid = threadIdx.x, warp = tid >> 5;
  const int tt = (blockIdx.x - NB) / 8, ct = (blockIdx.x - NB) % 8;

  if (tid == 0) {
    for (int s = 0; s < STAGES; s++) { mbar_init(bars + 8 * s, 1); mbar_init(bars + 8 * (STAGES + s), 2); }
    asm volatile("fence.mbarrier_init.release.cluster;" ::: "memory");
  }
  __syncthreads();

  if (warp >= 8) {
    if (tid == 256) {
      tma_prefetch_desc(&maps.o);
      for (int k = 0; k < STAGES; k++) {
        const uint32_t full = bars + 8 * k, sa = sbase + k * STAGE_BYTES;
        mbar_expect_tx(full, STAGE_BYTES);
#pragma unroll
        for (int j = 0; j < 2; j++) tma_load_2d(sa + j * 8192, &maps.w, ct * 128 + j * 64, k * 64, full);
      }
      asm volatile("griddepcontrol.wait;" ::: "memory");
      int stage = 0; uint32_t ph = 1;
      for (int k = 0; k < KSTEPS; k++) {
        mbar_wait(bars + 8 * (STAGES + stage), ph);
        const uint32_t full = bars + 8 * stage, sa = sbase + stage * STAGE_BYTES;
        const bool pre = k < STAGES;
        if (!pre) mbar_expect_tx(full, STAGE_BYTES);
        tma_load_2d(sa + W_BYTES, &maps.o, k * 64, tt * K3_N, full);
        if (!pre) {
#pragma unroll
          for (int j = 0; j < 2; j++) tma_load_2d(sa + j * 8192, &maps.w, ct * 128 + j * 64, k * 64, full);
        }
        if (++stage == STAGES) { stage = 0; ph ^= 1; }
      }
    }
  } else {
    const int wg = warp >> 2, lane = tid & 31, wq = warp & 3;
    int stage = 0; uint32_t ph = 0;
    float acc[K3_N / 2];
    int prev = -1;
    for (int k = 0; k < KSTEPS; k++) {
      mbar_wait(bars + 8 * stage, ph);
      const uint32_t sa = sbase + stage * STAGE_BYTES;
      wg_fence();
#pragma unroll
      for (int kk = 0; kk < 4; kk++) {
        const uint64_t da = make_desc(sa + wg * 8192 + kk * 2048, 16, 1024, 1);
        const uint64_t db = make_desc(sa + W_BYTES + kk * 32, 16, 1024, 1);
        wgmma_k3_ss_ta(acc, da, db, (k | kk) != 0);
      }
      wg_commit();
      if (prev >= 0) { wg_wait<1>(); if ((tid & 127) == 0) mbar_arrive(bars + 8 * (STAGES + prev)); }
      prev = stage;
      if (++stage == STAGES) { stage = 0; ph ^= 1; }
    }
    wg_wait<0>();
#pragma unroll
    for (int i = 0; i < K3_N / 2; i++) asm volatile("" : "+f"(acc[i]) :: "memory");
    named_bar(1, 256);
    const uint32_t ebuf = sbase + wg * STAGE_BYTES;
    const uint32_t ea = ebuf + ((lane >> 4) * 8 + (lane & 7)) * 128 + (((2 * wq + ((lane >> 3) & 1)) ^ (lane & 7)) << 4);
#pragma unroll
    for (int i = 0; i < K3_N / 8; i += 2) {
      const int i1 = i + 1 < K3_N / 8 ? i + 1 : i;
      stsm_x4_t(ea + i * 1024, pack_bf16(acc[4 * i], acc[4 * i + 1]), pack_bf16(acc[4 * i + 2], acc[4 * i + 3]),
                pack_bf16(acc[4 * i1], acc[4 * i1 + 1]), pack_bf16(acc[4 * i1 + 2], acc[4 * i1 + 3]));
    }
    fence_async_smem();
    named_bar(2 + wg, 128);
    if ((tid & 127) == 0) {
      tma_store_2d(&maps.c, ebuf, ct * 128 + wg * 64, tt * K3_N);
      bulk_commit();
      bulk_wait<0>();
    }
  }
}

typedef CUresult (*EncodeFn)(CUtensorMap*, CUtensorMapDataType, cuuint32_t, void*, const cuuint64_t*, const cuuint64_t*,
                             const cuuint32_t*, const cuuint32_t*, CUtensorMapInterleave, CUtensorMapSwizzle,
                             CUtensorMapL2promotion, CUtensorMapFloatOOBfill);

void make_map(EncodeFn enc, CUtensorMap* m, const void* ptr, uint64_t cols, uint64_t rows, uint64_t pitch_elems,
              uint32_t box_cols, uint32_t box_rows, CUtensorMapSwizzle swz,
              CUtensorMapL2promotion promo = CU_TENSOR_MAP_L2_PROMOTION_L2_128B) {
  cuuint64_t dims[2] = {cols, rows};
  cuuint64_t strides[1] = {pitch_elems * 2};
  cuuint32_t box[2] = {box_cols, box_rows};
  cuuint32_t es[2] = {1, 1};
  enc(m, CU_TENSOR_MAP_DATA_TYPE_BFLOAT16, 2, const_cast<void*>(ptr), dims, strides, box, es, CU_TENSOR_MAP_INTERLEAVE_NONE, swz,
      promo, CU_TENSOR_MAP_FLOAT_OOB_FILL_NONE);
}

void make_map_nd(EncodeFn enc, CUtensorMap* m, const void* ptr, int rank, const uint64_t* dims, const uint64_t* strides_elems,
                 const uint32_t* box, CUtensorMapSwizzle swz) {
  cuuint64_t d[5], st[4]; cuuint32_t b[5], es[5];
  for (int i = 0; i < rank; i++) { d[i] = dims[i]; b[i] = box[i]; es[i] = 1; if (i) st[i - 1] = strides_elems[i] * 2; }
  enc(m, CU_TENSOR_MAP_DATA_TYPE_BFLOAT16, rank, const_cast<void*>(ptr), d, st, b, es, CU_TENSOR_MAP_INTERLEAVE_NONE, swz,
      CU_TENSOR_MAP_L2_PROMOTION_L2_128B, CU_TENSOR_MAP_FLOAT_OOB_FILL_NONE);
}

}

extern "C" void kernel_launch(void* const* d_in, const int* in_sizes, int n_in, void* d_out, int out_size) {
  (void)in_sizes; (void)n_in; (void)out_size;
  const bf16* x = (const bf16*)d_in[0];
  const bf16* mem0 = (const bf16*)d_in[1];
  const bf16* Wq = (const bf16*)d_in[2];
  const bf16* Wk = (const bf16*)d_in[3];
  const bf16* Wv = (const bf16*)d_in[4];
  const bf16* Wo = (const bf16*)d_in[5];
  const bf16* Bq = (const bf16*)d_in[7];
  const bf16* Bk = (const bf16*)d_in[8];
  const bf16* Bv = (const bf16*)d_in[9];
  const bf16* shift_k = (const bf16*)d_in[10];
  const bf16* ssm_k = (const bf16*)d_in[11];
  const bf16* ssm_D = (const bf16*)d_in[12];
  bf16* out = (bf16*)d_out;

  static EncodeFn enc = nullptr;
  static uint64_t xbase0;
  static int nsm = 132;
  static cudaStream_t s1;
  static cudaEvent_t ev_fork, ev_join;
  if (!enc) {
    cudaDriverEntryPointQueryResult qr;
    void* fn = nullptr;
    cudaGetDriverEntryPoint("cuTensorMapEncodeTiled", &fn, cudaEnableDefault, &qr);
    enc = (EncodeFn)fn;
    void* ps = nullptr;
    cudaGetSymbolAddress(&ps, g_scratch);
    xbase0 = (uint64_t)ps;
    if ((xbase0 >> 32) != ((xbase0 + xo::BYTES - 1) >> 32)) xbase0 += xo::BYTES;
    cudaFuncSetAttribute(tail_kernel, cudaFuncAttributeMaxDynamicSharedMemorySize, k3::SMEM);
    cudaFuncSetAttribute(chain_kernel, cudaFuncAttributeMaxDynamicSharedMemorySize, chain::SMEM);
    cudaFuncSetAttribute(bpart_kernel, cudaFuncAttributeMaxDynamicSharedMemorySize, bp::SMEM);
    cudaStreamCreateWithFlags(&s1, cudaStreamNonBlocking);
    cudaEventCreateWithFlags(&ev_fork, cudaEventDisableTiming);
    cudaEventCreateWithFlags(&ev_join, cudaEventDisableTiming);
    int dev = 0; cudaGetDevice(&dev);
    cudaDeviceGetAttribute(&nsm, cudaDevAttrMultiProcessorCount, dev);
  }
  uint64_t xbase = xbase0;
  const CUtensorMapSwizzle SW128 = CU_TENSOR_MAP_SWIZZLE_128B, SW64 = CU_TENSOR_MAP_SWIZZLE_64B;
  GemmMaps m3; ChainMaps mc;
  make_map(enc, &m3.o, (void*)(xbase + xo::O), HD, S_LEN, HD, 64, K3_N, SW128);
  make_map(enc, &m3.w, Wo, DM, HD, DM, 64, 64, SW128);
  make_map(enc, &m3.c, out, DM, S_LEN, OUT_LD, 64, K3_N, SW128);
  const CUtensorMapL2promotion P256 = CU_TENSOR_MAP_L2_PROMOTION_L2_256B;
  make_map(enc, &mc.wq, Wq, HD, DM, HD, 64, 128, SW128, P256);
  make_map(enc, &mc.wk, Wk, HD, DM, HD, 64, 128, SW128, P256);
  make_map(enc, &mc.wv, Wv, HD, DM, HD, 64, 128, SW128, P256);
  make_map(enc, &mc.wo, Wo, DM, HD, DM, 32, 256, SW64, P256);
  {
    const uint64_t dx[3] = {64, S_LEN, DM / 64}, sx[3] = {1, DM, 64};
    const uint32_t bx[3] = {64, SEG, 8};
    make_map_nd(enc, &mc.x, x, 3, dx, sx, bx, SW128);
    const uint32_t bq[3] = {64, SEG, 4};
    make_map_nd(enc, &mc.xq, x, 3, dx, sx, bq, SW128);
    mc.xp = (const char*)x;
  }

  const int skip = 0;
  mc.t_step = T_STEP; mc.t_phase = T_PHASE;
  BMaps mb;
  const CUtensorMapSwizzle SWN = CU_TENSOR_MAP_SWIZZLE_NONE;
  make_map(enc, &mb.k, Bk, DM, S_LEN, DM, 8, 256, SWN);
  make_map(enc, &mb.q, Bq, DM, S_LEN, DM, 8, 256, SWN);
  make_map(enc, &mb.v, Bv, DM, S_LEN, DM, 8, 256, SWN);
  mb.shift_k = shift_k; mb.ssm_k = ssm_k; mb.ssm_D = ssm_D;
  make_map(enc, &mb.out, out, OUT_LD, S_LEN, OUT_LD, 8, 256, SWN);
  make_map(enc, &mb.k8, Bk, DM, S_LEN, DM, 8, 8, SWN);
  cudaStream_t s0 = cudaStreamPerThread;
  const int nb = nsm >= 132 ? 4 : 2, ntask1 = bp::NTASK - 2 * k3::NB;
  const bool fork = nsm >= 130 && !(skip & 16);
  if (fork) {
    cudaEventRecord(ev_fork, s0);
    cudaStreamWaitEvent(s1, ev_fork, 0);
    if (!(skip & 1)) bpart_kernel<<<nb, 512, bp::SMEM, s1>>>(mb, ntask1);
    cudaEventRecord(ev_join, s1);
  } else if (!(skip & 1)) {
    bpart_kernel<<<ntask1 / 2, 512, bp::SMEM, s0>>>(mb, ntask1);
  }
  if (!(skip & 4)) chain_kernel<<<128, 256, chain::SMEM, s0>>>(mc, mem0, xbase);
  if (!(skip & 8)) {
    cudaLaunchAttribute pdl[1];
    pdl[0].id = cudaLaunchAttributeProgrammaticStreamSerialization;
    pdl[0].val.programmaticStreamSerializationAllowed = 1;
    cudaLaunchConfig_t cfg = {};
    cfg.gridDim = dim3(128); cfg.blockDim = dim3(512); cfg.dynamicSmemBytes = k3::SMEM; cfg.stream = s0;
    cfg.attrs = pdl; cfg.numAttrs = 1;
    cudaLaunchKernelEx(&cfg, tail_kernel, m3, mb);
  }
  if (fork) cudaStreamWaitEvent(s0, ev_join, 0);
}
```

```cpp
#include <cuda_runtime.h>
#include <cuda_bf16.h>
#include <cuda.h>
#include <stdint.h>

namespace {

constexpr int S_LEN = 2048;
constexpr int DM = 1024;
constexpr int NH = 32;
constexpr int DH = 128;
constexpr int HD = NH * DH;
constexpr int SEG = 32;
constexpr int NSEG = S_LEN / SEG;
constexpr int OUT_LD = 2048;

typedef __nv_bfloat16 bf16;
#define K3_N 160

__device__ __forceinline__ uint32_t smem_u32(const void* p) { return (uint32_t)__cvta_generic_to_shared(p); }

__device__ __forceinline__ void mbar_init(uint32_t bar, uint32_t count) {
  asm volatile("mbarrier.init.shared::cta.b64 [%0], %1;" ::"r"(bar), "r"(count) : "memory");
}
__device__ __forceinline__ void mbar_expect_tx(uint32_t bar, uint32_t bytes) {
  asm volatile("mbarrier.arrive.expect_tx.shared::cta.b64 _, [%0], %1;" ::"r"(bar), "r"(bytes) : "memory");
}
__device__ __forceinline__ void mbar_arrive(uint32_t bar) {
  asm volatile("mbarrier.arrive.shared::cta.b64 _, [%0];" ::"r"(bar) : "memory");
}
__device__ __forceinline__ bool mbar_try(uint32_t bar, uint32_t parity) {
  uint32_t ok;
  asm volatile("{.reg .pred p; mbarrier.try_wait.parity.shared::cta.b64 p, [%1], %2; selp.u32 %0, 1, 0, p;}"
               : "=r"(ok) : "r"(bar), "r"(parity) : "memory");
  return ok;
}
__device__ __forceinline__ bool mbar_test(uint32_t bar, uint32_t parity) {
  uint32_t ok;
  asm volatile("{.reg .pred p; mbarrier.test_wait.parity.shared::cta.b64 p, [%1], %2; selp.u32 %0, 1, 0, p;}"
               : "=r"(ok) : "r"(bar), "r"(parity) : "memory");
  return ok;
}
template <int HINT = 1>
__device__ __forceinline__ void mbar_wait(uint32_t bar, uint32_t parity) {
  int guard = 0;
  while (__builtin_expect(!mbar_try(bar, parity), HINT)) { if (++guard > (1 << 22)) __trap(); }
}
__device__ __forceinline__ void tma_load_2d(uint32_t dst, const CUtensorMap* map, int c0, int c1, uint32_t bar) {
  asm volatile("cp.async.bulk.tensor.2d.shared::cluster.global.mbarrier::complete_tx::bytes [%0], [%1, {%3, %4}], [%2];"
               ::"r"(dst), "l"(map), "r"(bar), "r"(c0), "r"(c1) : "memory");
}
__device__ __forceinline__ void tma_load_3d(uint32_t dst, const CUtensorMap* map, int c0, int c1, int c2, uint32_t bar) {
  asm volatile("cp.async.bulk.tensor.3d.shared::cluster.global.mbarrier::complete_tx::bytes [%0], [%1, {%3, %4, %5}], [%2];"
               ::"r"(dst), "l"(map), "r"(bar), "r"(c0), "r"(c1), "r"(c2) : "memory");
}
__device__ __forceinline__ void tma_load_4d(uint32_t dst, const CUtensorMap* map, int c0, int c1, int c2, int c3, uint32_t bar) {
  asm volatile("cp.async.bulk.tensor.4d.shared::cluster.global.mbarrier::complete_tx::bytes [%0], [%1, {%3, %4, %5, %6}], [%2];"
               ::"r"(dst), "l"(map), "r"(bar), "r"(c0), "r"(c1), "r"(c2), "r"(c3) : "memory");
}
__device__ __forceinline__ void tma_store_2d(const CUtensorMap* map, uint32_t src, int c0, int c1) {
  asm volatile("cp.async.bulk.tensor.2d.global.shared::cta.bulk_group [%0, {%2, %3}], [%1];"
               ::"l"(map), "r"(src), "r"(c0), "r"(c1) : "memory");
}
__device__ __forceinline__ void tma_prefetch_2d(const CUtensorMap* map, int c0, int c1) {
  asm volatile("cp.async.bulk.prefetch.tensor.2d.L2.global [%0, {%1, %2}];" ::"l"(map), "r"(c0), "r"(c1) : "memory");
}
__device__ __forceinline__ void tma_prefetch_desc(const CUtensorMap* map) {
  asm volatile("prefetch.tensormap [%0];" ::"l"(map) : "memory");
}
__device__ __forceinline__ void fence_async_smem() { asm volatile("fence.proxy.async.shared::cta;" ::: "memory"); }
__device__ __forceinline__ void bulk_commit() { asm volatile("cp.async.bulk.commit_group;" ::: "memory"); }
template <int N> __device__ __forceinline__ void bulk_wait_read() { asm volatile("cp.async.bulk.wait_group.read %0;" ::"n"(N) : "memory"); }
template <int N> __device__ __forceinline__ void bulk_wait() { asm volatile("cp.async.bulk.wait_group %0;" ::"n"(N) : "memory"); }
__device__ __forceinline__ void named_bar(int id, int n) { asm volatile("bar.sync %0, %1;" ::"r"(id), "r"(n) : "memory"); }

__device__ __forceinline__ void named_bar_arrive(int id, int n) { asm volatile("bar.arrive %0, %1;" ::"r"(id), "r"(n) : "memory"); }
__device__ __forceinline__ float ex2(float x) { float y; asm("ex2.approx.ftz.f32 %0, %1;" : "=f"(y) : "f"(x)); return y; }
__device__ __forceinline__ float rcp(float x) { float y; asm("rcp.approx.ftz.f32 %0, %1;" : "=f"(y) : "f"(x)); return y; }

__device__ __forceinline__ void sts32(uint32_t a, uint32_t x) { asm volatile("st.shared.b32 [%0], %1;" ::"r"(a), "r"(x) : "memory"); }
__device__ __forceinline__ uint32_t lds32(uint32_t a) { uint32_t x; asm volatile("ld.shared.b32 %0, [%1];" : "=r"(x) : "r"(a) : "memory"); return x; }
__device__ __forceinline__ uint32_t lds32v(uint32_t a) { uint32_t x; asm volatile("ld.volatile.shared.b32 %0, [%1];" : "=r"(x) : "r"(a) : "memory"); return x; }
__device__ __forceinline__ void sts128(uint32_t a, const uint4& v) { asm volatile("st.shared.v4.b32 [%0], {%1,%2,%3,%4};" ::"r"(a), "r"(v.x), "r"(v.y), "r"(v.z), "r"(v.w) : "memory"); }
__device__ __forceinline__ void sts128f(uint32_t a, const float4& v) { asm volatile("st.shared.v4.f32 [%0], {%1,%2,%3,%4};" ::"r"(a), "f"(v.x), "f"(v.y), "f"(v.z), "f"(v.w) : "memory"); }
__device__ __forceinline__ uint4 lds128(uint32_t a) { uint4 v; asm volatile("ld.shared.v4.b32 {%0,%1,%2,%3}, [%4];" : "=r"(v.x), "=r"(v.y), "=r"(v.z), "=r"(v.w) : "r"(a) : "memory"); return v; }
__device__ __forceinline__ float4 lds128f(uint32_t a) { float4 v; asm volatile("ld.shared.v4.f32 {%0,%1,%2,%3}, [%4];" : "=f"(v.x), "=f"(v.y), "=f"(v.z), "=f"(v.w) : "r"(a) : "memory"); return v; }

__device__ __forceinline__ void cp_async16(uint32_t dst, const void* src) { asm volatile("cp.async.cg.shared.global [%0], [%1], 16;" ::"r"(dst), "l"(src) : "memory"); }
__device__ __forceinline__ void cp_async_commit() { asm volatile("cp.async.commit_group;" ::: "memory"); }
template <int N> __device__ __forceinline__ void cp_async_wait_group() { asm volatile("cp.async.wait_group %0;" ::"n"(N) : "memory"); }

__device__ __forceinline__ void wg_fence() { asm volatile("wgmma.fence.sync.aligned;" ::: "memory"); }
__device__ __forceinline__ void wg_commit() { asm volatile("wgmma.commit_group.sync.aligned;" ::: "memory"); }
template <int N> __device__ __forceinline__ void wg_wait() { asm volatile("wgmma.wait_group.sync.aligned %0;" ::"n"(N) : "memory"); }
__device__ __forceinline__ uint64_t make_desc(uint32_t addr, uint32_t lbo, uint32_t sbo, uint32_t swz) {
  return (uint64_t)((addr & 0x3FFFF) >> 4) | ((uint64_t)(lbo >> 4) << 16) | ((uint64_t)(sbo >> 4) << 32) | ((uint64_t)swz << 62);
}

__device__ __forceinline__ void ldsm_x4(uint32_t (&r)[4], uint32_t addr) {
  asm volatile("ldmatrix.sync.aligned.m8n8.x4.shared.b16 {%0,%1,%2,%3}, [%4];"
               : "=r"(r[0]), "=r"(r[1]), "=r"(r[2]), "=r"(r[3]) : "r"(addr) : "memory");
}
__device__ __forceinline__ void ldsm_x4_t(uint32_t (&r)[4], uint32_t addr) {
  asm volatile("ldmatrix.sync.aligned.m8n8.x4.trans.shared.b16 {%0,%1,%2,%3}, [%4];"
               : "=r"(r[0]), "=r"(r[1]), "=r"(r[2]), "=r"(r[3]) : "r"(addr) : "memory");
}
__device__ __forceinline__ void ldsm_x2(uint32_t& r0, uint32_t& r1, uint32_t addr) {
  asm volatile("ldmatrix.sync.aligned.m8n8.x2.shared.b16 {%0,%1}, [%2];" : "=r"(r0), "=r"(r1) : "r"(addr) : "memory");
}
__device__ __forceinline__ void stsm_x4(uint32_t addr, uint32_t r0, uint32_t r1, uint32_t r2, uint32_t r3) {
  asm volatile("stmatrix.sync.aligned.m8n8.x4.shared.b16 [%0], {%1,%2,%3,%4};"
               ::"r"(addr), "r"(r0), "r"(r1), "r"(r2), "r"(r3) : "memory");
}
__device__ __forceinline__ void stsm_x4_t(uint32_t addr, uint32_t r0, uint32_t r1, uint32_t r2, uint32_t r3) {
  asm volatile("stmatrix.sync.aligned.m8n8.x4.trans.shared.b16 [%0], {%1,%2,%3,%4};" ::"r"(addr), "r"(r0), "r"(r1), "r"(r2), "r"(r3) : "memory");
}
__device__ __forceinline__ void mma16816(float (&c)[4], const uint32_t (&a)[4], uint32_t b0, uint32_t b1) {
  asm volatile("mma.sync.aligned.m16n8k16.row.col.f32.bf16.bf16.f32 {%0,%1,%2,%3}, {%4,%5,%6,%7}, {%8,%9}, {%0,%1,%2,%3};"
               : "+f"(c[0]), "+f"(c[1]), "+f"(c[2]), "+f"(c[3])
               : "r"(a[0]), "r"(a[1]), "r"(a[2]), "r"(a[3]), "r"(b0), "r"(b1));
}
__device__ __forceinline__ void mma1688(float (&c)[4], uint32_t a0, uint32_t a1, uint32_t b0) {
  asm volatile("mma.sync.aligned.m16n8k8.row.col.f32.bf16.bf16.f32 {%0,%1,%2,%3}, {%4,%5}, {%6}, {%0,%1,%2,%3};"
               : "+f"(c[0]), "+f"(c[1]), "+f"(c[2]), "+f"(c[3]) : "r"(a0), "r"(a1), "r"(b0));
}
__device__ __forceinline__ uint32_t pack_bf16(float lo, float hi) {
  uint32_t r;
  asm("cvt.rn.bf16x2.f32 %0, %1, %2;" : "=r"(r) : "f"(hi), "f"(lo));
  return r;
}
__device__ __forceinline__ float bf_lo(uint32_t w) { return __uint_as_float(w << 16); }
__device__ __forceinline__ float bf_hi(uint32_t w) { return __uint_as_float(w & 0xFFFF0000u); }

__device__ __forceinline__ uint4 ld_relaxed4(const void* p) {
  uint4 v;
  asm volatile("ld.relaxed.gpu.global.v4.u32 {%0,%1,%2,%3}, [%4];" : "=r"(v.x), "=r"(v.y), "=r"(v.z), "=r"(v.w) : "l"(p) : "memory");
  return v;
}
__device__ __forceinline__ void st_relaxed4(void* p, uint32_t a, uint32_t b, uint32_t c, uint32_t d) {
  asm volatile("st.relaxed.gpu.global.v4.u32 [%0], {%1,%2,%3,%4};" ::"l"(p), "r"(a), "r"(b), "r"(c), "r"(d) : "memory");
}
__device__ __forceinline__ void st_relaxed2(void* p, uint32_t a, uint32_t b) {
  asm volatile("st.relaxed.gpu.global.v2.u32 [%0], {%1,%2};" ::"l"(p), "r"(a), "r"(b) : "memory");
}
__device__ __forceinline__ void st_relaxed1(void* p, uint32_t a) {
  asm volatile("st.relaxed.gpu.global.u32 [%0], %1;" ::"l"(p), "r"(a) : "memory");
}

__device__ __forceinline__ uint2 ld_relaxed2(const void* p) {
  uint2 v;
  asm volatile("ld.relaxed.gpu.global.v2.u32 {%0,%1}, [%2];" : "=r"(v.x), "=r"(v.y) : "l"(p) : "memory");
  return v;
}
__device__ __forceinline__ void sts64(uint32_t a, uint32_t x, uint32_t y) { asm volatile("st.shared.v2.b32 [%0], {%1,%2};" ::"r"(a), "r"(x), "r"(y) : "memory"); }
__device__ __forceinline__ uint2 lds64(uint32_t a) { uint2 v; asm volatile("ld.shared.v2.b32 {%0,%1}, [%2];" : "=r"(v.x), "=r"(v.y) : "r"(a) : "memory"); return v; }
__device__ __forceinline__ void lds128r(uint32_t (&r)[4], uint32_t a) {
  asm volatile("ld.shared.v4.b32 {%0,%1,%2,%3}, [%4];" : "=r"(r[0]), "=r"(r[1]), "=r"(r[2]), "=r"(r[3]) : "r"(a) : "memory");
}
__device__ __forceinline__ uint32_t movmat(uint32_t a) { uint32_t d; asm volatile("movmatrix.sync.aligned.m8n8.trans.b16 %0, %1;" : "=r"(d) : "r"(a)); return d; }
__device__ __forceinline__ uint32_t mapa(uint32_t addr, uint32_t rank) { uint32_t r; asm volatile("mapa.shared::cluster.u32 %0, %1, %2;" : "=r"(r) : "r"(addr), "r"(rank)); return r; }
__device__ __forceinline__ void st_async1(uint32_t dst, uint32_t a, uint32_t bar) {
  asm volatile("st.async.weak.shared::cluster.mbarrier::complete_tx::bytes.b32 [%0], %1, [%2];" ::"r"(dst), "r"(a), "r"(bar) : "memory");
}
__device__ __forceinline__ void st_async2(uint32_t dst, uint32_t a, uint32_t b, uint32_t bar) {
  asm volatile("st.async.weak.shared::cluster.mbarrier::complete_tx::bytes.v2.b32 [%0], {%1,%2}, [%3];" ::"r"(dst), "r"(a), "r"(b), "r"(bar) : "memory");
}
__device__ __forceinline__ void st_async4(uint32_t dst, uint32_t a, uint32_t b, uint32_t c, uint32_t d, uint32_t bar) {
  asm volatile("st.async.weak.shared::cluster.mbarrier::complete_tx::bytes.v4.b32 [%0], {%1,%2,%3,%4}, [%5];" ::"r"(dst), "r"(a), "r"(b), "r"(c), "r"(d), "r"(bar) : "memory");
}
__device__ __forceinline__ void cluster_arrive() { asm volatile("barrier.cluster.arrive.relaxed.aligned;" ::: "memory"); }
__device__ __forceinline__ void cluster_wait() { asm volatile("barrier.cluster.wait.acquire.aligned;" ::: "memory"); }

__device__ __forceinline__ void wgmma_k3_ss_ta(float (&d)[80], uint64_t da, uint64_t db, int scale_d) {
  asm volatile("{.reg .pred p; setp.ne.b32 p, %82, 0;\n"
    "wgmma.mma_async.sync.aligned.m64n160k16.f32.bf16.bf16 {%0, %1, %2, %3, %4, %5, %6, %7, %8, %9, %10, %11, %12, %13, %14, %15, %16, %17, %18, %19, %20, %21, %22, %23, %24, %25, %26, %27, %28, %29, %30, %31, %32, %33, %34, %35, %36, %37, %38, %39, %40, %41, %42, %43, %44, %45, %46, %47, %48, %49, %50, %51, %52, %53, %54, %55, %56, %57, %58, %59, %60, %61, %62, %63, %64, %65, %66, %67, %68, %69, %70, %71, %72, %73, %74, %75, %76, %77, %78, %79}, %80, %81, p, 1, 1, 1, 0;}"
    : "+f"(d[0]), "+f"(d[1]), "+f"(d[2]), "+f"(d[3]), "+f"(d[4]), "+f"(d[5]), "+f"(d[6]), "+f"(d[7]), "+f"(d[8]), "+f"(d[9]), "+f"(d[10]), "+f"(d[11]), "+f"(d[12]), "+f"(d[13]), "+f"(d[14]), "+f"(d[15]), "+f"(d[16]), "+f"(d[17]), "+f"(d[18]), "+f"(d[19]), "+f"(d[20]), "+f"(d[21]), "+f"(d[22]), "+f"(d[23]), "+f"(d[24]), "+f"(d[25]), "+f"(d[26]), "+f"(d[27]), "+f"(d[28]), "+f"(d[29]), "+f"(d[30]), "+f"(d[31]), "+f"(d[32]), "+f"(d[33]), "+f"(d[34]), "+f"(d[35]), "+f"(d[36]), "+f"(d[37]), "+f"(d[38]), "+f"(d[39]), "+f"(d[40]), "+f"(d[41]), "+f"(d[42]), "+f"(d[43]), "+f"(d[44]), "+f"(d[45]), "+f"(d[46]), "+f"(d[47]), "+f"(d[48]), "+f"(d[49]), "+f"(d[50]), "+f"(d[51]), "+f"(d[52]), "+f"(d[53]), "+f"(d[54]), "+f"(d[55]), "+f"(d[56]), "+f"(d[57]), "+f"(d[58]), "+f"(d[59]), "+f"(d[60]), "+f"(d[61]), "+f"(d[62]), "+f"(d[63]), "+f"(d[64]), "+f"(d[65]), "+f"(d[66]), "+f"(d[67]), "+f"(d[68]), "+f"(d[69]), "+f"(d[70]), "+f"(d[71]), "+f"(d[72]), "+f"(d[73]), "+f"(d[74]), "+f"(d[75]), "+f"(d[76]), "+f"(d[77]), "+f"(d[78]), "+f"(d[79])
    : "l"(da), "l"(db), "r"(scale_d));
}
__device__ __forceinline__ void wgmma_m64n32_ss_ta(float (&d)[16], uint64_t da, uint64_t db, int scale_d) {
  asm volatile("{.reg .pred p; setp.ne.b32 p, %18, 0;\n"
    "wgmma.mma_async.sync.aligned.m64n32k16.f32.bf16.bf16 {%0, %1, %2, %3, %4, %5, %6, %7, %8, %9, %10, %11, %12, %13, %14, %15}, %16, %17, p, 1, 1, 1, 0;}"
    : "+f"(d[0]), "+f"(d[1]), "+f"(d[2]), "+f"(d[3]), "+f"(d[4]), "+f"(d[5]), "+f"(d[6]), "+f"(d[7]), "+f"(d[8]), "+f"(d[9]), "+f"(d[10]), "+f"(d[11]), "+f"(d[12]), "+f"(d[13]), "+f"(d[14]), "+f"(d[15])
    : "l"(da), "l"(db), "r"(scale_d));
}

__device__ __forceinline__ void wgmma_m64n32_rs(float (&d)[16], const uint32_t (&a)[4], uint64_t db, int scale_d) {
  asm volatile("{.reg .pred p; setp.ne.b32 p, %21, 0;\n"
    "wgmma.mma_async.sync.aligned.m64n32k16.f32.bf16.bf16 {%0, %1, %2, %3, %4, %5, %6, %7, %8, %9, %10, %11, %12, %13, %14, %15}, {%16, %17, %18, %19}, %20, p, 1, 1, 0;}"
    : "+f"(d[0]), "+f"(d[1]), "+f"(d[2]), "+f"(d[3]), "+f"(d[4]), "+f"(d[5]), "+f"(d[6]), "+f"(d[7]), "+f"(d[8]), "+f"(d[9]), "+f"(d[10]), "+f"(d[11]), "+f"(d[12]), "+f"(d[13]), "+f"(d[14]), "+f"(d[15])
    : "r"(a[0]), "r"(a[1]), "r"(a[2]), "r"(a[3]), "l"(db), "r"(scale_d));
}

#define X_POS 5
#define T_STEP 2816
#define T_PHASE 1760
#define RATE0 2295
#define T_LAG 32
#define T_TOL 192
#define T_SLIP 640
#define O_FIX 5
#define NTMP 4
#define V_PRE 6
#define SFENCE(i) asm volatile("{.reg .pred p; setp.eq.u32 p, %0, %1; @p trap;}" ::"r"(n), "r"(4096 + (i)) : "memory")
constexpr int RING = 4;
constexpr uint32_t EMPTY = 0xFFFFFFFFu;
namespace xo {
constexpr uint32_t SLOT = 1u << 20, HEAD = 16384;
constexpr uint32_t VM = 512;
constexpr uint32_t PT = 1024;
constexpr uint32_t PM = 1536;
constexpr uint32_t VT = 8192;
constexpr uint32_t MEM = NH * HEAD;
constexpr uint32_t OM = MEM + 16384;
constexpr uint32_t O = RING * SLOT;
constexpr uint32_t BYTES = O + S_LEN * HD * 2;
}
__device__ __align__(1024) uint4 g_scratch[2 * (xo::BYTES / 16)];
__device__ unsigned g_epoch;
__device__ __align__(16) unsigned g_rate[128];

struct ChainMaps {
  CUtensorMap wq, wk, wv;
  CUtensorMap wo;
  CUtensorMap x, xq;
  const char* xp;
  uint32_t t_step, t_phase;
};

namespace chain {
constexpr int OFF_X = 65536;
constexpr int OFF_MEM = 131072;
constexpr int OFF_WS = 0;
constexpr int OFF_FP = 147456;
constexpr int OFF_KT = 163840;
constexpr int OFF_QT = 180224;
constexpr int OFF_VT = 196608;
constexpr int OFF_PX = 204800;
constexpr int OFF_S4 = OFF_PX + 1536;
constexpr int OFF_QM = 212992;
constexpr int OFF_KM = 215040;
constexpr int OFF_S1 = 217088;
constexpr int OFF_WVR = 0;
constexpr int OFF_WOR = 147456;
constexpr int OFF_RED = 212992;
constexpr int OFF_VPX = 221184;
constexpr int OFF_RX = 223232;
constexpr int OFF_TR = 225280;
constexpr int OFF_BAR = 229376;
constexpr int BAR_X = OFF_BAR, BAR_TOK = OFF_BAR + 16, BAR_EX = OFF_BAR + 32, BAR_P = OFF_BAR + 40, GRID_TGT = OFF_BAR + 128;
constexpr int CT_BASE = GRID_TGT + 4, CT_HEAD = GRID_TGT + 8, CT_OM = GRID_TGT + 12, CT_MP = GRID_TGT + 16, CT_O = GRID_TGT + 20, CT_PF = GRID_TGT + 24;
constexpr int CT_TT = GRID_TGT + 28, CT_T = GRID_TGT + 32;
constexpr uint32_t RANK_BIT = 1u << 24;
constexpr int SMEM = OFF_BAR + 256;
constexpr uint32_t SB_LO = 1024;
constexpr float SCALE = 0.08838834764831845f, L2E = 1.4426950408889634f;
}

__device__ __forceinline__ uint32_t umax4(uint32_t a, uint32_t b, uint32_t c, uint32_t d) { return max(max(a, b), max(c, d)); }
__device__ __forceinline__ bool warp_incomplete(uint32_t m) { return __any_sync(0xffffffffu, m == EMPTY); }
#define PIN(x) asm volatile("" : "+r"(x))
#define KEEPALIVE(a, z) do { float _d0, _d1, _d2, _d3; asm volatile("mma.sync.aligned.m16n8k16.row.col.f32.bf16.bf16.f32 {%0,%1,%2,%3}, {%4,%5,%6,%7}, {%4,%5}, {%8,%8,%8,%8};" \
    : "=f"(_d0), "=f"(_d1), "=f"(_d2), "=f"(_d3) : "r"(a[0]), "r"(a[1]), "r"(a[2]), "r"(a[3]), "f"(0.f)); \
      \
    asm volatile("{.reg .pred p; setp.ne.u32 p, %0, 0; @p st.shared.f32 [%0], %1;}" ::"r"(z), "f"(_d0 + _d3) : "memory"); } while (0)
constexpr int POLL_LIMIT = 1 << 17;

__device__ __forceinline__ uint32_t keep(uint32_t x) { return __shfl_sync(0xffffffffu, x, threadIdx.x & 31); }
__device__ __forceinline__ char* gptr(uint32_t hi, uint32_t lo) { return (char*)(((uint64_t)hi << 32) | lo); }
__device__ __forceinline__ uint32_t slot_off(int n) { return ((uint32_t)n & (RING - 1)) * xo::SLOT; }
__device__ __forceinline__ float quad_max(float x) {
  const float a = __shfl_xor_sync(~0u, x, 1), b = __shfl_xor_sync(~0u, x, 2), c = __shfl_xor_sync(~0u, x, 3);
  return fmaxf(fmaxf(x, a), fmaxf(b, c));
}
__device__ __forceinline__ void acc_fence(float (&a)[16]) {
#pragma unroll
  for (int i = 0; i < 16; i++) asm volatile("" : "+f"(a[i]) :: "memory");
}
template <int NB = 1, int STRIDE = 0>
__device__ __forceinline__ void gather_issue(uint32_t dst, const char* src) {
#pragma unroll
  for (int b = 0; b < NB; b++)
#pragma unroll
    for (int i = 0; i < 4; i++) cp_async16(dst + b * STRIDE + i * 512, src + b * STRIDE + i * 512);
  cp_async_commit();
}
template <int NB, int STRIDE>
__device__ __forceinline__ bool gather_incomplete(uint32_t chk) {
  uint32_t m = 0;
#pragma unroll
  for (int b = 0; b < NB; b++) m = max(m, umax4(lds32(chk + b * STRIDE), lds32(chk + b * STRIDE + 512), lds32(chk + b * STRIDE + 1024), lds32(chk + b * STRIDE + 1536)));
  return warp_incomplete(m);
}
__device__ __forceinline__ uint32_t ld_relaxed1(const void* p) {
  uint32_t v;
  asm volatile("ld.relaxed.gpu.global.u32 %0, [%1];" : "=r"(v) : "l"(p) : "memory");
  return v;
}
__device__ __forceinline__ uint32_t gtime() { uint64_t g; asm volatile("mov.u64 %0, %%globaltimer;" : "=l"(g) :: "memory"); return (uint32_t)g; }
#define WAIT_UNTIL(t, ka, alive, id) do { \
    int _d = gtime() - (t); \
    if (__builtin_expect(_d > T_TOL, 0)) do { t += T_SLIP; _d -= T_SLIP; } while (_d > T_TOL); \
    if (alive) for (int _k = 64; _d < -96 && --_k; _d = gtime() - (t)) KEEPALIVE(ka, zr); \
    for (uint32_t _g = -128; (int)(_d & ++_g) < 0;) _d = gtime() - (t); } while (0)
__device__ __forceinline__ void issue_x(uint32_t sb, const CUtensorMap* map, int n, int part, int q = 0) {
  asm volatile("{.reg .pred p; elect.sync _|p, 0xffffffff;\n"
               "@p cp.async.bulk.tensor.3d.shared::cluster.global.mbarrier::complete_tx::bytes [%0], [%1, {%3, %4, %5}], [%2];}"
               ::"r"(sb + chain::OFF_X + part * 32768 + q * 16384), "l"(map), "r"(sb + chain::BAR_X + 8 * part), "r"(0), "r"(n * SEG), "r"(part * 8 + q * 4) : "memory");
}
__device__ __forceinline__ void issue_x_if(uint32_t sb, const CUtensorMap* map, int n, int part, uint32_t on) {
  asm volatile("{.reg .pred p, q; elect.sync _|p, 0xffffffff; setp.ne.and.u32 q, %6, 0, p;\n"
               "@q cp.async.bulk.tensor.3d.shared::cluster.global.mbarrier::complete_tx::bytes [%0], [%1, {%3, %4, %5}], [%2];}"
               ::"r"(sb + chain::OFF_X + part * 32768), "l"(map), "r"(sb + chain::BAR_X + 8 * part), "r"(0), "r"(n * SEG), "r"(part * 8), "r"(on) : "memory");
}
__device__ __forceinline__ void prefetch_l2(const char* p, uint32_t bytes) {
  asm volatile("{.reg .pred p; elect.sync _|p, 0xffffffff; @p cp.async.bulk.prefetch.L2.global [%0], %1;}" ::"l"(p), "r"(bytes) : "memory");
}
__device__ __forceinline__ void expect_elect(uint32_t bar, uint32_t bytes) {
  asm volatile("{.reg .pred p; elect.sync _|p, 0xffffffff; @p mbarrier.arrive.expect_tx.shared::cta.b64 _, [%0], %1;}" ::"r"(bar), "r"(bytes) : "memory");
}
template <int WG> __device__ __forceinline__ constexpr uint64_t xdesc(int ks) {
  return (uint64_t)(((chain::SB_LO + chain::OFF_X + WG * 32768 + (ks >> 2) * 4096 + (ks & 3) * 32) >> 4) + (1u << 16)) |
         ((uint64_t)(64u | (1u << 30)) << 32);
}
template <int WG> __device__ __forceinline__ constexpr uint64_t wdesc(int o, int ks) {
  return (uint64_t)(((chain::SB_LO + chain::OFF_WS + WG * 32768 + o * 16384 + ks * 2048) >> 4) + (1u << 16)) | ((uint64_t)(64u | (1u << 30)) << 32);
}
__device__ __forceinline__ void load_mem0(uint2 (&m)[8], const bf16* __restrict__ mem0) {
#pragma unroll
  for (int r = 0; r < 8; r++) m[r] = ld_relaxed2((const uint2*)(mem0 + r * DM) + threadIdx.x);
}
__device__ __forceinline__ void store_mem0(uint32_t sb, const uint2 (&m)[8]) {
  const uint32_t d = sb + chain::OFF_MEM + threadIdx.x * 64;
  sts128(d, make_uint4(__byte_perm(m[0].x, m[1].x, 0x5410), __byte_perm(m[2].x, m[3].x, 0x5410), __byte_perm(m[4].x, m[5].x, 0x5410), __byte_perm(m[6].x, m[7].x, 0x5410)));
  sts128(d + 16, make_uint4(__byte_perm(m[0].x, m[1].x, 0x7632), __byte_perm(m[2].x, m[3].x, 0x7632), __byte_perm(m[4].x, m[5].x, 0x7632), __byte_perm(m[6].x, m[7].x, 0x7632)));
  sts128(d + 32, make_uint4(__byte_perm(m[0].y, m[1].y, 0x5410), __byte_perm(m[2].y, m[3].y, 0x5410), __byte_perm(m[4].y, m[5].y, 0x5410), __byte_perm(m[6].y, m[7].y, 0x5410)));
  sts128(d + 48, make_uint4(__byte_perm(m[0].y, m[1].y, 0x7632), __byte_perm(m[2].y, m[3].y, 0x7632), __byte_perm(m[4].y, m[5].y, 0x7632), __byte_perm(m[6].y, m[7].y, 0x7632)));
}
template <int K> __device__ __forceinline__ uint32_t loop_zero(int n) { uint32_t z; asm volatile("shr.u32 %0, %1, %2;" : "=r"(z) : "r"(n), "n"(16 + K)); return z; }
#define NEWZ(k) zr = loop_zero<k>(n)

template <int WG>
__device__ __forceinline__ void role_a(const ChainMaps& maps, const bf16* __restrict__ mem0, const uint32_t sb, const uint32_t xbase_hi) {
  using namespace chain;
  const int h = blockIdx.x >> 2;
  const bool J = sb >= RANK_BIT;
  const uint32_t u16 = (threadIdx.x & 96) * 64 + (threadIdx.x & 31) * 16;
  const uint32_t t16 = keep(u16), l16 = keep((threadIdx.x & 31) * 16);
  const uint32_t a_wl = keep((((threadIdx.x >> 4) & 1) * 8 + (threadIdx.x & 7)) * 128 + (((((threadIdx.x >> 4) & 6) + ((threadIdx.x >> 3) & 1)) ^ (threadIdx.x & 7)) << 4));
  const uint32_t xhi = keep(xbase_hi + (t16 >> 16));
#define xh (lds32(sb + CT_HEAD) + t16)
#define xm (lds32(sb + CT_BASE) + t16 + xo::MEM)
#define last_warp __any_sync(0xffffffffu, tv >= 6144)
#define tv (t16 ^ zr)
  const CUtensorMap* wm = J ? &maps.wk : &maps.wq;

  uint32_t aW[2][24][4];
  uint2 m0[8];
  load_mem0(m0, mem0);
  mbar_wait(sb + BAR_P, 0);
#pragma unroll
  for (int ks = 0; ks < 24; ks++) ldsm_x4_t(aW[0][ks], sb + a_wl + OFF_X + WG * 49152 + ks * 2048);
  named_bar(0, 256);
  if (WG == 1 && __any_sync(0xffffffffu, t16 >= 6144)) {
    fence_async_smem();
    if (l16 == 0) {
      mbar_expect_tx(sb + BAR_P + 16, 2 * 16384);
      for (int q = 0; q < 2; q++) tma_load_2d(sb + OFF_X + (4 + q) * 16384, wm, h * DH + (q ^ 1) * 64, q * 512 + 256, sb + BAR_P + 16);
    }
    __syncwarp();
    expect_elect(sb + BAR_X, 32768); expect_elect(sb + BAR_X + 8, 32768); expect_elect(sb + BAR_TOK, 8192);
    issue_x(sb, &maps.x, 0, 0); issue_x(sb, &maps.x, 0, 1);
  }
  mbar_wait(sb + BAR_P + 8, 0);
#pragma unroll
  for (int ks = 0; ks < 16; ks++) ldsm_x4_t(aW[1][ks], sb + a_wl + OFF_X + 6 * 16384 + WG * 32768 + ks * 2048);
  mbar_wait(sb + BAR_P + 16, 0);
#pragma unroll
  for (int ks = 0; ks < 8; ks++) ldsm_x4_t(aW[1][16 + ks], sb + a_wl + OFF_X + (4 + WG) * 16384 + ks * 2048);
  named_bar(0, 256);
  cluster_arrive();
  store_mem0(sb, m0);
  mbar_wait(sb + BAR_P + 24, 0);
  cluster_wait();
  const uint32_t rsb = sb ^ RANK_BIT;
  const uint32_t a_ws = sb + a_wl + OFF_WS + WG * 32768;

  uint32_t ws[2][4][4];
  auto load_ws = [&]() {
#pragma unroll
    for (int q = 0; q < 2; q++) {
      const uint32_t a = a_ws + q * 4096;
      ldsm_x4_t(ws[q][0], a); ldsm_x4_t(ws[q][1], a + 16384); ldsm_x4_t(ws[q][2], a + 2048); ldsm_x4_t(ws[q][3], a + 16384 + 2048);
    }
  };
  uint32_t tref = 0;
#pragma unroll 1
  for (int n = 0; n <= (J ? NSEG : NSEG - 1); n++) {
#define s (n - 1)
#define sv ((int)(n ^ zr) - 1)
    const bool more = __builtin_expect(s + 1 < NSEG, 1);
    uint32_t zr = loop_zero<0>(n);
#define wq ((int)(tv >> 11))
#define lv (l16 ^ zr)
#define gh (xh + slot_off(sv))
    uint32_t tmp[NTMP][4];
    auto load_tmp = [&](int o) {
#pragma unroll
      for (int ks = 0; ks < NTMP; ks++) ldsm_x4_t(tmp[ks], a_ws + o * 16384 + ks * 2048);
    };
    auto wait_x = [&]() { mbar_wait<0>(sb + BAR_X + 8 * WG, n & 1); };
    if (__builtin_expect(s < 0, 0)) { load_tmp(1); wait_x(); }
    else {
      {
        if (WG == 1) { if (__builtin_expect(s > 0, 1)) {
          const uint32_t dst = sb + OFF_MEM + tv + t16 - l16, chk = dst + ((lv >> 5) & 12);
          uint32_t tries = zr;
#pragma unroll 1
          do {
            if (tries) {
              const char* src = gptr(xhi, xm + t16 - l16 + slot_off(sv));
              tref += T_SLIP;
              WAIT_UNTIL(tref, aW[0][0], 1, -1);
              gather_issue<2, 2048>(dst, src);
            }
            KEEPALIVE(aW[0][0], zr);
            cp_async_wait_group<0>();
          } while (gather_incomplete<2, 2048>(chk) && ++tries < POLL_LIMIT);
        } } else if (J == 0) {
          uint32_t tries = s == 0;
#pragma unroll 1
          do {
            if (tries) gather_issue(sb + OFF_VT + tv, gptr(xhi, gh) + xo::VT);
            cp_async_wait_group<0>();
          } while (gather_incomplete<1, 0>(sb + OFF_VT + t16 + ((lv >> 5) & 12)) && ++tries < POLL_LIMIT);
        }
        named_bar(1, 256);
      }
      float c[2][2][4];
#pragma unroll
      for (int i = 0; i < 4; i++) c[i >> 1][i & 1][0] = c[i >> 1][i & 1][1] = c[i >> 1][i & 1][2] = c[i >> 1][i & 1][3] = 0.f;
      {
        const uint32_t a_mem = sb + OFF_MEM + WG * 8192 + l16;
        uint32_t b[4][4];
        bool tok;
        constexpr int PR[16] = {12, 13, 0, 1, 2, 3, 4, 14, 5, 6, 7, 8, 9, 15, 10, 11};
        ldsm_x4_t(b[0], a_mem + PR[0] * 512); ldsm_x4_t(b[1], a_mem + PR[1] * 512);
#pragma unroll
        for (int i = 0; i < 16; i++) {
          if ((i & 1) == 0 && i < 14) {
            ldsm_x4_t(b[(i + 2) & 3], a_mem + PR[i + 2] * 512); ldsm_x4_t(b[(i + 3) & 3], a_mem + PR[i + 3] * 512);
            if (i == 2 || i == 8) { ldsm_x4_t(ws[1][0], a_ws + (i == 2 ? 2 : 3) * 4096); ldsm_x4_t(ws[1][1], a_ws + (i == 2 ? 2 : 3) * 4096 + 16384); }
            if (i == 4 || i == 10) { ldsm_x4_t(ws[1][2], a_ws + (i == 4 ? 2 : 3) * 4096 + 2048); ldsm_x4_t(ws[1][3], a_ws + (i == 4 ? 2 : 3) * 4096 + 16384 + 2048); }
          }
          const int p = PR[i];
          if (p >= 12) {
            const int z = i != 0;
            mma16816(c[0][0], ws[z][0], b[i & 3][0], b[i & 3][1]); mma16816(c[1][0], ws[z][1], b[i & 3][0], b[i & 3][1]);
            mma16816(c[0][1], ws[z][2], b[i & 3][2], b[i & 3][3]); mma16816(c[1][1], ws[z][3], b[i & 3][2], b[i & 3][3]);
          } else {
            mma16816(c[1][0], aW[1][2 * p], b[i & 3][0], b[i & 3][1]); mma16816(c[1][1], aW[1][2 * p + 1], b[i & 3][2], b[i & 3][3]);
            mma16816(c[0][0], aW[0][2 * p], b[i & 3][0], b[i & 3][1]); mma16816(c[0][1], aW[0][2 * p + 1], b[i & 3][2], b[i & 3][3]);
          }
          if (i == 12) tok = mbar_test(sb + BAR_TOK + 8 * (s & 1), (s >> 1) & 1);
          if (i == 15 && __builtin_expect(!tok, 0)) mbar_wait(sb + BAR_TOK + 8 * (s & 1), (s >> 1) & 1);
          if (i == X_POS + 4 * (1 - WG)) { issue_x_if(sb, &maps.x, s + 1, WG, t16 >= 6144 && more); if (WG) __syncwarp(); }
        }
      }
      sts128f(sb + OFF_PX + WG * 512 + t16, make_float4(c[1][0][0] + c[1][1][0], c[1][0][1] + c[1][1][1], c[1][0][2] + c[1][1][2], c[1][0][3] + c[1][1][3]));
      const float4 own = make_float4(c[0][0][0] + c[0][1][0], c[0][0][1] + c[0][1][1], c[0][0][2] + c[0][1][2], c[0][0][3] + c[0][1][3]);
      NEWZ(1);
      uint32_t a = (J ? OFF_KM : OFF_QM) + WG * 1024 + wq * 256 + (lv >> 2);
      uint32_t ra = rsb + a, ra2 = ra + 128, rx = rsb + BAR_EX + zr;
      PIN(a); PIN(ra); PIN(ra2); PIN(rx);
      const uint32_t kt = sb + OFF_KT + (s & 1) * 8192;
#define k_lane ((lv & 240) + ((lv & 256) << 2))
#define a_lane (((lv & 128) << 1) + ((lv & 256) >> 1) + (lv & 112))
      uint32_t kb[4][4], aq = sb + OFF_QM + a_lane;
      PIN(aq);
      SFENCE(16);
      named_bar(3, 256);
      {
        const float4 o = lds128f(sb + OFF_PX + (WG ^ 1) * 512 + t16);
        const uint32_t lo = pack_bf16(own.x + o.x, own.y + o.y), hi = pack_bf16(own.z + o.z, own.w + o.w);
        if (J == 1 && more) { st_async1(ra, lo, rx); st_async1(ra2, hi, rx); }
        sts32(sb + a, lo); sts32(sb + a + 128, hi);
      }
      if (J == 0) {
        uint32_t am[4][4];
        uint2 vm0, vm1;
        const char* pvm = WG == 0 ? gptr(xhi, gh - (lv >> 1)) + xo::VM : nullptr;
        if (WG == 1) {
#pragma unroll
          for (int p = 0; p < 4; p++) ldsm_x4(kb[p], kt + wq * 256 + k_lane + p * 2048);
        }
        named_bar(7, 256);
#pragma unroll
        for (int p = 0; p < 4; p++) ldsm_x4_t(am[p], aq + p * 512);
        auto scores = [&]() {
          float c0[2][4], c1[2][4];
#pragma unroll
          for (int i = 0; i < 2; i++) { c0[i][0] = c0[i][1] = c0[i][2] = c0[i][3] = 0.f; c1[i][0] = c1[i][1] = c1[i][2] = c1[i][3] = 0.f; }
#pragma unroll
          for (int p = 0; p < 4; p++) { mma16816(c0[p & 1], am[p], kb[p][0], kb[p][1]); mma16816(c1[p & 1], am[p], kb[p][2], kb[p][3]); }
          const uint32_t r1 = pack_bf16((c0[0][0] + c0[1][0]) + (c1[0][2] + c1[1][2]), (c0[0][1] + c0[1][1]) + (c1[0][3] + c1[1][3]));
          return pack_bf16(bf_lo(r1) * SCALE, bf_hi(r1) * SCALE);
        };
        if (WG == 1) {
          const uint32_t st = scores();
          uint32_t vb[4][4];
          sts32(sb + OFF_S4 + l16 + wq * 4, st);
          named_bar(8, 128);
          const uint4 sc = lds128(sb + OFF_S4 + l16);
          float x[8] = {bf_lo(sc.x), bf_hi(sc.x), bf_lo(sc.y), bf_hi(sc.y), bf_lo(sc.z), bf_hi(sc.z), bf_lo(sc.w), bf_hi(sc.w)};
          float mx = fmaxf(fmaxf(fmaxf(x[0], x[1]), fmaxf(x[2], x[3])), fmaxf(fmaxf(x[4], x[5]), fmaxf(x[6], x[7])));
          {
            const uint32_t va = sb + OFF_VT + t16 + (sc.x & zr);
#pragma unroll
            for (int e = 0; e < 4; e++) lds128r(vb[e], va + e * 512);
          }
          mx = quad_max(mx);
          const float mb = mx * L2E;
#pragma unroll
          for (int i = 0; i < 8; i++) x[i] = ex2(fmaf(x[i], L2E, -mb));
          uint32_t pa[4], pb[4];
          asm volatile("" : "=r"(pa[1]), "=r"(pa[3]), "=r"(pb[1]), "=r"(pb[3]));
          pa[0] = pack_bf16(x[0], x[1]); pa[2] = pack_bf16(x[2], x[3]);
          pb[0] = pack_bf16(x[4], x[5]); pb[2] = pack_bf16(x[6], x[7]);
          float oa[4][4];
#pragma unroll
          for (int e = 0; e < 4; e++) { oa[e][0] = oa[e][1] = oa[e][2] = oa[e][3] = 0.f; mma16816(oa[e], pa, vb[e][0], vb[e][1]); }
#pragma unroll
          for (int e = 0; e < 4; e++) mma16816(oa[e], pb, vb[e][2], vb[e][3]);
          sts64(sb + OFF_PX + 1024 + t16, __float_as_uint(mx), __float_as_uint(((x[0] + x[1]) + (x[2] + x[3])) + ((x[4] + x[5]) + (x[6] + x[7]))));
          sts128f(sb + OFF_PX + t16, make_float4(oa[0][0], oa[0][1], oa[1][0], oa[1][1]));
          sts128f(sb + OFF_PX + 512 + t16, make_float4(oa[2][0], oa[2][1], oa[3][0], oa[3][1]));
          named_bar_arrive(9, 256);
          wait_x();
          load_tmp(1);
        } else {
          const uint32_t xo0 = lds32(sb + CT_OM) + wq * 512 + l16;
          mbar_wait<0>(sb + BAR_EX, s & 1);
          vm0 = ld_relaxed2(pvm); vm1 = ld_relaxed2(pvm + 256);
#pragma unroll
          for (int p = 0; p < 4; p++) ldsm_x4_t(kb[p], sb + OFF_KM + p * 512 + l16);
          const uint32_t sm = scores();
          float mx = quad_max(fmaxf(bf_lo(sm), bf_hi(sm)));
          auto check_vm = [&]() {
            if (__builtin_expect(warp_incomplete(max(vm0.x, vm1.x)), 0)) {
              uint32_t tries = zr;
#pragma unroll 1
              do { vm0 = ld_relaxed2(pvm); vm1 = ld_relaxed2(pvm + 256); } while (warp_incomplete(max(vm0.x, vm1.x)) && ++tries < POLL_LIMIT);
            }
          };
          SFENCE(25);
          named_bar(9, 256);
          const uint2 ms = lds64(sb + OFF_PX + 1024 + t16);
          const float4 t0 = lds128f(sb + OFF_PX + t16), t1 = lds128f(sb + OFF_PX + 512 + t16);
          mx = fmaxf(mx, __uint_as_float(ms.x));
          const float mb = mx * L2E;
          const float e0 = ex2(fmaf(bf_lo(sm), L2E, -mb)), e1 = ex2(fmaf(bf_hi(sm), L2E, -mb)), ct = ex2(fmaf(__uint_as_float(ms.x), L2E, -mb));
          uint32_t p4 = pack_bf16(e0, e1), p5;
          asm volatile("" : "=r"(p5));
          float sx = fmaf(ct, __uint_as_float(ms.y), e0 + e1);
          float oa[4][4] = {{t0.x * ct, t0.y * ct, 0.f, 0.f}, {t0.z * ct, t0.w * ct, 0.f, 0.f}, {t1.x * ct, t1.y * ct, 0.f, 0.f}, {t1.z * ct, t1.w * ct, 0.f, 0.f}};
          const float s1 = __shfl_xor_sync(~0u, sx, 1), s2 = __shfl_xor_sync(~0u, sx, 2), s3 = __shfl_xor_sync(~0u, sx, 3);
          check_vm();
          mma1688(oa[0], p4, p5, vm0.x); mma1688(oa[1], p4, p5, vm0.y); mma1688(oa[2], p4, p5, vm1.x); mma1688(oa[3], p4, p5, vm1.y);
          const float rx = rcp((sx + s1) + (s2 + s3));
          st_relaxed4(gptr(xhi, xo0 + slot_off(sv)), pack_bf16(oa[0][0] * rx, oa[0][1] * rx), pack_bf16(oa[1][0] * rx, oa[1][1] * rx),
                      pack_bf16(oa[2][0] * rx, oa[2][1] * rx), pack_bf16(oa[3][0] * rx, oa[3][1] * rx));
          SFENCE(24);
          named_bar_arrive(10, 256);
          st_relaxed4(gptr(xhi, xo0 + slot_off(sv + 3)), EMPTY, EMPTY, EMPTY, EMPTY);
          load_tmp(1);
          wait_x();
        }
      } else {
        bool xok;
        {
          const int mt = WG | (wq == 3), ktile = wq == 3 ? 2 + WG : wq - 1;
          const uint32_t qt = sb + OFF_QT + (s & 1) * 8192 + mt * 512 + a_lane;
          uint32_t q[8][4];
          if (__any_sync(0xffffffffu, tv < 2048)) {
            named_bar(7, 256);
#pragma unroll
            for (int p = 0; p < 4; p++) ldsm_x4_t(kb[p], sb + OFF_KM + p * 512 + l16);
          } else {
            named_bar_arrive(7, 256);
#pragma unroll
            for (int p = 0; p < 4; p++) ldsm_x4(kb[p], kt + ktile * 256 + k_lane + p * 2048);
          }
#pragma unroll
          for (int i = 0; i < 8; i++) ldsm_x4(q[i], qt + i * 1024);
          __syncwarp();
          float c0[4][4];
#pragma unroll
          for (int i = 0; i < 4; i++) { c0[i][0] = c0[i][1] = c0[i][2] = c0[i][3] = 0.f; mma16816(c0[i], q[i], kb[i >> 1][(i & 1) * 2], kb[i >> 1][(i & 1) * 2 + 1]); }
#pragma unroll
          for (int i = 0; i < 4; i++) mma16816(c0[i], q[4 + i], kb[2 + (i >> 1)][(i & 1) * 2], kb[2 + (i >> 1)][(i & 1) * 2 + 1]);
          load_tmp(1);
          xok = mbar_test(sb + BAR_X + 8 * WG, n & 1);
          NEWZ(3);
          const uint32_t r0 = pack_bf16((c0[0][0] + c0[1][0]) + (c0[2][0] + c0[3][0]), (c0[0][1] + c0[1][1]) + (c0[2][1] + c0[3][1]));
          const uint32_t r1 = pack_bf16((c0[0][2] + c0[1][2]) + (c0[2][2] + c0[3][2]), (c0[0][3] + c0[1][3]) + (c0[2][3] + c0[3][3]));
          const uint32_t sa = wq == 0 ? sb + OFF_S1 + (lv >> 2) + mt * 256 : sb + OFF_S4 + l16 + mt * 4096 + ktile * 4;
          sts32(sa, pack_bf16(bf_lo(r0) * SCALE, bf_hi(r0) * SCALE));
          sts32(sa + (wq == 0 ? 128 : 2048), pack_bf16(bf_lo(r1) * SCALE, bf_hi(r1) * SCALE));
        }
        if (WG == 1) named_bar_arrive(8, 256);
        else {
          if (more) named_bar_arrive(10, 256);
          const uint32_t gp = gh;
          named_bar(8, 256);
          const uint4 sc = lds128(sb + OFF_S4 + t16); const uint32_t s1 = lds32(sb + OFF_S1 + wq * 128 + (lv >> 2));
          float y[10] = {bf_lo(s1), bf_hi(s1), bf_lo(sc.x), bf_hi(sc.x), bf_lo(sc.y), bf_hi(sc.y), bf_lo(sc.z), bf_hi(sc.z), bf_lo(sc.w), bf_hi(sc.w)};
          const int rel = wq * 8 + (int)(lv >> 6) - (int)((lv >> 3) & 6);
          const float NEG = -999292928.f;
#pragma unroll
          for (int e = 0; e < 4; e++) {
            if (e * 8 > rel) y[2 * e + 2] = NEG;
            if (e * 8 + 1 > rel) y[2 * e + 3] = NEG;
          }
          float my = fmaxf(fmaxf(fmaxf(y[0], y[1]), fmaxf(y[2], y[3])), fmaxf(fmaxf(y[4], y[5]), fmaxf(y[6], y[7])));
          my = quad_max(fmaxf(my, fmaxf(y[8], y[9])));
#pragma unroll
          for (int i = 0; i < 10; i++) y[i] = ex2((y[i] - my) * L2E);
          float sy = ((y[0] + y[1]) + (y[2] + y[3])) + ((y[4] + y[5]) + (y[6] + y[7])) + (y[8] + y[9]);
          const float ry = rcp((sy + __shfl_xor_sync(~0u, sy, 1)) + (__shfl_xor_sync(~0u, sy, 2) + __shfl_xor_sync(~0u, sy, 3)));
          st_relaxed4(gptr(xhi, gp) + xo::PT, pack_bf16(y[2] * ry, y[3] * ry), pack_bf16(y[4] * ry, y[5] * ry), pack_bf16(y[6] * ry, y[7] * ry), pack_bf16(y[8] * ry, y[9] * ry));
          const uint32_t l12 = lv - (lv >> 2);
          st_relaxed1(gptr(xhi, gp - l12) + xo::PM, pack_bf16(y[0] * ry, y[1] * ry));
        }
        if (!xok && more) wait_x();
      }
    }
    if (more) {
      float acc[16];
      const uint32_t xph = (s + 1) & 1;
      auto batch = [&](const uint32_t (&a)[24][4], int o) {
        wg_fence();
#pragma unroll
        for (int ks = NTMP; ks < 8; ks++) wgmma_m64n32_ss_ta(acc, wdesc<WG>(o, ks), xdesc<WG>(24 + ks), ks != NTMP);
#pragma unroll
        for (int ks = 0; ks < NTMP; ks++) wgmma_m64n32_rs(acc, tmp[ks], xdesc<WG>(24 + ks), 1);
#pragma unroll
        for (int ks = 0; ks < 24; ks++) wgmma_m64n32_rs(acc, a[ks], xdesc<WG>(ks), 1);
        wg_commit();
        SFENCE(50 + o);
      };
      if (WG == 0) named_bar(12, 256);
      else if (__builtin_expect(s >= 0, 1)) named_bar(10, 256);
      batch(aW[1], 1);
      named_bar_arrive(WG ? 12 : 13, 256);
      wg_wait<0>();
      acc_fence(acc);
      load_tmp(0);
#pragma unroll
      for (int i = 0; i < 4; i++) sts128f(sb + OFF_FP + WG * 8192 + t16 + i * 512, make_float4(acc[4 * i], acc[4 * i + 1], acc[4 * i + 2], acc[4 * i + 3]));
      NEWZ(4);
      if (WG == 0 && s >= 0) {
        const uint32_t g1 = xh + slot_off(sv + 1);
        if (J == 0) gather_issue(sb + OFF_VT + tv, gptr(xhi, g1) + xo::VT);
        else {
          st_relaxed4(gptr(xhi, g1) + xo::PT, EMPTY, EMPTY, EMPTY, EMPTY);
          st_relaxed1(gptr(xhi, g1 - lv + (lv >> 2)) + xo::PM, EMPTY);
        }
      }
      uint32_t esrc = 0;
      if (WG == 1) { esrc = xm + t16 - l16 + 2048 + slot_off(sv + 1); tref += lds32(sb + CT_T); }
      named_bar(WG ? 13 : 14, 256);
      batch(aW[0], 0);
      NEWZ(5);
      if (WG == 1) {
        named_bar(14, 256);
        if (last_warp && s + 2 < NSEG) {
          expect_elect(sb + BAR_TOK + 8 * (xph ^ 1), 8192); expect_elect(sb + BAR_X, 32768); expect_elect(sb + BAR_X + 8, 32768);
          if (J == 0) expect_elect(sb + BAR_EX, 2048);
          if (s == NSEG - 3) asm volatile("griddepcontrol.launch_dependents;");
        }
      }
      const uint32_t tb = lds32(sb + CT_TT) + xph * 8192 + WG * 4096 + ((tv + l16) >> 1);
      float4 oth[4];
#pragma unroll
      for (int i = 0; i < 4; i++) oth[i] = lds128f(sb + OFF_FP + (WG ^ 1) * 8192 + t16 + i * 512);
      if (WG == 1 && __builtin_expect(s >= 0, 1)) {
        const uint32_t edst = sb + OFF_MEM + tv + t16 - l16;
        WAIT_UNTIL(tref, aW[0][0], 0, J ? 7 : 0);
        gather_issue<2, 2048>(edst, gptr(xhi, esrc) - 2048);
      }
      wg_wait<0>();
      acc_fence(acc);
      uint32_t lt[4], ht[4];
#pragma unroll
      for (int i = 0; i < 4; i++) {
        const float4 o = oth[i];
        lt[i] = pack_bf16(acc[4 * i] + o.x, acc[4 * i + 1] + o.y); ht[i] = pack_bf16(acc[4 * i + 2] + o.z, acc[4 * i + 3] + o.w);
      }
      stsm_x4_t(tb, lt[0], ht[0], lt[1], ht[1]); stsm_x4_t(tb + 512, lt[2], ht[2], lt[3], ht[3]);
      NEWZ(6);
      if (WG == 0 && last_warp) {
        load_ws();
        named_bar(11, 256);
        fence_async_smem();
        const uint32_t tt = (J ? OFF_KT : OFF_QT) + xph * 8192;
        asm volatile("{.reg .pred p; elect.sync _|p, 0xffffffff;\n"
                     "@p cp.async.bulk.shared::cluster.shared::cta.mbarrier::complete_tx::bytes [%0], [%1], 8192, [%2];}"
                     ::"r"(rsb + tt), "r"(sb + tt), "r"(rsb + BAR_TOK + 8 * xph) : "memory");
      } else {
        named_bar_arrive(11, 256);
        load_ws();
      }
    }
    if (!more) break;
    if (__builtin_expect(s < 0, 0)) {
      tref = gtime() / T_SLIP * T_SLIP - T_SLIP;
    }
  }
  cp_async_wait_group<0>();
  if (J == 0) mbar_wait(sb + BAR_TOK + 8, 1);
}

template <int WG>
__device__ __forceinline__ void role_v(const ChainMaps& maps, const bf16* __restrict__ mem0, const uint32_t sb, const uint32_t xbase_hi) {
  using namespace chain;
  const int h = blockIdx.x >> 2;
  const uint32_t u16 = (threadIdx.x & 96) * 64 + (threadIdx.x & 31) * 16;
  const uint32_t t16 = keep(u16), l16 = keep((threadIdx.x & 31) * 16);
  const uint32_t xhi = keep(xbase_hi + (t16 >> 16));
#define j (sb >> 24)
  auto wv_addr = [&](uint32_t t) { return WG * 32768 + ((t & 256) << 2) + ((t & 112) << 3) + ((((t >> 6) & 96) + ((t >> 3) & 16)) ^ (t & 112)); };
  auto wo_addr = [&](uint32_t t) { return OFF_WOR + WG * 32768 + ((t & 6144) << 2) + ((t & 256) << 1) + ((t & 112) << 2) + ((((j ^ 1) << 5) + ((t >> 3) & 16)) ^ ((t >> 1) & 48)); };
#define ovt (((tv + l16) >> 1) + (xo::VT + WG * 512 + j * 4096))
#define ovm (((tv & 4096) >> 1) + ((tv & 2048) >> 3) + (lv >> 1) + (xo::VM + j * 4096))
#define xvt (lds32(sb + CT_HEAD) + ovt)
#define xvm (lds32(sb + CT_HEAD) + ovm)
#define xom (lds32(sb + CT_OM) + t16 + WG * 8192)
#define warp_is(q) __any_sync(0xffffffffu, (tv >> 11) == (q))
#define upper_warps (WG == 1 || __any_sync(0xffffffffu, tv >= 4096))

  uint32_t aV[16][4];
  uint32_t aO[16][4];
  uint32_t bO[16][4];
  uint32_t rot[16][4];
  if (WG == 1 && __any_sync(0xffffffffu, t16 >= 6144)) {
    expect_elect(sb + BAR_X, 32768); expect_elect(sb + BAR_X + 8, 32768);
    issue_x(sb, &maps.x, 0, 0); issue_x(sb, &maps.x, 0, 1);
    prefetch_l2(maps.xp + 65536 + (h * 2 + j) * 3072, 3072);
  }
  cluster_arrive();
  { uint2 m0[8]; load_mem0(m0, mem0); store_mem0(sb, m0); }
  mbar_wait(sb + BAR_P, 0);
#pragma unroll
  for (int ks = 0; ks < 16; ks++) ldsm_x4_t(aV[ks], sb + wv_addr(t16) + OFF_WOR + ks * 2048);
  auto load_v = [&](uint32_t t) {
#pragma unroll
    for (int ks = 0; ks < 16; ks++) ldsm_x4_t(rot[ks], sb + wv_addr(t) + OFF_WVR + ks * 2048);
  };
  load_v(t16);
  named_bar(0, 256);
  if (threadIdx.x == 0) {
    fence_async_smem();
    mbar_expect_tx(sb + BAR_P + 8, 4 * 16384);
    for (int q = 0; q < 4; q++) tma_load_2d(sb + OFF_WOR + q * 16384, &maps.wo, h * 32, j * 2048 + q * 256, sb + BAR_P + 8);
    for (int q = 0; q < 4; q++) tma_prefetch_2d(&maps.wo, h * 32, j * 2048 + 1024 + q * 256);
  }
  __syncwarp();
  cluster_wait();
  const uint32_t rsb = sb ^ RANK_BIT;

  uint32_t tref = 0;
#pragma unroll 1
  for (int n = 0; n <= NSEG; n++) {
    const bool more = __builtin_expect(s + 1 < NSEG, 1);
    uint32_t zr = loop_zero<0>(n);
    bool xok = false;
    if (__builtin_expect(s >= 0, 1)) {
      if (__builtin_expect(s > 0, 1)) {
        const uint32_t dst = sb + OFF_MEM + WG * 8192 + t16 + ((lv >> 5) & 12);
        uint32_t tries = zr;
#pragma unroll 1
        do {
          if (tries) { const char* src = gptr(xhi, xm + WG * 8192 + slot_off(sv)); tref += T_SLIP; WAIT_UNTIL(tref, aV[0], 1, -1); gather_issue(sb + OFF_MEM + WG * 8192 + tv, src); }
          KEEPALIVE(aV[0], zr);
          cp_async_wait_group<0>();
        } while (gather_incomplete<1, 0>(dst) && ++tries < POLL_LIMIT);
        named_bar(1 + WG, 128);
      }
      const uint32_t a_mem = sb + OFF_MEM + WG * 8192 + l16;
      float c[2][4];
      c[0][0] = c[0][1] = c[0][2] = c[0][3] = c[1][0] = c[1][1] = c[1][2] = c[1][3] = 0.f;
      constexpr int NBUF = (48 - 8 - 4 * O_FIX) / 4;
      uint32_t b[NBUF][4];
#pragma unroll
      for (int p = 0; p < NBUF - 1; p++) ldsm_x4_t(b[p], a_mem + p * 512);
#pragma unroll
      for (int p = 0; p < 16; p++) {
        if (p + NBUF - 1 < 16) ldsm_x4_t(b[(p + NBUF - 1) % NBUF], a_mem + (p + NBUF - 1) * 512);
        if (p < 8) { mma16816(c[0], aV[2 * p], b[p % NBUF][0], b[p % NBUF][1]); mma16816(c[1], aV[2 * p + 1], b[p % NBUF][2], b[p % NBUF][3]); }
        else { mma16816(c[0], rot[2 * p - 16], b[p % NBUF][0], b[p % NBUF][1]); mma16816(c[1], rot[2 * p - 15], b[p % NBUF][2], b[p % NBUF][3]); }
      }
      xok = mbar_test(sb + BAR_X + 8 * WG, n & 1);
      SFENCE(15);
      const float4 own = make_float4(c[0][0] + c[1][0], c[0][1] + c[1][1], c[0][2] + c[1][2], c[0][3] + c[1][3]);
      NEWZ(1);
      const uint32_t pvm = WG == 0 ? xvm + slot_off(sv) : 0;
      if (WG == 1) sts128f(sb + OFF_VPX + wq * 512 + l16, own);
      named_bar(3, 256);
      if (WG == 0) {
        const float4 o = lds128f(sb + OFF_VPX + wq * 512 + l16);
        st_relaxed2(gptr(xhi, pvm), pack_bf16(own.x + o.x, own.y + o.y), pack_bf16(own.z + o.z, own.w + o.w));
      }
    }
    auto token_pv = [&](int seg, bool staged) {
      constexpr int NU = 2 - WG;
      uint4 pt0, pt1, v0[NU], v1[NU]; uint32_t pm0, pm1; uint2 vm[NU];
      const uint32_t ap = l16 + WG * 4096 + xo::PT, am = (lv >> 2) + WG * 4096 + xo::PM;
      const uint32_t at = ovt - WG * 512;
      if (staged) {
        const uint32_t b = sb + OFF_MEM;
        pt0 = lds128(b + ap); pt1 = lds128(b + ap + 2048); pm0 = lds32(b + am); pm1 = lds32(b + am + 2048);
#pragma unroll
        for (int u = 0; u < NU; u++) { v0[u] = lds128(b + at - u * 2048); v1[u] = lds128(b + at + 512 - u * 2048); vm[u] = lds64(b + ovm - u * 2048); }
      } else {
        const uint32_t b = lds32(sb + CT_HEAD) + slot_off(seg);
        pt0.x = EMPTY;
#pragma unroll
        for (int u = 0; u < NU; u++) {
          v0[u] = ld_relaxed4(gptr(xhi, b + at) - u * 2048); v1[u] = ld_relaxed4(gptr(xhi, b + at) + 512 - u * 2048);
          vm[u] = ld_relaxed2(gptr(xhi, b + ovm) - u * 2048);
        }
      }
      const bool odd = lv & 16;
      char* op = gptr(xhi, lds32(sb + CT_O) + (seg * SEG + WG * 16 + (lv >> 6)) * (HD * 2) + wq * 32 + (lv & 16) + ((lv >> 2) & 8));
      if (!staged || __builtin_expect(warp_incomplete(umax4(pt0.x, pt1.x, pm0, pm1)), 0)) {
        const uint32_t b = lds32(sb + CT_HEAD) + slot_off(seg);
        uint32_t tries = zr;
#pragma unroll 1
        do {
          pt0 = ld_relaxed4(gptr(xhi, b + ap)); pt1 = ld_relaxed4(gptr(xhi, b + ap) + 2048);
          pm0 = ld_relaxed1(gptr(xhi, b + am)); pm1 = ld_relaxed1(gptr(xhi, b + am) + 2048);
        } while (warp_incomplete(umax4(pt0.x, pt1.x, pm0, pm1)) && ++tries < POLL_LIMIT);
      }
      const uint32_t pa[4] = {pt0.x, pt1.x, pt0.y, pt1.y}, pb[4] = {pt0.z, pt1.z, pt0.w, pt1.w};
#pragma unroll
      for (int u = 0; u < NU; u++) {
        float o0[4] = {0.f, 0.f, 0.f, 0.f}, o1[4] = {0.f, 0.f, 0.f, 0.f};
        mma1688(o0, pm0, pm1, vm[u].x); mma1688(o1, pm0, pm1, vm[u].y);
        mma16816(o0, pa, v0[u].x, v0[u].y); mma16816(o1, pa, v1[u].x, v1[u].y);
        if (WG) { mma16816(o0, pb, v0[u].z, v0[u].w); mma16816(o1, pb, v1[u].z, v1[u].w); }
#pragma unroll
        for (int r = 0; r < 2; r++) {
          const uint32_t w0 = pack_bf16(o0[2 * r], o0[2 * r + 1]), w1 = pack_bf16(o1[2 * r], o1[2 * r + 1]);
          const uint32_t rv = __shfl_xor_sync(~0u, odd ? w0 : w1, 1);
          asm volatile("st.global.v2.u32 [%0], {%1, %2};" ::"l"(op + r * 8 * HD * 2 - u * 64), "r"(odd ? rv : w0), "r"(odd ? w1 : rv) : "memory");
        }
      }
    };
    if (!more) {
      named_bar(3, 256);
      if (upper_warps) {
#pragma unroll 1
        for (int seg = NSEG - 2; seg < NSEG; seg++) token_pv(seg, false);
      }
      break;
    }
    {
      if (__builtin_expect(s > 0, 1)) {
        const uint32_t o = WG ? ovt - 512 : tv + 512;
        const char* src = gptr(xhi, lds32(sb + CT_HEAD) + slot_off(sv - 1) + o);
#pragma unroll
        for (int i = 0; i < 3 - WG; i++) cp_async16(sb + OFF_MEM + o + i * 512, src + i * 512);
        cp_async_commit();
      }
      bool xw;
      {
        float acc[16];
        if (__builtin_expect(!xok, 0)) mbar_wait<0>(sb + BAR_X + 8 * WG, (s + 1) & 1);
        wg_fence();
#pragma unroll
        for (int ks = 0; ks < 16; ks++) wgmma_m64n32_rs(acc, rot[ks], xdesc<WG>(16 + ks), ks != 0);
        wg_commit();
#pragma unroll
        for (int ks = 0; ks < 16; ks++) wgmma_m64n32_rs(acc, aV[ks], xdesc<WG>(ks), 1);
        wg_commit();
        SFENCE(50);
        NEWZ(2);
        xw = warp_is(3) && s + 2 < NSEG;
        tref += lds32(sb + CT_T + 4) + (WG * T_LAG - T_SLIP);
        const uint32_t pvt = xvt + slot_off(sv + 1), awo = sb + wo_addr(tv);
        if (WG == 0 && warp_is(1) && s >= 0) expect_elect(sb + BAR_EX, 512);
        if (xw) {
          expect_elect(sb + BAR_X + 8 * WG, 32768);
          if (WG == 1 && s == NSEG - 3) asm volatile("griddepcontrol.launch_dependents;");
          if (WG == 1 && s + 5 < NSEG) prefetch_l2(maps.xp + (s + 5) * 65536 + lds32(sb + CT_PF), 1024);
        }
        wg_wait<1>();
        if (xw) { named_bar(4 + WG, 128); issue_x(sb, &maps.xq, s + 2, WG, 1); }
        else if (s + 2 < NSEG) named_bar_arrive(4 + WG, 128);
        if (__builtin_expect(s == 0, 0)) {
          mbar_wait(sb + BAR_P + 16, 0);
#pragma unroll
          for (int ks = 16 - O_FIX; ks < 16; ks++) ldsm_x4_t(bO[ks], (awo ^ 32) + (ks & 7) * 1024);
        }
#pragma unroll
        for (int ks = 0; ks < 16 - O_FIX; ks++) ldsm_x4_t(bO[ks], (ks < 8 ? awo : awo ^ 32) + (ks & 7) * 1024);
        wg_wait<0>();
        acc_fence(acc);
        constexpr int K = WG * 2, G = 2 - K;
        sts128f(sb + OFF_RED + WG * 1024 + t16, make_float4(acc[G], acc[G + 1], acc[4 + G], acc[5 + G]));
        sts128f(sb + OFF_RED + WG * 1024 + 512 + t16, make_float4(acc[8 + G], acc[9 + G], acc[12 + G], acc[13 + G]));
        cp_async_wait_group<0>();
        named_bar(3, 256);
        const float4 o0 = lds128f(sb + OFF_RED + (WG ^ 1) * 1024 + t16), o1 = lds128f(sb + OFF_RED + (WG ^ 1) * 1024 + 512 + t16);
        st_relaxed4(gptr(xhi, pvt),
                    pack_bf16(acc[K] + o0.x, acc[K + 1] + o0.y), pack_bf16(acc[4 + K] + o0.z, acc[5 + K] + o0.w),
                    pack_bf16(acc[8 + K] + o1.x, acc[9 + K] + o1.y), pack_bf16(acc[12 + K] + o1.z, acc[13 + K] + o1.w));
      }
      if (__builtin_expect(s >= 0, 1)) {
        uint32_t tries = 0;
#pragma unroll
        for (int ks = 0; ks < 16 - O_FIX; ks++) tries |= bO[ks][0];
        const char* po = gptr(xhi, xom + slot_off(sv) + (tries & zr));
        tries = zr;
        float d[2][2][4];
        uint32_t mx;
#pragma unroll 1
        do {
          tref += T_SLIP;
          WAIT_UNTIL(tref, aV[0], 1, 1);
          uint4 o[8];
#pragma unroll
          for (int i = 0; i < 4; i++) o[i] = ld_relaxed4(po + i * 512);
#pragma unroll
          for (int i = 0; i < 4; i++) o[4 + i] = ld_relaxed4(po + 16384 + i * 512);
          __syncwarp();
#pragma unroll
          for (int i = 0; i < 2; i++)
#pragma unroll
            for (int q = 0; q < 2; q++) { d[i][q][0] = d[i][q][1] = d[i][q][2] = d[i][q][3] = 0.f; }
#pragma unroll
          for (int i = 0; i < 4; i++) {
            mma16816(d[0][0], aO[2 * i], o[i].x, o[i].y); mma16816(d[1][0], aO[8 + 2 * i], o[i].x, o[i].y);
            mma16816(d[0][1], aO[2 * i + 1], o[i].z, o[i].w); mma16816(d[1][1], aO[9 + 2 * i], o[i].z, o[i].w);
          }
          mx = umax4(o[0].w, o[1].w, o[2].w, o[3].w);
          SFENCE(33 + tries);
#pragma unroll
          for (int i = 0; i < 4; i++) {
            mma16816(d[0][0], bO[2 * i], o[4 + i].x, o[4 + i].y); mma16816(d[1][0], bO[8 + 2 * i], o[4 + i].x, o[4 + i].y);
            mma16816(d[0][1], bO[2 * i + 1], o[4 + i].z, o[4 + i].w); mma16816(d[1][1], bO[9 + 2 * i], o[4 + i].z, o[4 + i].w);
          }
          mx = max(mx, umax4(o[4].w, o[5].w, o[6].w, o[7].w));
        } while (warp_incomplete(mx) && ++tries < POLL_LIMIT);
        NEWZ(3);
        const uint32_t rd = sb + OFF_RED + (WG ^ 1) * 1024 + t16;
        sts128f(rd, make_float4(d[0][0][0] + d[0][1][0], d[0][0][1] + d[0][1][1], d[0][0][2] + d[0][1][2], d[0][0][3] + d[0][1][3]));
        sts128f(rd + 512, make_float4(d[1][0][0] + d[1][1][0], d[1][0][1] + d[1][1][1], d[1][0][2] + d[1][1][2], d[1][0][3] + d[1][1][3]));
        if (upper_warps) {
          named_bar_arrive(7, 256);
          if (xw) issue_x(sb, &maps.xq, s + 2, WG, 0);
          if (__builtin_expect(s > 0, 1)) token_pv(sv - 1, true);
        } else {
          uint32_t mp = lds32(sb + CT_MP) + (lv >> 2);
          named_bar(7, 256);
          float4 p[8];
#pragma unroll
          for (int i = 0; i < 8; i++) p[i] = lds128f(sb + OFF_RED + lv + wq * 512 + i * 1024);
          float4 r;
          r.x = ((p[0].x + p[1].x) + (p[2].x + p[3].x)) + ((p[4].x + p[5].x) + (p[6].x + p[7].x));
          r.y = ((p[0].y + p[1].y) + (p[2].y + p[3].y)) + ((p[4].y + p[5].y) + (p[6].y + p[7].y));
          r.z = ((p[0].z + p[1].z) + (p[2].z + p[3].z)) + ((p[4].z + p[5].z) + (p[6].z + p[7].z));
          r.w = ((p[0].w + p[1].w) + (p[2].w + p[3].w)) + ((p[4].w + p[5].w) + (p[6].w + p[7].w));
          const bool w0 = warp_is(0);
          if (w0) st_async4(rsb + OFF_RX + lv, __float_as_uint(r.x), __float_as_uint(r.y), __float_as_uint(r.z), __float_as_uint(r.w), rsb + BAR_EX);
          if (!w0) {
            char* pp = gptr(xhi, mp + slot_off(sv + 1));
            mbar_wait(sb + BAR_EX, s & 1);
            const float4 q = lds128f(sb + OFF_RX + l16);
            st_relaxed1(pp, pack_bf16(r.x + q.x, r.y + q.y)); st_relaxed1(pp + 128, pack_bf16(r.z + q.z, r.w + q.w));
            pp = gptr(xhi, mp + slot_off(sv + 3));
            st_relaxed1(pp, EMPTY); st_relaxed1(pp + 128, EMPTY);
          }
        }
        NEWZ(4);
        const char* src = gptr(xhi, xm + WG * 8192 + slot_off(sv + 1));
        const uint32_t awv = sb + wv_addr(tv) + OFF_WVR;
        tref += lds32(sb + CT_T + 8) - WG * T_LAG;
        named_bar(8, 256);
#pragma unroll
        for (int ks = 0; ks < V_PRE; ks++) ldsm_x4_t(rot[ks], awv + ks * 2048);
        WAIT_UNTIL(tref, aV[0], 1, 2);
        gather_issue(sb + OFF_MEM + WG * 8192 + tv, src);
#pragma unroll
        for (int ks = V_PRE; ks < 16; ks++) ldsm_x4_t(rot[ks], awv + ks * 2048);
        NEWZ(6);
        st_relaxed4(gptr(xhi, xvt + slot_off(sv + 2)), EMPTY, EMPTY, EMPTY, EMPTY);
        if (WG == 0) st_relaxed2(gptr(xhi, xvm + slot_off(sv + 2)), EMPTY, EMPTY);
      } else {
        load_v(tv);
        if (xw) issue_x(sb, &maps.xq, s + 2, WG, 0);
        mbar_wait(sb + BAR_P + 8, 0);
#pragma unroll
        for (int ks = 0; ks < 8; ks++) { ldsm_x4_t(aO[ks], sb + wo_addr(tv) + ks * 1024); ldsm_x4_t(aO[8 + ks], sb + (wo_addr(tv) ^ 32) + ks * 1024); }
        named_bar(0, 256);
        if (threadIdx.x == 0) {
          fence_async_smem();
          mbar_expect_tx(sb + BAR_P + 16, 4 * 16384);
          for (int q = 0; q < 4; q++) tma_load_2d(sb + OFF_WOR + q * 16384, &maps.wo, h * 32, j * 2048 + 1024 + q * 256, sb + BAR_P + 16);
        }
        __syncwarp();
        tref = gtime() / T_SLIP * T_SLIP - T_SLIP;
      }
    }
  }
}

#undef j
#undef s
#undef sv
#undef xm
#undef wq

__global__ void __launch_bounds__(256, 1) __cluster_dims__(2, 1, 1)
chain_kernel(const __grid_constant__ ChainMaps maps, const bf16* __restrict__ mem0, const uint64_t xbase) {
  using namespace chain;
  extern __shared__ uint8_t smem_raw[];
  uint32_t sb = smem_u32(smem_raw);
  PIN(sb);
  if (sb != SB_LO + (blockIdx.x & 1) * RANK_BIT || mapa(sb, (blockIdx.x & 1) ^ 1) != (sb ^ RANK_BIT)) __trap();
  const int tid = threadIdx.x;
  const int h = blockIdx.x >> 2, role = (blockIdx.x >> 1) & 1, j = blockIdx.x & 1;
  if (tid == 0) {
    for (int i = 0; i < 9; i++) mbar_init(sb + OFF_BAR + 8 * i, 1);
    asm volatile("fence.mbarrier_init.release.cluster;" ::: "memory");
    const uint32_t xl = (uint32_t)xbase;
    sts32(sb + CT_BASE, xl); sts32(sb + CT_HEAD, xl + h * xo::HEAD); sts32(sb + CT_OM, xl + xo::OM + (role ? j * 32768 : h * 2048));
    sts32(sb + CT_MP, xl + xo::MEM + (h * 2 + j) * 256); sts32(sb + CT_O, xl + xo::O + (h * 2 + j) * 128); sts32(sb + CT_PF, (h * 2 + j) * 1024);
    sts32(sb + CT_TT, sb + (j ? OFF_KT : OFF_QT));
    if (role == 0) {
      const CUtensorMap* wm = j ? &maps.wk : &maps.wq;
      mbar_expect_tx(sb + BAR_P, 6 * 16384);
      for (int c = 0; c < 3; c++)
        for (int q = 0; q < 2; q++) tma_load_2d(sb + OFF_X + (q * 3 + c) * 16384, wm, h * DH + q * 64, q * 512 + c * 128, sb + BAR_P);
      mbar_expect_tx(sb + BAR_P + 8, 4 * 16384);
      for (int c = 0; c < 2; c++)
        for (int q = 0; q < 2; q++) tma_load_2d(sb + OFF_X + (6 + q * 2 + c) * 16384, wm, h * DH + (q ^ 1) * 64, q * 512 + c * 128, sb + BAR_P + 8);
      mbar_expect_tx(sb + BAR_P + 24, 4 * 16384);
      for (int q = 0; q < 2; q++)
        for (int o = 0; o < 2; o++) tma_load_2d(sb + OFF_WS + (q * 2 + o) * 16384, wm, h * DH + (q ^ o) * 64, q * 512 + 384, sb + BAR_P + 24);
      for (int q = 0; q < 2; q++) tma_prefetch_2d(wm, h * DH + (q ^ 1) * 64, q * 512 + 256);
    } else {
      mbar_expect_tx(sb + BAR_P, 8 * 16384);
      for (int q = 0; q < 4; q++) tma_load_2d(sb + OFF_WOR + q * 16384, &maps.wv, h * DH + j * 64, (q >> 1) * 512 + (q & 1) * 128, sb + BAR_P);
      for (int q = 0; q < 4; q++) tma_load_2d(sb + OFF_WVR + q * 16384, &maps.wv, h * DH + j * 64, (q >> 1) * 512 + 256 + (q & 1) * 128, sb + BAR_P);
    }
  }
  for (int r = 0; r < RING; r++) {
    char* p = (char*)xbase + r * xo::SLOT;
    const int wq = (tid >> 5) & 3;
    if (role == 1) st_relaxed4(p + h * xo::HEAD + xo::VT + (8 * j + 2 * wq + (tid >> 7)) * 512 + (tid & 31) * 16, EMPTY, EMPTY, EMPTY, EMPTY);
    else if (j == 0) st_relaxed4(p + (tid < 128 ? xo::OM + h * 2048 + tid * 16 : h * xo::HEAD + wq * 2048 + xo::VM + (tid & 31) * 16), EMPTY, EMPTY, EMPTY, EMPTY);
    else {
      st_relaxed4(p + h * xo::HEAD + (tid >> 6) * 2048 + 1024 + (tid & 63) * 16, EMPTY, EMPTY, EMPTY, EMPTY);
      if (tid < 32) st_relaxed4(p + xo::MEM + h * 512 + tid * 16, EMPTY, EMPTY, EMPTY, EMPTY);
    }
  }
  __syncthreads();
  if (__shfl_sync(0xffffffffu, tid >> 5, 0) == 0) {
    uint32_t t[2], c[2], ka[4] = {0, 0, 0, 0};
    const uint32_t z = maps.t_step >> 24;
#pragma unroll
    for (int i = 0; i < 2; i++) {
      const uint32_t end = (gtime() & ~31u) + (i ? 2048 : 1024);
      for (int g = z; g < 256 && (int)(gtime() - (end - 96)) < 0; g++) KEEPALIVE(ka, z);
      for (int g = z; g < 256 && (int)((t[i] = gtime()) - end) < 0; g++) {}
      c[i] = (uint32_t)clock64();
    }
    uint32_t v = 0, target = 0;
    if (tid == 0) {
      st_relaxed1(&g_rate[blockIdx.x], (t[1] - t[0]) * 4096u / (c[1] - c[0]));
      __threadfence();
      target = (atomicAdd(&g_epoch, 1u) & ~127u) + 128u;
    }
    target = __shfl_sync(0xffffffffu, target, 0);
    int guard = 0;
    do { asm volatile("ld.acquire.gpu.global.u32 %0, [%1];" : "=r"(v) : "l"(&g_epoch) : "memory"); }
    while (__any_sync(0xffffffffu, (int)(v - target) < 0) && ++guard < (1 << 20));
    const uint4 r4 = ld_relaxed4(&g_rate[tid * 4]);
    uint32_t r = min(__reduce_max_sync(0xffffffffu, umax4(r4.x, r4.y, r4.z, r4.w)), 4 * RATE0);
    if (r < RATE0 + 28) r = RATE0;
    const uint32_t a = (maps.t_step * r / RATE0 + 31) & ~31u, b = (maps.t_phase * r / RATE0 + 31) & ~31u;
    sts128(sb + CT_T, make_uint4(a, b, a - b, r));
  }
  const uint32_t xhi = (uint32_t)(xbase >> 32);
  const int wg = __shfl_sync(0xffffffffu, tid >> 7, 0);
  if (role == 0) {
    if (wg == 0) role_a<0>(maps, mem0, sb, xhi); else role_a<1>(maps, mem0, sb, xhi);
  } else {
    if (wg == 0) role_v<0>(maps, mem0, sb, xhi); else role_v<1>(maps, mem0, sb, xhi);
  }
  __syncwarp();
  cluster_arrive();
  cluster_wait();
}

struct BMaps {
  CUtensorMap q, k, v, out, k8;
  const bf16 *shift_k, *ssm_k, *ssm_D;
};

#define B_SLEEP 200
namespace bp {
constexpr int U_PITCH = (2048 + 128) * 2 + 16;
constexpr int KR_WORDS = 1048;
constexpr int KR_PITCH = 8704;
constexpr int OFF_U = 0;
constexpr int OFF_KR = (8 * U_PITCH + 127) / 128 * 128;
constexpr int Q_OFF = 4352;
constexpr int OFF_BAR = OFF_KR + 8 * KR_PITCH;
constexpr int GROUP_BYTES = OFF_BAR + 128;
constexpr int SMEM = 2 * GROUP_BYTES + 128;
constexpr int NTASK = DM / 8;
static_assert(Q_OFF >= 4224 && Q_OFF + 4096 <= KR_PITCH, "staging does not fit");
}

__device__ __forceinline__ uint32_t bmul2(uint32_t a, uint32_t b) { uint32_t r; asm("mul.rn.bf16x2 %0, %1, %2;" : "=r"(r) : "r"(a), "r"(b)); return r; }
__device__ __forceinline__ uint32_t badd2(uint32_t a, uint32_t b) { uint32_t r; asm("add.rn.bf16x2 %0, %1, %2;" : "=r"(r) : "r"(a), "r"(b)); return r; }

__device__ __forceinline__ void mbar_wait_sleep(uint32_t bar, uint32_t parity) {
  int guard = 0;
  while (!mbar_try(bar, parity)) { __nanosleep(B_SLEEP); if (++guard > (1 << 22)) __trap(); }
}

__device__ __forceinline__ void bpart_body(const BMaps& maps, int first, int stride, int end) {
  using namespace bp;
  extern __shared__ uint8_t smem_all[];
  const int grp = __shfl_sync(0xffffffffu, threadIdx.x >> 8, 0);
  const int lane = keep(threadIdx.x & 31), g = lane >> 2, t = lane & 3;
  const int w = __shfl_sync(0xffffffffu, (threadIdx.x >> 5) & 7, 0);
  const uint32_t sb = ((smem_u32(smem_all) + 127) & ~127u) + grp * GROUP_BYTES;
  const uint32_t kr = sb + OFF_KR + w * KR_PITCH, bar_k = sb + OFF_BAR + 8 * w, bar_q = bar_k + 64;
  if (lane == 0) { mbar_init(bar_k, 1); mbar_init(bar_q, 1); asm volatile("fence.mbarrier_init.release.cluster;" ::: "memory"); }
  if (lane < 16) sts128(sb + OFF_U + w * U_PITCH + lane * 16, make_uint4(0, 0, 0, 0));
  __syncwarp();
  if (grp == 1) { named_bar_arrive(3, 512); named_bar(5, 512); }
  const int lm = lane >> 3, lr = lane & 7;
  uint32_t ph = 0;
  for (int task = first + grp; task < end; task += stride, ph ^= 1) {
    const int d0 = task * 8;
    uint4 x[8];
    {
      const uint4* kf = (const uint4*)(maps.ssm_k + (size_t)(d0 + w) * S_LEN);
#pragma unroll
      for (int it = 0; it < 8; it++) x[it] = __ldg(kf + it * 32 + lane);
    }
    const uint4 ska = __ldg((const uint4*)(maps.shift_k + (d0 + 2 * t) * 4));
    __syncwarp();
    if (lane == 0) {
      mbar_expect_tx(bar_k, 2 * 4096 + 128);
      tma_load_2d(kr + 4096, &maps.k8, d0, w * 256 + 248, bar_k);
      tma_load_2d(kr, &maps.k, d0, w * 256 - 8, bar_k);
      bulk_wait_read<0>();
      tma_load_2d(kr + Q_OFF, &maps.v, d0, w * 256, bar_k);
    }
    __syncwarp();
    if (task == first) named_bar_arrive(5, 512);
    const uint32_t sk[4] = {__byte_perm(ska.x, ska.z, 0x5410), __byte_perm(ska.x, ska.z, 0x7632), __byte_perm(ska.y, ska.w, 0x5410), __byte_perm(ska.y, ska.w, 0x7632)};
    mbar_wait_sleep(bar_k, ph);
    {
      const uint32_t ka = kr + (lane + 8) * 16;
#pragma unroll
      for (int i = 0; i < 8; i++) {
        uint32_t k0[4], k1[4], k2[4], k3[4], v[4], r[4];
        ldsm_x4(k3, ka + i * 512 - 48); ldsm_x4(k2, ka + i * 512 - 32); ldsm_x4(k1, ka + i * 512 - 16); ldsm_x4(k0, ka + i * 512);
        ldsm_x4(v, ka + (Q_OFF - 128) + i * 512);
#pragma unroll
        for (int b = 0; b < 4; b++) {
          uint32_t acc = bmul2(k3[b], sk[3]);
          acc = badd2(acc, bmul2(k2[b], sk[2]));
          acc = badd2(acc, bmul2(k1[b], sk[1]));
          acc = badd2(acc, bmul2(k0[b], sk[0]));
          r[b] = bmul2(acc, v[b]);
        }
        const int ch = 16 + w * 32 + i * 4 + lm;
        stsm_x4_t(sb + OFF_U + lr * U_PITCH + ((ch ^ ((ch >> 3) & 1)) << 4), r[0], r[1], r[2], r[3]);
      }
    }
    __syncwarp();
    {
      const uint32_t c0 = kr, c1 = c0 + (KR_WORDS + 16) * 4;
      uint32_t carry = 0;
#pragma unroll
      for (int it = 0; it < 8; it++) {
        const int blk = it * 32 + lane;
        uint32_t prev = __shfl_up_sync(0xffffffffu, x[it].w, 1);
        if (lane == 0) prev = carry;
        carry = __shfl_sync(0xffffffffu, x[it].w, 31);
        sts128(c0 + (1028 - 4 * blk) * 4, make_uint4(__byte_perm(x[it].w, 0, 0x1032), __byte_perm(x[it].z, 0, 0x1032),
                                                     __byte_perm(x[it].y, 0, 0x1032), __byte_perm(x[it].x, 0, 0x1032)));
        sts128(c1 + (1028 - 4 * blk) * 4, make_uint4(__byte_perm(x[it].w, x[it].z, 0x7610), __byte_perm(x[it].z, x[it].y, 0x7610),
                                                     __byte_perm(x[it].y, x[it].x, 0x7610), __byte_perm(x[it].x, prev, 0x7610)));
      }
      if (lane < 4) { sts128(c0 + (1032 + 4 * lane) * 4, make_uint4(0, 0, 0, 0)); sts128(c1 + (1032 + 4 * lane) * 4, make_uint4(0, 0, 0, 0)); }
      __syncwarp();
    }
    named_bar(3 + grp, 512);
    float acc[16][4];
#pragma unroll
    for (int jn = 0; jn < 16; jn++) { acc[jn][0] = acc[jn][1] = acc[jn][2] = acc[jn][3] = 0.f; }
    {
      const uint32_t ub = sb + OFF_U + w * U_PITCH;
      uint32_t kd = kr + (((g & 1) ? 0 : KR_WORDS + 16) + ((((g & 1) ? 2063 : 2062) - (g - 2 * t)) >> 1)) * 4;
      uint32_t uc = 2 * (8 + lr + (lm >> 1) * 8) + (lm & 1);
#pragma unroll 1
      for (int d0s = 0; d0s < 8; d0s++, kd -= 32, uc -= 2) {
        const uint32_t uf = ub + ((uc ^ ((uc >> 3) & 1)) << 4);
        uint32_t A[3][4];
        A[0][0] = lds32v(kd); A[0][1] = lds32v(kd - 16); A[0][2] = lds32v(kd + 16); A[0][3] = lds32v(kd);
        uint32_t F[8][4];
#pragma unroll
        for (int m = 7; m >= 0; m--) ldsm_x4(F[m], uf + m * 512);
#pragma unroll
        for (int i = 0; i < 16; i++) {
          if (i + 1 < 16) {
            A[(i + 1) % 3][0] = lds32v(kd - 256 * (i + 1)); A[(i + 1) % 3][1] = lds32v(kd - 256 * (i + 1) - 16);
            A[(i + 1) % 3][2] = lds32v(kd - 256 * (i + 1) + 16); A[(i + 1) % 3][3] = lds32v(kd - 256 * (i + 1));
          }
#pragma unroll
          for (int jn = 15; jn >= i; jn--) mma16816(acc[jn], A[i % 3], F[(jn - i) >> 1][((jn - i) & 1) * 2], F[(jn - i) >> 1][((jn - i) & 1) * 2 + 1]);
        }
      }
    }
    named_bar_arrive(3 + (grp ^ 1), 512);
    __syncwarp();
    fence_async_smem();
    __syncwarp();
    if (lane == 0) { mbar_expect_tx(bar_q, 4096); tma_load_2d(kr + Q_OFF, &maps.q, d0, w * 256, bar_q); }
    const uint32_t dpair = __ldg((const uint32_t*)(maps.ssm_D + d0) + t);
    {
      const uint32_t ya = kr + w * 16 + (((lm >> 1) * 8 + lr) * 32) + (lm & 1) * 16;
#pragma unroll
      for (int jn = 0; jn < 16; jn += 2)
        stsm_x4_t(ya + jn * 256, pack_bf16(acc[jn][0], acc[jn][1]), pack_bf16(acc[jn][2], acc[jn][3]),
                  pack_bf16(acc[jn + 1][0], acc[jn + 1][1]), pack_bf16(acc[jn + 1][2], acc[jn + 1][3]));
    }
    named_bar(1 + grp, 256);
    mbar_wait_sleep(bar_q, ph);
    {
      const uint32_t ya = sb + OFF_KR + lr * (KR_PITCH + 16) + (w * 256 + lm * 8) * 2;
#pragma unroll
      for (int i = 0; i < 8; i++) {
        uint32_t y[4], u[4], q[4], r[4];
        ldsm_x4(q, kr + Q_OFF + lane * 16 + i * 512);
        ldsm_x4_t(y, ya + i * 64);
        const int ch = 16 + w * 32 + i * 4 + lm;
        ldsm_x4_t(u, sb + OFF_U + lr * U_PITCH + ((ch ^ ((ch >> 3) & 1)) << 4));
#pragma unroll
        for (int b = 0; b < 4; b++) r[b] = bmul2(q[b], badd2(y[b], bmul2(u[b], dpair)));
        stsm_x4(kr + Q_OFF + lane * 16 + i * 512, r[0], r[1], r[2], r[3]);
      }
      fence_async_smem();
      __syncwarp();
      if (lane == 0) { tma_store_2d(&maps.out, kr + Q_OFF, DM + d0, w * 256); bulk_commit(); }
    }
    named_bar(1 + grp, 256);
  }
  if (lane == 0) bulk_wait<0>();
}

__global__ void __launch_bounds__(512, 1) __cluster_dims__(2, 1, 1) bpart_kernel(const __grid_constant__ BMaps maps, int end) {
  bpart_body(maps, blockIdx.x * 2, gridDim.x * 2, end);
}

struct GemmMaps {
  CUtensorMap o;
  CUtensorMap w;
  CUtensorMap c;
};
namespace k3 {
constexpr int STAGES = 6;
constexpr int W_BYTES = 2 * 8192, O_BYTES = K3_N * 128, STAGE_BYTES = W_BYTES + O_BYTES;
constexpr int TT = (S_LEN + K3_N - 1) / K3_N, NGEMM = TT * (DM / 128), NB = 128 - NGEMM, KSTEPS = HD / 64;
constexpr int SMEM_G = STAGES * STAGE_BYTES + 1024 + 256;
constexpr int SMEM = SMEM_G > bp::SMEM ? SMEM_G : bp::SMEM;
static_assert(STAGE_BYTES % 1024 == 0, "swizzle atoms");
}

__global__ void __launch_bounds__(512, 1)
tail_kernel(const __grid_constant__ GemmMaps maps, const __grid_constant__ BMaps bmaps) {
  using namespace k3;
  if (blockIdx.x < NB) {
    bpart_body(bmaps, bp::NTASK - 2 * NB + 2 * blockIdx.x, bp::NTASK, bp::NTASK);
    return;
  }
  extern __shared__ uint8_t smem_raw[];
  const uint32_t sbase = (smem_u32(smem_raw) + 1023) & ~1023u;
  const uint32_t bars = sbase + STAGES * STAGE_BYTES;
  const int tid = threadIdx.x, warp = tid >> 5;
  const int tt = (blockIdx.x - NB) / 8, ct = (blockIdx.x - NB) % 8;

  if (tid == 0) {
    for (int s = 0; s < STAGES; s++) { mbar_init(bars + 8 * s, 1); mbar_init(bars + 8 * (STAGES + s), 2); }
    asm volatile("fence.mbarrier_init.release.cluster;" ::: "memory");
  }
  __syncthreads();

  if (warp >= 8) {
    if (tid == 256) {
      tma_prefetch_desc(&maps.o);
      for (int k = 0; k < STAGES; k++) {
        const uint32_t full = bars + 8 * k, sa = sbase + k * STAGE_BYTES;
        mbar_expect_tx(full, STAGE_BYTES);
#pragma unroll
        for (int j = 0; j < 2; j++) tma_load_2d(sa + j * 8192, &maps.w, ct * 128 + j * 64, k * 64, full);
      }
      asm volatile("griddepcontrol.wait;" ::: "memory");
      int stage = 0; uint32_t ph = 1;
      for (int k = 0; k < KSTEPS; k++) {
        mbar_wait(bars + 8 * (STAGES + stage), ph);
        const uint32_t full = bars + 8 * stage, sa = sbase + stage * STAGE_BYTES;
        const bool pre = k < STAGES;
        if (!pre) mbar_expect_tx(full, STAGE_BYTES);
        tma_load_2d(sa + W_BYTES, &maps.o, k * 64, tt * K3_N, full);
        if (!pre) {
#pragma unroll
          for (int j = 0; j < 2; j++) tma_load_2d(sa + j * 8192, &maps.w, ct * 128 + j * 64, k * 64, full);
        }
        if (++stage == STAGES) { stage = 0; ph ^= 1; }
      }
    }
  } else {
    const int wg = warp >> 2, lane = tid & 31, wq = warp & 3;
    int stage = 0; uint32_t ph = 0;
    float acc[K3_N / 2];
    int prev = -1;
    for (int k = 0; k < KSTEPS; k++) {
      mbar_wait(bars + 8 * stage, ph);
      const uint32_t sa = sbase + stage * STAGE_BYTES;
      wg_fence();
#pragma unroll
      for (int kk = 0; kk < 4; kk++) {
        const uint64_t da = make_desc(sa + wg * 8192 + kk * 2048, 16, 1024, 1);
        const uint64_t db = make_desc(sa + W_BYTES + kk * 32, 16, 1024, 1);
        wgmma_k3_ss_ta(acc, da, db, (k | kk) != 0);
      }
      wg_commit();
      if (prev >= 0) { wg_wait<1>(); if ((tid & 127) == 0) mbar_arrive(bars + 8 * (STAGES + prev)); }
      prev = stage;
      if (++stage == STAGES) { stage = 0; ph ^= 1; }
    }
    wg_wait<0>();
#pragma unroll
    for (int i = 0; i < K3_N / 2; i++) asm volatile("" : "+f"(acc[i]) :: "memory");
    named_bar(1, 256);
    const uint32_t ebuf = sbase + wg * STAGE_BYTES;
    const uint32_t ea = ebuf + ((lane >> 4) * 8 + (lane & 7)) * 128 + (((2 * wq + ((lane >> 3) & 1)) ^ (lane & 7)) << 4);
#pragma unroll
    for (int i = 0; i < K3_N / 8; i += 2) {
      const int i1 = i + 1 < K3_N / 8 ? i + 1 : i;
      stsm_x4_t(ea + i * 1024, pack_bf16(acc[4 * i], acc[4 * i + 1]), pack_bf16(acc[4 * i + 2], acc[4 * i + 3]),
                pack_bf16(acc[4 * i1], acc[4 * i1 + 1]), pack_bf16(acc[4 * i1 + 2], acc[4 * i1 + 3]));
    }
    fence_async_smem();
    named_bar(2 + wg, 128);
    if ((tid & 127) == 0) {
      tma_store_2d(&maps.c, ebuf, ct * 128 + wg * 64, tt * K3_N);
      bulk_commit();
      bulk_wait<0>();
    }
  }
}

typedef CUresult (*EncodeFn)(CUtensorMap*, CUtensorMapDataType, cuuint32_t, void*, const cuuint64_t*, const cuuint64_t*,
                             const cuuint32_t*, const cuuint32_t*, CUtensorMapInterleave, CUtensorMapSwizzle,
                             CUtensorMapL2promotion, CUtensorMapFloatOOBfill);

void make_map(EncodeFn enc, CUtensorMap* m, const void* ptr, uint64_t cols, uint64_t rows, uint64_t pitch_elems,
              uint32_t box_cols, uint32_t box_rows, CUtensorMapSwizzle swz,
              CUtensorMapL2promotion promo = CU_TENSOR_MAP_L2_PROMOTION_L2_128B) {
  cuuint64_t dims[2] = {cols, rows};
  cuuint64_t strides[1] = {pitch_elems * 2};
  cuuint32_t box[2] = {box_cols, box_rows};
  cuuint32_t es[2] = {1, 1};
  enc(m, CU_TENSOR_MAP_DATA_TYPE_BFLOAT16, 2, const_cast<void*>(ptr), dims, strides, box, es, CU_TENSOR_MAP_INTERLEAVE_NONE, swz,
      promo, CU_TENSOR_MAP_FLOAT_OOB_FILL_NONE);
}

void make_map_nd(EncodeFn enc, CUtensorMap* m, const void* ptr, int rank, const uint64_t* dims, const uint64_t* strides_elems,
                 const uint32_t* box, CUtensorMapSwizzle swz) {
  cuuint64_t d[5], st[4]; cuuint32_t b[5], es[5];
  for (int i = 0; i < rank; i++) { d[i] = dims[i]; b[i] = box[i]; es[i] = 1; if (i) st[i - 1] = strides_elems[i] * 2; }
  enc(m, CU_TENSOR_MAP_DATA_TYPE_BFLOAT16, rank, const_cast<void*>(ptr), d, st, b, es, CU_TENSOR_MAP_INTERLEAVE_NONE, swz,
      CU_TENSOR_MAP_L2_PROMOTION_L2_128B, CU_TENSOR_MAP_FLOAT_OOB_FILL_NONE);
}

}

extern "C" void kernel_launch(void* const* d_in, const int* in_sizes, int n_in, void* d_out, int out_size) {
  (void)in_sizes; (void)n_in; (void)out_size;
  const bf16* x = (const bf16*)d_in[0];
  const bf16* mem0 = (const bf16*)d_in[1];
  const bf16* Wq = (const bf16*)d_in[2];
  const bf16* Wk = (const bf16*)d_in[3];
  const bf16* Wv = (const bf16*)d_in[4];
  const bf16* Wo = (const bf16*)d_in[5];
  const bf16* Bq = (const bf16*)d_in[7];
  const bf16* Bk = (const bf16*)d_in[8];
  const bf16* Bv = (const bf16*)d_in[9];
  const bf16* shift_k = (const bf16*)d_in[10];
  const bf16* ssm_k = (const bf16*)d_in[11];
  const bf16* ssm_D = (const bf16*)d_in[12];
  bf16* out = (bf16*)d_out;

  static EncodeFn enc = nullptr;
  static uint64_t xbase0;
  static int nsm = 132;
  static cudaStream_t s1;
  static cudaEvent_t ev_fork, ev_join;
  if (!enc) {
    cudaDriverEntryPointQueryResult qr;
    void* fn = nullptr;
    cudaGetDriverEntryPoint("cuTensorMapEncodeTiled", &fn, cudaEnableDefault, &qr);
    enc = (EncodeFn)fn;
    void* ps = nullptr;
    cudaGetSymbolAddress(&ps, g_scratch);
    xbase0 = (uint64_t)ps;
    if ((xbase0 >> 32) != ((xbase0 + xo::BYTES - 1) >> 32)) xbase0 += xo::BYTES;
    cudaFuncSetAttribute(tail_kernel, cudaFuncAttributeMaxDynamicSharedMemorySize, k3::SMEM);
    cudaFuncSetAttribute(chain_kernel, cudaFuncAttributeMaxDynamicSharedMemorySize, chain::SMEM);
    cudaFuncSetAttribute(bpart_kernel, cudaFuncAttributeMaxDynamicSharedMemorySize, bp::SMEM);
    cudaStreamCreateWithFlags(&s1, cudaStreamNonBlocking);
    cudaEventCreateWithFlags(&ev_fork, cudaEventDisableTiming);
    cudaEventCreateWithFlags(&ev_join, cudaEventDisableTiming);
    int dev = 0; cudaGetDevice(&dev);
    cudaDeviceGetAttribute(&nsm, cudaDevAttrMultiProcessorCount, dev);
  }
  uint64_t xbase = xbase0;
  const CUtensorMapSwizzle SW128 = CU_TENSOR_MAP_SWIZZLE_128B, SW64 = CU_TENSOR_MAP_SWIZZLE_64B;
  GemmMaps m3; ChainMaps mc;
  make_map(enc, &m3.o, (void*)(xbase + xo::O), HD, S_LEN, HD, 64, K3_N, SW128);
  make_map(enc, &m3.w, Wo, DM, HD, DM, 64, 64, SW128);
  make_map(enc, &m3.c, out, DM, S_LEN, OUT_LD, 64, K3_N, SW128);
  const CUtensorMapL2promotion P256 = CU_TENSOR_MAP_L2_PROMOTION_L2_256B;
  make_map(enc, &mc.wq, Wq, HD, DM, HD, 64, 128, SW128, P256);
  make_map(enc, &mc.wk, Wk, HD, DM, HD, 64, 128, SW128, P256);
  make_map(enc, &mc.wv, Wv, HD, DM, HD, 64, 128, SW128, P256);
  make_map(enc, &mc.wo, Wo, DM, HD, DM, 32, 256, SW64, P256);
  {
    const uint64_t dx[3] = {64, S_LEN, DM / 64}, sx[3] = {1, DM, 64};
    const uint32_t bx[3] = {64, SEG, 8};
    make_map_nd(enc, &mc.x, x, 3, dx, sx, bx, SW128);
    const uint32_t bq[3] = {64, SEG, 4};
    make_map_nd(enc, &mc.xq, x, 3, dx, sx, bq, SW128);
    mc.xp = (const char*)x;
  }

  const int skip = 0;
  mc.t_step = T_STEP; mc.t_phase = T_PHASE;
  BMaps mb;
  const CUtensorMapSwizzle SWN = CU_TENSOR_MAP_SWIZZLE_NONE;
  make_map(enc, &mb.k, Bk, DM, S_LEN, DM, 8, 256, SWN);
  make_map(enc, &mb.q, Bq, DM, S_LEN, DM, 8, 256, SWN);
  make_map(enc, &mb.v, Bv, DM, S_LEN, DM, 8, 256, SWN);
  mb.shift_k = shift_k; mb.ssm_k = ssm_k; mb.ssm_D = ssm_D;
  make_map(enc, &mb.out, out, OUT_LD, S_LEN, OUT_LD, 8, 256, SWN);
  make_map(enc, &mb.k8, Bk, DM, S_LEN, DM, 8, 8, SWN);
  cudaStream_t s0 = cudaStreamPerThread;
  const int nb = nsm >= 132 ? 4 : 2, ntask1 = bp::NTASK - 2 * k3::NB;
  const bool fork = nsm >= 130 && !(skip & 16);
  if (fork) {
    cudaEventRecord(ev_fork, s0);
    cudaStreamWaitEvent(s1, ev_fork, 0);
    if (!(skip & 1)) bpart_kernel<<<nb, 512, bp::SMEM, s1>>>(mb, ntask1);
    cudaEventRecord(ev_join, s1);
  } else if (!(skip & 1)) {
    bpart_kernel<<<ntask1 / 2, 512, bp::SMEM, s0>>>(mb, ntask1);
  }
  if (!(skip & 4)) chain_kernel<<<128, 256, chain::SMEM, s0>>>(mc, mem0, xbase);
  if (!(skip & 8)) {
    cudaLaunchAttribute pdl[1];
    pdl[0].id = cudaLaunchAttributeProgrammaticStreamSerialization;
    pdl[0].val.programmaticStreamSerializationAllowed = 1;
    cudaLaunchConfig_t cfg = {};
    cfg.gridDim = dim3(128); cfg.blockDim = dim3(512); cfg.dynamicSmemBytes = k3::SMEM; cfg.stream = s0;
    cfg.attrs = pdl; cfg.numAttrs = 1;
    cudaLaunchKernelEx(&cfg, tail_kernel, m3, mb);
  }
  if (fork) cudaStreamWaitEvent(s0, ev_join, 0);
}
```

```cpp
#include <cuda_runtime.h>
#include <cuda_bf16.h>
#include <cuda.h>
#include <stdint.h>

namespace {

constexpr int S_LEN = 2048;
constexpr int DM = 1024;
constexpr int NH = 32;
constexpr int DH = 128;
constexpr int HD = NH * DH;
constexpr int SEG = 32;
constexpr int NSEG = S_LEN / SEG;
constexpr int OUT_LD = 2048;

typedef __nv_bfloat16 bf16;
#define K3_N 160

__device__ __forceinline__ uint32_t smem_u32(const void* p) { return (uint32_t)__cvta_generic_to_shared(p); }

__device__ __forceinline__ void mbar_init(uint32_t bar, uint32_t count) {
  asm volatile("mbarrier.init.shared::cta.b64 [%0], %1;" ::"r"(bar), "r"(count) : "memory");
}
__device__ __forceinline__ void mbar_expect_tx(uint32_t bar, uint32_t bytes) {
  asm volatile("mbarrier.arrive.expect_tx.shared::cta.b64 _, [%0], %1;" ::"r"(bar), "r"(bytes) : "memory");
}
__device__ __forceinline__ void mbar_arrive(uint32_t bar) {
  asm volatile("mbarrier.arrive.shared::cta.b64 _, [%0];" ::"r"(bar) : "memory");
}
__device__ __forceinline__ bool mbar_try(uint32_t bar, uint32_t parity) {
  uint32_t ok;
  asm volatile("{.reg .pred p; mbarrier.try_wait.parity.shared::cta.b64 p, [%1], %2; selp.u32 %0, 1, 0, p;}"
               : "=r"(ok) : "r"(bar), "r"(parity) : "memory");
  return ok;
}
__device__ __forceinline__ bool mbar_test(uint32_t bar, uint32_t parity) {
  uint32_t ok;
  asm volatile("{.reg .pred p; mbarrier.test_wait.parity.shared::cta.b64 p, [%1], %2; selp.u32 %0, 1, 0, p;}"
               : "=r"(ok) : "r"(bar), "r"(parity) : "memory");
  return ok;
}
template <int HINT = 1>
__device__ __forceinline__ void mbar_wait(uint32_t bar, uint32_t parity) {
  int guard = 0;
  while (__builtin_expect(!mbar_try(bar, parity), HINT)) { if (++guard > (1 << 22)) __trap(); }
}
__device__ __forceinline__ void tma_load_2d(uint32_t dst, const CUtensorMap* map, int c0, int c1, uint32_t bar) {
  asm volatile("cp.async.bulk.tensor.2d.shared::cluster.global.mbarrier::complete_tx::bytes [%0], [%1, {%3, %4}], [%2];"
               ::"r"(dst), "l"(map), "r"(bar), "r"(c0), "r"(c1) : "memory");
}
__device__ __forceinline__ void tma_store_2d(const CUtensorMap* map, uint32_t src, int c0, int c1) {
  asm volatile("cp.async.bulk.tensor.2d.global.shared::cta.bulk_group [%0, {%2, %3}], [%1];"
               ::"l"(map), "r"(src), "r"(c0), "r"(c1) : "memory");
}
__device__ __forceinline__ void tma_prefetch_2d(const CUtensorMap* map, int c0, int c1) {
  asm volatile("cp.async.bulk.prefetch.tensor.2d.L2.global [%0, {%1, %2}];" ::"l"(map), "r"(c0), "r"(c1) : "memory");
}
__device__ __forceinline__ void tma_prefetch_desc(const CUtensorMap* map) {
  asm volatile("prefetch.tensormap [%0];" ::"l"(map) : "memory");
}
__device__ __forceinline__ void fence_async_smem() { asm volatile("fence.proxy.async.shared::cta;" ::: "memory"); }
__device__ __forceinline__ void bulk_commit() { asm volatile("cp.async.bulk.commit_group;" ::: "memory"); }
template <int N> __device__ __forceinline__ void bulk_wait_read() { asm volatile("cp.async.bulk.wait_group.read %0;" ::"n"(N) : "memory"); }
template <int N> __device__ __forceinline__ void bulk_wait() { asm volatile("cp.async.bulk.wait_group %0;" ::"n"(N) : "memory"); }
__device__ __forceinline__ void named_bar(int id, int n) { asm volatile("bar.sync %0, %1;" ::"r"(id), "r"(n) : "memory"); }

__device__ __forceinline__ void named_bar_arrive(int id, int n) { asm volatile("bar.arrive %0, %1;" ::"r"(id), "r"(n) : "memory"); }
__device__ __forceinline__ float ex2(float x) { float y; asm("ex2.approx.ftz.f32 %0, %1;" : "=f"(y) : "f"(x)); return y; }
__device__ __forceinline__ float rcp(float x) { float y; asm("rcp.approx.ftz.f32 %0, %1;" : "=f"(y) : "f"(x)); return y; }

__device__ __forceinline__ void sts32(uint32_t a, uint32_t x) { asm volatile("st.shared.b32 [%0], %1;" ::"r"(a), "r"(x) : "memory"); }
__device__ __forceinline__ uint32_t lds32(uint32_t a) { uint32_t x; asm volatile("ld.shared.b32 %0, [%1];" : "=r"(x) : "r"(a) : "memory"); return x; }
__device__ __forceinline__ uint32_t lds32v(uint32_t a) { uint32_t x; asm volatile("ld.volatile.shared.b32 %0, [%1];" : "=r"(x) : "r"(a) : "memory"); return x; }
__device__ __forceinline__ void sts128(uint32_t a, const uint4& v) { asm volatile("st.shared.v4.b32 [%0], {%1,%2,%3,%4};" ::"r"(a), "r"(v.x), "r"(v.y), "r"(v.z), "r"(v.w) : "memory"); }
__device__ __forceinline__ void sts128f(uint32_t a, const float4& v) { asm volatile("st.shared.v4.f32 [%0], {%1,%2,%3,%4};" ::"r"(a), "f"(v.x), "f"(v.y), "f"(v.z), "f"(v.w) : "memory"); }
__device__ __forceinline__ uint4 lds128(uint32_t a) { uint4 v; asm volatile("ld.shared.v4.b32 {%0,%1,%2,%3}, [%4];" : "=r"(v.x), "=r"(v.y), "=r"(v.z), "=r"(v.w) : "r"(a) : "memory"); return v; }
__device__ __forceinline__ float4 lds128f(uint32_t a) { float4 v; asm volatile("ld.shared.v4.f32 {%0,%1,%2,%3}, [%4];" : "=f"(v.x), "=f"(v.y), "=f"(v.z), "=f"(v.w) : "r"(a) : "memory"); return v; }

__device__ __forceinline__ void cp_async16(uint32_t dst, const void* src) { asm volatile("cp.async.cg.shared.global [%0], [%1], 16;" ::"r"(dst), "l"(src) : "memory"); }
__device__ __forceinline__ void cp_async_commit() { asm volatile("cp.async.commit_group;" ::: "memory"); }
template <int N> __device__ __forceinline__ void cp_async_wait_group() { asm volatile("cp.async.wait_group %0;" ::"n"(N) : "memory"); }

__device__ __forceinline__ void wg_fence() { asm volatile("wgmma.fence.sync.aligned;" ::: "memory"); }
__device__ __forceinline__ void wg_commit() { asm volatile("wgmma.commit_group.sync.aligned;" ::: "memory"); }
template <int N> __device__ __forceinline__ void wg_wait() { asm volatile("wgmma.wait_group.sync.aligned %0;" ::"n"(N) : "memory"); }
__device__ __forceinline__ uint64_t make_desc(uint32_t addr, uint32_t lbo, uint32_t sbo, uint32_t swz) {
  return (uint64_t)((addr & 0x3FFFF) >> 4) | ((uint64_t)(lbo >> 4) << 16) | ((uint64_t)(sbo >> 4) << 32) | ((uint64_t)swz << 62);
}

__device__ __forceinline__ void ldsm_x4(uint32_t (&r)[4], uint32_t addr) {
  asm volatile("ldmatrix.sync.aligned.m8n8.x4.shared.b16 {%0,%1,%2,%3}, [%4];"
               : "=r"(r[0]), "=r"(r[1]), "=r"(r[2]), "=r"(r[3]) : "r"(addr) : "memory");
}
__device__ __forceinline__ void ldsm_x4_t(uint32_t (&r)[4], uint32_t addr) {
  asm volatile("ldmatrix.sync.aligned.m8n8.x4.trans.shared.b16 {%0,%1,%2,%3}, [%4];"
               : "=r"(r[0]), "=r"(r[1]), "=r"(r[2]), "=r"(r[3]) : "r"(addr) : "memory");
}
__device__ __forceinline__ void stsm_x4(uint32_t addr, uint32_t r0, uint32_t r1, uint32_t r2, uint32_t r3) {
  asm volatile("stmatrix.sync.aligned.m8n8.x4.shared.b16 [%0], {%1,%2,%3,%4};"
               ::"r"(addr), "r"(r0), "r"(r1), "r"(r2), "r"(r3) : "memory");
}
__device__ __forceinline__ void stsm_x4_t(uint32_t addr, uint32_t r0, uint32_t r1, uint32_t r2, uint32_t r3) {
  asm volatile("stmatrix.sync.aligned.m8n8.x4.trans.shared.b16 [%0], {%1,%2,%3,%4};" ::"r"(addr), "r"(r0), "r"(r1), "r"(r2), "r"(r3) : "memory");
}
__device__ __forceinline__ void mma16816(float (&c)[4], const uint32_t (&a)[4], uint32_t b0, uint32_t b1) {
  asm volatile("mma.sync.aligned.m16n8k16.row.col.f32.bf16.bf16.f32 {%0,%1,%2,%3}, {%4,%5,%6,%7}, {%8,%9}, {%0,%1,%2,%3};"
               : "+f"(c[0]), "+f"(c[1]), "+f"(c[2]), "+f"(c[3])
               : "r"(a[0]), "r"(a[1]), "r"(a[2]), "r"(a[3]), "r"(b0), "r"(b1));
}
__device__ __forceinline__ void mma1688(float (&c)[4], uint32_t a0, uint32_t a1, uint32_t b0) {
  asm volatile("mma.sync.aligned.m16n8k8.row.col.f32.bf16.bf16.f32 {%0,%1,%2,%3}, {%4,%5}, {%6}, {%0,%1,%2,%3};"
               : "+f"(c[0]), "+f"(c[1]), "+f"(c[2]), "+f"(c[3]) : "r"(a0), "r"(a1), "r"(b0));
}
__device__ __forceinline__ uint32_t pack_bf16(float lo, float hi) {
  uint32_t r;
  asm("cvt.rn.bf16x2.f32 %0, %1, %2;" : "=r"(r) : "f"(hi), "f"(lo));
  return r;
}
__device__ __forceinline__ float bf_lo(uint32_t w) { return __uint_as_float(w << 16); }
__device__ __forceinline__ float bf_hi(uint32_t w) { return __uint_as_float(w & 0xFFFF0000u); }

__device__ __forceinline__ uint4 ld_relaxed4(const void* p) {
  uint4 v;
  asm volatile("ld.relaxed.gpu.global.v4.u32 {%0,%1,%2,%3}, [%4];" : "=r"(v.x), "=r"(v.y), "=r"(v.z), "=r"(v.w) : "l"(p) : "memory");
  return v;
}
__device__ __forceinline__ void st_relaxed4(void* p, uint32_t a, uint32_t b, uint32_t c, uint32_t d) {
  asm volatile("st.relaxed.gpu.global.v4.u32 [%0], {%1,%2,%3,%4};" ::"l"(p), "r"(a), "r"(b), "r"(c), "r"(d) : "memory");
}
__device__ __forceinline__ void st_relaxed2(void* p, uint32_t a, uint32_t b) {
  asm volatile("st.relaxed.gpu.global.v2.u32 [%0], {%1,%2};" ::"l"(p), "r"(a), "r"(b) : "memory");
}
__device__ __forceinline__ void st_relaxed1(void* p, uint32_t a) {
  asm volatile("st.relaxed.gpu.global.u32 [%0], %1;" ::"l"(p), "r"(a) : "memory");
}

__device__ __forceinline__ uint2 ld_relaxed2(const void* p) {
  uint2 v;
  asm volatile("ld.relaxed.gpu.global.v2.u32 {%0,%1}, [%2];" : "=r"(v.x), "=r"(v.y) : "l"(p) : "memory");
  return v;
}
__device__ __forceinline__ void sts64(uint32_t a, uint32_t x, uint32_t y) { asm volatile("st.shared.v2.b32 [%0], {%1,%2};" ::"r"(a), "r"(x), "r"(y) : "memory"); }
__device__ __forceinline__ uint2 lds64(uint32_t a) { uint2 v; asm volatile("ld.shared.v2.b32 {%0,%1}, [%2];" : "=r"(v.x), "=r"(v.y) : "r"(a) : "memory"); return v; }
__device__ __forceinline__ void lds128r(uint32_t (&r)[4], uint32_t a) {
  asm volatile("ld.shared.v4.b32 {%0,%1,%2,%3}, [%4];" : "=r"(r[0]), "=r"(r[1]), "=r"(r[2]), "=r"(r[3]) : "r"(a) : "memory");
}
__device__ __forceinline__ uint32_t mapa(uint32_t addr, uint32_t rank) { uint32_t r; asm volatile("mapa.shared::cluster.u32 %0, %1, %2;" : "=r"(r) : "r"(addr), "r"(rank)); return r; }
__device__ __forceinline__ void st_async1(uint32_t dst, uint32_t a, uint32_t bar) {
  asm volatile("st.async.weak.shared::cluster.mbarrier::complete_tx::bytes.b32 [%0], %1, [%2];" ::"r"(dst), "r"(a), "r"(bar) : "memory");
}
__device__ __forceinline__ void st_async4(uint32_t dst, uint32_t a, uint32_t b, uint32_t c, uint32_t d, uint32_t bar) {
  asm volatile("st.async.weak.shared::cluster.mbarrier::complete_tx::bytes.v4.b32 [%0], {%1,%2,%3,%4}, [%5];" ::"r"(dst), "r"(a), "r"(b), "r"(c), "r"(d), "r"(bar) : "memory");
}
__device__ __forceinline__ void cluster_arrive() { asm volatile("barrier.cluster.arrive.relaxed.aligned;" ::: "memory"); }
__device__ __forceinline__ void cluster_wait() { asm volatile("barrier.cluster.wait.acquire.aligned;" ::: "memory"); }

__device__ __forceinline__ void wgmma_k3_ss_ta(float (&d)[80], uint64_t da, uint64_t db, int scale_d) {
  asm volatile("{.reg .pred p; setp.ne.b32 p, %82, 0;\n"
    "wgmma.mma_async.sync.aligned.m64n160k16.f32.bf16.bf16 {%0, %1, %2, %3, %4, %5, %6, %7, %8, %9, %10, %11, %12, %13, %14, %15, %16, %17, %18, %19, %20, %21, %22, %23, %24, %25, %26, %27, %28, %29, %30, %31, %32, %33, %34, %35, %36, %37, %38, %39, %40, %41, %42, %43, %44, %45, %46, %47, %48, %49, %50, %51, %52, %53, %54, %55, %56, %57, %58, %59, %60, %61, %62, %63, %64, %65, %66, %67, %68, %69, %70, %71, %72, %73, %74, %75, %76, %77, %78, %79}, %80, %81, p, 1, 1, 1, 0;}"
    : "+f"(d[0]), "+f"(d[1]), "+f"(d[2]), "+f"(d[3]), "+f"(d[4]), "+f"(d[5]), "+f"(d[6]), "+f"(d[7]), "+f"(d[8]), "+f"(d[9]), "+f"(d[10]), "+f"(d[11]), "+f"(d[12]), "+f"(d[13]), "+f"(d[14]), "+f"(d[15]), "+f"(d[16]), "+f"(d[17]), "+f"(d[18]), "+f"(d[19]), "+f"(d[20]), "+f"(d[21]), "+f"(d[22]), "+f"(d[23]), "+f"(d[24]), "+f"(d[25]), "+f"(d[26]), "+f"(d[27]), "+f"(d[28]), "+f"(d[29]), "+f"(d[30]), "+f"(d[31]), "+f"(d[32]), "+f"(d[33]), "+f"(d[34]), "+f"(d[35]), "+f"(d[36]), "+f"(d[37]), "+f"(d[38]), "+f"(d[39]), "+f"(d[40]), "+f"(d[41]), "+f"(d[42]), "+f"(d[43]), "+f"(d[44]), "+f"(d[45]), "+f"(d[46]), "+f"(d[47]), "+f"(d[48]), "+f"(d[49]), "+f"(d[50]), "+f"(d[51]), "+f"(d[52]), "+f"(d[53]), "+f"(d[54]), "+f"(d[55]), "+f"(d[56]), "+f"(d[57]), "+f"(d[58]), "+f"(d[59]), "+f"(d[60]), "+f"(d[61]), "+f"(d[62]), "+f"(d[63]), "+f"(d[64]), "+f"(d[65]), "+f"(d[66]), "+f"(d[67]), "+f"(d[68]), "+f"(d[69]), "+f"(d[70]), "+f"(d[71]), "+f"(d[72]), "+f"(d[73]), "+f"(d[74]), "+f"(d[75]), "+f"(d[76]), "+f"(d[77]), "+f"(d[78]), "+f"(d[79])
    : "l"(da), "l"(db), "r"(scale_d));
}
__device__ __forceinline__ void wgmma_m64n32_ss_ta(float (&d)[16], uint64_t da, uint64_t db, int scale_d) {
  asm volatile("{.reg .pred p; setp.ne.b32 p, %18, 0;\n"
    "wgmma.mma_async.sync.aligned.m64n32k16.f32.bf16.bf16 {%0, %1, %2, %3, %4, %5, %6, %7, %8, %9, %10, %11, %12, %13, %14, %15}, %16, %17, p, 1, 1, 1, 0;}"
    : "+f"(d[0]), "+f"(d[1]), "+f"(d[2]), "+f"(d[3]), "+f"(d[4]), "+f"(d[5]), "+f"(d[6]), "+f"(d[7]), "+f"(d[8]), "+f"(d[9]), "+f"(d[10]), "+f"(d[11]), "+f"(d[12]), "+f"(d[13]), "+f"(d[14]), "+f"(d[15])
    : "l"(da), "l"(db), "r"(scale_d));
}

__device__ __forceinline__ void wgmma_m64n32_rs(float (&d)[16], const uint32_t (&a)[4], uint64_t db, int scale_d) {
  asm volatile("{.reg .pred p; setp.ne.b32 p, %21, 0;\n"
    "wgmma.mma_async.sync.aligned.m64n32k16.f32.bf16.bf16 {%0, %1, %2, %3, %4, %5, %6, %7, %8, %9, %10, %11, %12, %13, %14, %15}, {%16, %17, %18, %19}, %20, p, 1, 1, 0;}"
    : "+f"(d[0]), "+f"(d[1]), "+f"(d[2]), "+f"(d[3]), "+f"(d[4]), "+f"(d[5]), "+f"(d[6]), "+f"(d[7]), "+f"(d[8]), "+f"(d[9]), "+f"(d[10]), "+f"(d[11]), "+f"(d[12]), "+f"(d[13]), "+f"(d[14]), "+f"(d[15])
    : "r"(a[0]), "r"(a[1]), "r"(a[2]), "r"(a[3]), "l"(db), "r"(scale_d));
}

#define X_POS 5
#define T_STEP 2816
#define T_PHASE 1760
#define RATE0 2295
#define T_LAG 32
#define T_TOL 192
#define T_SLIP 640
#define O_FIX 5
#define NTMP 4
#define V_PRE 6
#define SFENCE(i) asm volatile("{.reg .pred p; setp.eq.u32 p, %0, %1; @p trap;}" ::"r"(n), "r"(4096 + (i)) : "memory")
constexpr int RING = 4;
constexpr uint32_t EMPTY = 0xFFFFFFFFu;
namespace xo {
constexpr uint32_t SLOT = 1u << 20, HEAD = 16384;
constexpr uint32_t VM = 512;
constexpr uint32_t PT = 1024;
constexpr uint32_t PM = 1536;
constexpr uint32_t VT = 8192;
constexpr uint32_t MEM = NH * HEAD;
constexpr uint32_t OM = MEM + 16384;
constexpr uint32_t O = RING * SLOT;
constexpr uint32_t BYTES = O + S_LEN * HD * 2;
}
__device__ __align__(1024) uint4 g_scratch[2 * (xo::BYTES / 16)];
__device__ unsigned g_epoch;
__device__ __align__(16) unsigned g_rate[128];

struct ChainMaps {
  CUtensorMap wq, wk, wv;
  CUtensorMap wo;
  CUtensorMap x, xq;
  const char* xp;
  uint32_t t_step, t_phase;
};

namespace chain {
constexpr int OFF_X = 65536;
constexpr int OFF_MEM = 131072;
constexpr int OFF_WS = 0;
constexpr int OFF_FP = 147456;
constexpr int OFF_KT = 163840;
constexpr int OFF_QT = 180224;
constexpr int OFF_VT = 196608;
constexpr int OFF_PX = 204800;
constexpr int OFF_S4 = OFF_PX + 1536;
constexpr int OFF_QM = 212992;
constexpr int OFF_KM = 215040;
constexpr int OFF_S1 = 217088;
constexpr int OFF_WVR = 0;
constexpr int OFF_WOR = 147456;
constexpr int OFF_RED = 212992;
constexpr int OFF_VPX = 221184;
constexpr int OFF_RX = 223232;
constexpr int OFF_BAR = 229376;
constexpr int BAR_X = OFF_BAR, BAR_TOK = OFF_BAR + 16, BAR_EX = OFF_BAR + 32, BAR_P = OFF_BAR + 40, GRID_TGT = OFF_BAR + 128;
constexpr int CT_BASE = GRID_TGT + 4, CT_HEAD = GRID_TGT + 8, CT_OM = GRID_TGT + 12, CT_MP = GRID_TGT + 16, CT_O = GRID_TGT + 20, CT_PF = GRID_TGT + 24;
constexpr int CT_TT = GRID_TGT + 28, CT_T = GRID_TGT + 32;
constexpr uint32_t RANK_BIT = 1u << 24;
constexpr int SMEM = OFF_BAR + 256;
constexpr uint32_t SB_LO = 1024;
constexpr float SCALE = 0.08838834764831845f, L2E = 1.4426950408889634f;
}

__device__ __forceinline__ uint32_t umax4(uint32_t a, uint32_t b, uint32_t c, uint32_t d) { return max(max(a, b), max(c, d)); }
__device__ __forceinline__ bool warp_incomplete(uint32_t m) { return __any_sync(0xffffffffu, m == EMPTY); }
#define PIN(x) asm volatile("" : "+r"(x))
#define KEEPALIVE(a, z) do { float _d0, _d1, _d2, _d3; asm volatile("mma.sync.aligned.m16n8k16.row.col.f32.bf16.bf16.f32 {%0,%1,%2,%3}, {%4,%5,%6,%7}, {%4,%5}, {%8,%8,%8,%8};" \
    : "=f"(_d0), "=f"(_d1), "=f"(_d2), "=f"(_d3) : "r"(a[0]), "r"(a[1]), "r"(a[2]), "r"(a[3]), "f"(0.f)); \
      \
    asm volatile("{.reg .pred p; setp.ne.u32 p, %0, 0; @p st.shared.f32 [%0], %1;}" ::"r"(z), "f"(_d0 + _d3) : "memory"); } while (0)
constexpr int POLL_LIMIT = 1 << 15;

__device__ __forceinline__ uint32_t keep(uint32_t x) { return __shfl_sync(0xffffffffu, x, threadIdx.x & 31); }
__device__ __forceinline__ char* gptr(uint32_t hi, uint32_t lo) { return (char*)(((uint64_t)hi << 32) | lo); }
__device__ __forceinline__ uint32_t slot_off(int n) { return ((uint32_t)n & (RING - 1)) * xo::SLOT; }
__device__ __forceinline__ float quad_max(float x) {
  const float a = __shfl_xor_sync(~0u, x, 1), b = __shfl_xor_sync(~0u, x, 2), c = __shfl_xor_sync(~0u, x, 3);
  return fmaxf(fmaxf(x, a), fmaxf(b, c));
}
__device__ __forceinline__ void acc_fence(float (&a)[16]) {
#pragma unroll
  for (int i = 0; i < 16; i++) asm volatile("" : "+f"(a[i]) :: "memory");
}
template <int NB = 1, int STRIDE = 0>
__device__ __forceinline__ void gather_issue(uint32_t dst, const char* src) {
#pragma unroll
  for (int b = 0; b < NB; b++)
#pragma unroll
    for (int i = 0; i < 4; i++) cp_async16(dst + b * STRIDE + i * 512, src + b * STRIDE + i * 512);
  cp_async_commit();
}
template <int NB, int STRIDE>
__device__ __forceinline__ bool gather_incomplete(uint32_t chk) {
  uint32_t m = 0;
#pragma unroll
  for (int b = 0; b < NB; b++) m = max(m, umax4(lds32(chk + b * STRIDE), lds32(chk + b * STRIDE + 512), lds32(chk + b * STRIDE + 1024), lds32(chk + b * STRIDE + 1536)));
  return warp_incomplete(m);
}
__device__ __forceinline__ uint32_t ld_relaxed1(const void* p) {
  uint32_t v;
  asm volatile("ld.relaxed.gpu.global.u32 %0, [%1];" : "=r"(v) : "l"(p) : "memory");
  return v;
}
__device__ __forceinline__ uint32_t gtime() { uint64_t g; asm volatile("mov.u64 %0, %%globaltimer;" : "=l"(g) :: "memory"); return (uint32_t)g; }
#define WAIT_UNTIL(t, ka, alive, id) do { \
    int _d = gtime() - (t); \
    if (__builtin_expect(_d > T_TOL, 0)) do { t += T_SLIP; _d -= T_SLIP; } while (_d > T_TOL); \
    if (alive) for (int _k = 64; _d < -96 && --_k; _d = gtime() - (t)) KEEPALIVE(ka, zr); \
    for (uint32_t _g = 0xFFFFFF80u; (int)(_d & ++_g) < 0;) _d = gtime() - (t); } while (0)
__device__ __forceinline__ void issue_x(uint32_t sb, const CUtensorMap* map, int n, int part, int q = 0) {
  asm volatile("{.reg .pred p; elect.sync _|p, 0xffffffff;\n"
               "@p cp.async.bulk.tensor.3d.shared::cluster.global.mbarrier::complete_tx::bytes [%0], [%1, {%3, %4, %5}], [%2];}"
               ::"r"(sb + chain::OFF_X + part * 32768 + q * 16384), "l"(map), "r"(sb + chain::BAR_X + 8 * part), "r"(0), "r"(n * SEG), "r"(part * 8 + q * 4) : "memory");
}
__device__ __forceinline__ void issue_x_if(uint32_t sb, const CUtensorMap* map, int n, int part, uint32_t on) {
  asm volatile("{.reg .pred p, q; elect.sync _|p, 0xffffffff; setp.ne.and.u32 q, %6, 0, p;\n"
               "@q cp.async.bulk.tensor.3d.shared::cluster.global.mbarrier::complete_tx::bytes [%0], [%1, {%3, %4, %5}], [%2];}"
               ::"r"(sb + chain::OFF_X + part * 32768), "l"(map), "r"(sb + chain::BAR_X + 8 * part), "r"(0), "r"(n * SEG), "r"(part * 8), "r"(on) : "memory");
}
__device__ __forceinline__ void prefetch_l2(const char* p, uint32_t bytes) {
  asm volatile("{.reg .pred p; elect.sync _|p, 0xffffffff; @p cp.async.bulk.prefetch.L2.global [%0], %1;}" ::"l"(p), "r"(bytes) : "memory");
}
__device__ __forceinline__ void expect_elect(uint32_t bar, uint32_t bytes) {
  asm volatile("{.reg .pred p; elect.sync _|p, 0xffffffff; @p mbarrier.arrive.expect_tx.shared::cta.b64 _, [%0], %1;}" ::"r"(bar), "r"(bytes) : "memory");
}
template <int WG> __device__ __forceinline__ constexpr uint64_t xdesc(int ks) {
  return (uint64_t)(((chain::SB_LO + chain::OFF_X + WG * 32768 + (ks >> 2) * 4096 + (ks & 3) * 32) >> 4) + (1u << 16)) |
         ((uint64_t)(64u | (1u << 30)) << 32);
}
template <int WG> __device__ __forceinline__ constexpr uint64_t wdesc(int o, int ks) {
  return (uint64_t)(((chain::SB_LO + chain::OFF_WS + WG * 32768 + o * 16384 + ks * 2048) >> 4) + (1u << 16)) | ((uint64_t)(64u | (1u << 30)) << 32);
}
__device__ __forceinline__ void load_mem0(uint2 (&m)[8], const bf16* __restrict__ mem0) {
#pragma unroll
  for (int r = 0; r < 8; r++) m[r] = ld_relaxed2((const uint2*)(mem0 + r * DM) + threadIdx.x);
}
__device__ __forceinline__ void store_mem0(uint32_t sb, const uint2 (&m)[8]) {
  const uint32_t d = sb + chain::OFF_MEM + threadIdx.x * 64;
  sts128(d, make_uint4(__byte_perm(m[0].x, m[1].x, 0x5410), __byte_perm(m[2].x, m[3].x, 0x5410), __byte_perm(m[4].x, m[5].x, 0x5410), __byte_perm(m[6].x, m[7].x, 0x5410)));
  sts128(d + 16, make_uint4(__byte_perm(m[0].x, m[1].x, 0x7632), __byte_perm(m[2].x, m[3].x, 0x7632), __byte_perm(m[4].x, m[5].x, 0x7632), __byte_perm(m[6].x, m[7].x, 0x7632)));
  sts128(d + 32, make_uint4(__byte_perm(m[0].y, m[1].y, 0x5410), __byte_perm(m[2].y, m[3].y, 0x5410), __byte_perm(m[4].y, m[5].y, 0x5410), __byte_perm(m[6].y, m[7].y, 0x5410)));
  sts128(d + 48, make_uint4(__byte_perm(m[0].y, m[1].y, 0x7632), __byte_perm(m[2].y, m[3].y, 0x7632), __byte_perm(m[4].y, m[5].y, 0x7632), __byte_perm(m[6].y, m[7].y, 0x7632)));
}
template <int K> __device__ __forceinline__ uint32_t loop_zero(int n) { uint32_t z; asm volatile("shr.u32 %0, %1, %2;" : "=r"(z) : "r"(n), "n"(16 + K)); return z; }
#define NEWZ(k) zr = loop_zero<k>(n)

template <int WG>
__device__ __forceinline__ void role_a(const ChainMaps& maps, const bf16* __restrict__ mem0, const uint32_t sb, const uint32_t xbase_hi) {
  using namespace chain;
  const int h = blockIdx.x >> 2;
  const bool J = sb >= RANK_BIT;
  const uint32_t u16 = (threadIdx.x & 96) * 64 + (threadIdx.x & 31) * 16;
  const uint32_t t16 = keep(u16), l16 = keep((threadIdx.x & 31) * 16);
  const uint32_t a_wl = keep((((threadIdx.x >> 4) & 1) * 8 + (threadIdx.x & 7)) * 128 + (((((threadIdx.x >> 4) & 6) + ((threadIdx.x >> 3) & 1)) ^ (threadIdx.x & 7)) << 4));
  const uint32_t xhi = keep(xbase_hi + (t16 >> 16));
#define xh (lds32(sb + CT_HEAD) + t16)
#define xm (lds32(sb + CT_BASE) + t16 + xo::MEM)
#define last_warp __any_sync(0xffffffffu, tv >= 6144)
#define tv (t16 ^ zr)
  const CUtensorMap* wm = J ? &maps.wk : &maps.wq;

  uint32_t aW[2][24][4];
  uint2 m0[8];
  load_mem0(m0, mem0);
  mbar_wait(sb + BAR_P, 0);
#pragma unroll
  for (int ks = 0; ks < 24; ks++) ldsm_x4_t(aW[0][ks], sb + a_wl + OFF_X + WG * 49152 + ks * 2048);
  named_bar(0, 256);
  if (WG == 1 && __any_sync(0xffffffffu, t16 >= 6144)) {
    fence_async_smem();
    if (l16 == 0) {
      mbar_expect_tx(sb + BAR_P + 16, 2 * 16384);
      for (int q = 0; q < 2; q++) tma_load_2d(sb + OFF_X + (4 + q) * 16384, wm, h * DH + (q ^ 1) * 64, q * 512 + 256, sb + BAR_P + 16);
    }
    __syncwarp();
    expect_elect(sb + BAR_X, 32768); expect_elect(sb + BAR_X + 8, 32768); expect_elect(sb + BAR_TOK, 8192);
    issue_x(sb, &maps.x, 0, 0); issue_x(sb, &maps.x, 0, 1);
  }
  mbar_wait(sb + BAR_P + 8, 0);
#pragma unroll
  for (int ks = 0; ks < 16; ks++) ldsm_x4_t(aW[1][ks], sb + a_wl + OFF_X + 6 * 16384 + WG * 32768 + ks * 2048);
  mbar_wait(sb + BAR_P + 16, 0);
#pragma unroll
  for (int ks = 0; ks < 8; ks++) ldsm_x4_t(aW[1][16 + ks], sb + a_wl + OFF_X + (4 + WG) * 16384 + ks * 2048);
  named_bar(0, 256);
  cluster_arrive();
  store_mem0(sb, m0);
  mbar_wait(sb + BAR_P + 24, 0);
  cluster_wait();
  const uint32_t rsb = sb ^ RANK_BIT;
  const uint32_t a_ws = sb + a_wl + OFF_WS + WG * 32768;

  uint32_t ws[2][4][4];
  auto load_ws = [&]() {
#pragma unroll
    for (int q = 0; q < 2; q++) {
      const uint32_t a = a_ws + q * 4096;
      ldsm_x4_t(ws[q][0], a); ldsm_x4_t(ws[q][1], a + 16384); ldsm_x4_t(ws[q][2], a + 2048); ldsm_x4_t(ws[q][3], a + 16384 + 2048);
    }
  };
  uint32_t tref = 0;
#pragma unroll 1
  for (int n = 0; n <= (J ? NSEG : NSEG - 1); n++) {
#define s (n - 1)
#define sv ((int)(n ^ zr) - 1)
    const bool more = __builtin_expect(s + 1 < NSEG, 1);
    uint32_t zr = loop_zero<0>(n);
#define wq ((int)(tv >> 11))
#define lv (l16 ^ zr)
#define gh (xh + slot_off(sv))
    uint32_t tmp[NTMP][4];
    auto load_tmp = [&](int o) {
#pragma unroll
      for (int ks = 0; ks < NTMP; ks++) ldsm_x4_t(tmp[ks], a_ws + o * 16384 + ks * 2048);
    };
    auto wait_x = [&]() { mbar_wait<0>(sb + BAR_X + 8 * WG, n & 1); };
    if (__builtin_expect(s < 0, 0)) { load_tmp(1); wait_x(); }
    else {
      {
        if (WG == 1) { if (__builtin_expect(s > 0, 1)) {
          const uint32_t dst = sb + OFF_MEM + tv + t16 - l16, chk = dst + ((lv >> 5) & 12);
          uint32_t tries = zr;
#pragma unroll 1
          do {
            if (tries) {
              const char* src = gptr(xhi, xm + t16 - l16 + slot_off(sv));
              tref += T_SLIP;
              WAIT_UNTIL(tref, aW[0][0], 1, -1);
              gather_issue<2, 2048>(dst, src);
            }
            KEEPALIVE(aW[0][0], zr);
            cp_async_wait_group<0>();
          } while (gather_incomplete<2, 2048>(chk) && ++tries < POLL_LIMIT);
        } } else if (J == 0) {
          uint32_t tries = s == 0;
#pragma unroll 1
          do {
            if (tries) gather_issue(sb + OFF_VT + tv, gptr(xhi, gh) + xo::VT);
            cp_async_wait_group<0>();
          } while (gather_incomplete<1, 0>(sb + OFF_VT + t16 + ((lv >> 5) & 12)) && ++tries < POLL_LIMIT);
        }
        named_bar(1, 256);
      }
      float c[2][2][4];
#pragma unroll
      for (int i = 0; i < 4; i++) c[i >> 1][i & 1][0] = c[i >> 1][i & 1][1] = c[i >> 1][i & 1][2] = c[i >> 1][i & 1][3] = 0.f;
      {
        const uint32_t a_mem = sb + OFF_MEM + WG * 8192 + l16;
        uint32_t b[4][4];
        bool tok;
        constexpr int PR[16] = {12, 13, 0, 1, 2, 3, 4, 14, 5, 6, 7, 8, 9, 15, 10, 11};
        ldsm_x4_t(b[0], a_mem + PR[0] * 512); ldsm_x4_t(b[1], a_mem + PR[1] * 512);
#pragma unroll
        for (int i = 0; i < 16; i++) {
          if ((i & 1) == 0 && i < 14) {
            ldsm_x4_t(b[(i + 2) & 3], a_mem + PR[i + 2] * 512); ldsm_x4_t(b[(i + 3) & 3], a_mem + PR[i + 3] * 512);
            if (i == 2 || i == 8) { ldsm_x4_t(ws[1][0], a_ws + (i == 2 ? 2 : 3) * 4096); ldsm_x4_t(ws[1][1], a_ws + (i == 2 ? 2 : 3) * 4096 + 16384); }
            if (i == 4 || i == 10) { ldsm_x4_t(ws[1][2], a_ws + (i == 4 ? 2 : 3) * 4096 + 2048); ldsm_x4_t(ws[1][3], a_ws + (i == 4 ? 2 : 3) * 4096 + 16384 + 2048); }
          }
          const int p = PR[i];
          if (p >= 12) {
            const int z = i != 0;
            mma16816(c[0][0], ws[z][0], b[i & 3][0], b[i & 3][1]); mma16816(c[1][0], ws[z][1], b[i & 3][0], b[i & 3][1]);
            mma16816(c[0][1], ws[z][2], b[i & 3][2], b[i & 3][3]); mma16816(c[1][1], ws[z][3], b[i & 3][2], b[i & 3][3]);
          } else {
            mma16816(c[1][0], aW[1][2 * p], b[i & 3][0], b[i & 3][1]); mma16816(c[1][1], aW[1][2 * p + 1], b[i & 3][2], b[i & 3][3]);
            mma16816(c[0][0], aW[0][2 * p], b[i & 3][0], b[i & 3][1]); mma16816(c[0][1], aW[0][2 * p + 1], b[i & 3][2], b[i & 3][3]);
          }
          if (i == 12) tok = mbar_test(sb + BAR_TOK + 8 * (s & 1), (s >> 1) & 1);
          if (i == 15 && __builtin_expect(!tok, 0)) mbar_wait(sb + BAR_TOK + 8 * (s & 1), (s >> 1) & 1);
          if (i == X_POS + 4 * (1 - WG)) { issue_x_if(sb, &maps.x, s + 1, WG, t16 >= 6144 && more); if (WG) __syncwarp(); }
        }
      }
      sts128f(sb + OFF_PX + WG * 512 + t16, make_float4(c[1][0][0] + c[1][1][0], c[1][0][1] + c[1][1][1], c[1][0][2] + c[1][1][2], c[1][0][3] + c[1][1][3]));
      const float4 own = make_float4(c[0][0][0] + c[0][1][0], c[0][0][1] + c[0][1][1], c[0][0][2] + c[0][1][2], c[0][0][3] + c[0][1][3]);
      NEWZ(1);
      uint32_t a = (J ? OFF_KM : OFF_QM) + WG * 1024 + wq * 256 + (lv >> 2);
      uint32_t ra = rsb + a, ra2 = ra + 128, rx = rsb + BAR_EX + zr;
      PIN(a); PIN(ra); PIN(ra2); PIN(rx);
      const uint32_t kt = sb + OFF_KT + (s & 1) * 8192;
#define k_lane ((lv & 240) + ((lv & 256) << 2))
#define a_lane (((lv & 128) << 1) + ((lv & 256) >> 1) + (lv & 112))
      uint32_t kb[4][4], aq = sb + OFF_QM + a_lane;
      PIN(aq);
      SFENCE(16);
      named_bar(3, 256);
      {
        const float4 o = lds128f(sb + OFF_PX + (WG ^ 1) * 512 + t16);
        const uint32_t lo = pack_bf16(own.x + o.x, own.y + o.y), hi = pack_bf16(own.z + o.z, own.w + o.w);
        if (J == 1 && more) { st_async1(ra, lo, rx); st_async1(ra2, hi, rx); }
        sts32(sb + a, lo); sts32(sb + a + 128, hi);
      }
      if (J == 0) {
        uint32_t am[4][4];
        uint2 vm0, vm1;
        const char* pvm = WG == 0 ? gptr(xhi, gh - (lv >> 1)) + xo::VM : nullptr;
        if (WG == 1) {
#pragma unroll
          for (int p = 0; p < 4; p++) ldsm_x4(kb[p], kt + wq * 256 + k_lane + p * 2048);
        }
        named_bar(7, 256);
#pragma unroll
        for (int p = 0; p < 4; p++) ldsm_x4_t(am[p], aq + p * 512);
        auto scores = [&]() {
          float c0[2][4], c1[2][4];
#pragma unroll
          for (int i = 0; i < 2; i++) { c0[i][0] = c0[i][1] = c0[i][2] = c0[i][3] = 0.f; c1[i][0] = c1[i][1] = c1[i][2] = c1[i][3] = 0.f; }
#pragma unroll
          for (int p = 0; p < 4; p++) { mma16816(c0[p & 1], am[p], kb[p][0], kb[p][1]); mma16816(c1[p & 1], am[p], kb[p][2], kb[p][3]); }
          const uint32_t r1 = pack_bf16((c0[0][0] + c0[1][0]) + (c1[0][2] + c1[1][2]), (c0[0][1] + c0[1][1]) + (c1[0][3] + c1[1][3]));
          return pack_bf16(bf_lo(r1) * SCALE, bf_hi(r1) * SCALE);
        };
        if (WG == 1) {
          const uint32_t st = scores();
          uint32_t vb[4][4];
          sts32(sb + OFF_S4 + l16 + wq * 4, st);
          named_bar(8, 128);
          const uint4 sc = lds128(sb + OFF_S4 + l16);
          float x[8] = {bf_lo(sc.x), bf_hi(sc.x), bf_lo(sc.y), bf_hi(sc.y), bf_lo(sc.z), bf_hi(sc.z), bf_lo(sc.w), bf_hi(sc.w)};
          float mx = fmaxf(fmaxf(fmaxf(x[0], x[1]), fmaxf(x[2], x[3])), fmaxf(fmaxf(x[4], x[5]), fmaxf(x[6], x[7])));
          {
            const uint32_t va = sb + OFF_VT + t16 + (sc.x & zr);
#pragma unroll
            for (int e = 0; e < 4; e++) lds128r(vb[e], va + e * 512);
          }
          mx = quad_max(mx);
          const float mb = mx * L2E;
#pragma unroll
          for (int i = 0; i < 8; i++) x[i] = ex2(fmaf(x[i], L2E, -mb));
          uint32_t pa[4], pb[4];
          asm volatile("" : "=r"(pa[1]), "=r"(pa[3]), "=r"(pb[1]), "=r"(pb[3]));
          pa[0] = pack_bf16(x[0], x[1]); pa[2] = pack_bf16(x[2], x[3]);
          pb[0] = pack_bf16(x[4], x[5]); pb[2] = pack_bf16(x[6], x[7]);
          float oa[4][4];
#pragma unroll
          for (int e = 0; e < 4; e++) { oa[e][0] = oa[e][1] = oa[e][2] = oa[e][3] = 0.f; mma16816(oa[e], pa, vb[e][0], vb[e][1]); }
#pragma unroll
          for (int e = 0; e < 4; e++) mma16816(oa[e], pb, vb[e][2], vb[e][3]);
          sts64(sb + OFF_PX + 1024 + t16, __float_as_uint(mx), __float_as_uint(((x[0] + x[1]) + (x[2] + x[3])) + ((x[4] + x[5]) + (x[6] + x[7]))));
          sts128f(sb + OFF_PX + t16, make_float4(oa[0][0], oa[0][1], oa[1][0], oa[1][1]));
          sts128f(sb + OFF_PX + 512 + t16, make_float4(oa[2][0], oa[2][1], oa[3][0], oa[3][1]));
          named_bar_arrive(9, 256);
          wait_x();
          load_tmp(1);
        } else {
          const uint32_t xo0 = lds32(sb + CT_OM) + wq * 512 + l16;
          mbar_wait<0>(sb + BAR_EX, s & 1);
          vm0 = ld_relaxed2(pvm); vm1 = ld_relaxed2(pvm + 256);
#pragma unroll
          for (int p = 0; p < 4; p++) ldsm_x4_t(kb[p], sb + OFF_KM + p * 512 + l16);
          const uint32_t sm = scores();
          float mx = quad_max(fmaxf(bf_lo(sm), bf_hi(sm)));
          auto check_vm = [&]() {
            if (__builtin_expect(warp_incomplete(max(vm0.x, vm1.x)), 0)) {
              uint32_t tries = zr;
#pragma unroll 1
              do { vm0 = ld_relaxed2(pvm); vm1 = ld_relaxed2(pvm + 256); } while (warp_incomplete(max(vm0.x, vm1.x)) && ++tries < POLL_LIMIT);
            }
          };
          SFENCE(25);
          named_bar(9, 256);
          const uint2 ms = lds64(sb + OFF_PX + 1024 + t16);
          const float4 t0 = lds128f(sb + OFF_PX + t16), t1 = lds128f(sb + OFF_PX + 512 + t16);
          mx = fmaxf(mx, __uint_as_float(ms.x));
          const float mb = mx * L2E;
          const float e0 = ex2(fmaf(bf_lo(sm), L2E, -mb)), e1 = ex2(fmaf(bf_hi(sm), L2E, -mb)), ct = ex2(fmaf(__uint_as_float(ms.x), L2E, -mb));
          uint32_t p4 = pack_bf16(e0, e1), p5;
          asm volatile("" : "=r"(p5));
          float sx = fmaf(ct, __uint_as_float(ms.y), e0 + e1);
          float oa[4][4] = {{t0.x * ct, t0.y * ct, 0.f, 0.f}, {t0.z * ct, t0.w * ct, 0.f, 0.f}, {t1.x * ct, t1.y * ct, 0.f, 0.f}, {t1.z * ct, t1.w * ct, 0.f, 0.f}};
          const float s1 = __shfl_xor_sync(~0u, sx, 1), s2 = __shfl_xor_sync(~0u, sx, 2), s3 = __shfl_xor_sync(~0u, sx, 3);
          check_vm();
          mma1688(oa[0], p4, p5, vm0.x); mma1688(oa[1], p4, p5, vm0.y); mma1688(oa[2], p4, p5, vm1.x); mma1688(oa[3], p4, p5, vm1.y);
          const float rx = rcp((sx + s1) + (s2 + s3));
          st_relaxed4(gptr(xhi, xo0 + slot_off(sv)), pack_bf16(oa[0][0] * rx, oa[0][1] * rx), pack_bf16(oa[1][0] * rx, oa[1][1] * rx),
                      pack_bf16(oa[2][0] * rx, oa[2][1] * rx), pack_bf16(oa[3][0] * rx, oa[3][1] * rx));
          SFENCE(24);
          named_bar_arrive(10, 256);
          st_relaxed4(gptr(xhi, xo0 + slot_off(sv + 3)), EMPTY, EMPTY, EMPTY, EMPTY);
          load_tmp(1);
          wait_x();
        }
      } else {
        bool xok;
        {
          const int mt = WG | (wq == 3), ktile = wq == 3 ? 2 + WG : wq - 1;
          const uint32_t qt = sb + OFF_QT + (s & 1) * 8192 + mt * 512 + a_lane;
          uint32_t q[8][4];
          if (__any_sync(0xffffffffu, tv < 2048)) {
            named_bar(7, 256);
#pragma unroll
            for (int p = 0; p < 4; p++) ldsm_x4_t(kb[p], sb + OFF_KM + p * 512 + l16);
          } else {
            named_bar_arrive(7, 256);
#pragma unroll
            for (int p = 0; p < 4; p++) ldsm_x4(kb[p], kt + ktile * 256 + k_lane + p * 2048);
          }
#pragma unroll
          for (int i = 0; i < 8; i++) ldsm_x4(q[i], qt + i * 1024);
          __syncwarp();
          float c0[4][4];
#pragma unroll
          for (int i = 0; i < 4; i++) { c0[i][0] = c0[i][1] = c0[i][2] = c0[i][3] = 0.f; mma16816(c0[i], q[i], kb[i >> 1][(i & 1) * 2], kb[i >> 1][(i & 1) * 2 + 1]); }
#pragma unroll
          for (int i = 0; i < 4; i++) mma16816(c0[i], q[4 + i], kb[2 + (i >> 1)][(i & 1) * 2], kb[2 + (i >> 1)][(i & 1) * 2 + 1]);
          load_tmp(1);
          xok = mbar_test(sb + BAR_X + 8 * WG, n & 1);
          NEWZ(3);
          const uint32_t r0 = pack_bf16((c0[0][0] + c0[1][0]) + (c0[2][0] + c0[3][0]), (c0[0][1] + c0[1][1]) + (c0[2][1] + c0[3][1]));
          const uint32_t r1 = pack_bf16((c0[0][2] + c0[1][2]) + (c0[2][2] + c0[3][2]), (c0[0][3] + c0[1][3]) + (c0[2][3] + c0[3][3]));
          const uint32_t sa = wq == 0 ? sb + OFF_S1 + (lv >> 2) + mt * 256 : sb + OFF_S4 + l16 + mt * 4096 + ktile * 4;
          sts32(sa, pack_bf16(bf_lo(r0) * SCALE, bf_hi(r0) * SCALE));
          sts32(sa + (wq == 0 ? 128 : 2048), pack_bf16(bf_lo(r1) * SCALE, bf_hi(r1) * SCALE));
        }
        if (WG == 1) named_bar_arrive(8, 256);
        else {
          if (more) named_bar_arrive(10, 256);
          const uint32_t gp = gh;
          named_bar(8, 256);
          const uint4 sc = lds128(sb + OFF_S4 + t16); const uint32_t s1 = lds32(sb + OFF_S1 + wq * 128 + (lv >> 2));
          float y[10] = {bf_lo(s1), bf_hi(s1), bf_lo(sc.x), bf_hi(sc.x), bf_lo(sc.y), bf_hi(sc.y), bf_lo(sc.z), bf_hi(sc.z), bf_lo(sc.w), bf_hi(sc.w)};
          const int rel = wq * 8 + (int)(lv >> 6) - (int)((lv >> 3) & 6);
          const float NEG = -999292928.f;
#pragma unroll
          for (int e = 0; e < 4; e++) {
            if (e * 8 > rel) y[2 * e + 2] = NEG;
            if (e * 8 + 1 > rel) y[2 * e + 3] = NEG;
          }
          float my = fmaxf(fmaxf(fmaxf(y[0], y[1]), fmaxf(y[2], y[3])), fmaxf(fmaxf(y[4], y[5]), fmaxf(y[6], y[7])));
          my = quad_max(fmaxf(my, fmaxf(y[8], y[9])));
#pragma unroll
          for (int i = 0; i < 10; i++) y[i] = ex2((y[i] - my) * L2E);
          float sy = ((y[0] + y[1]) + (y[2] + y[3])) + ((y[4] + y[5]) + (y[6] + y[7])) + (y[8] + y[9]);
          const float ry = rcp((sy + __shfl_xor_sync(~0u, sy, 1)) + (__shfl_xor_sync(~0u, sy, 2) + __shfl_xor_sync(~0u, sy, 3)));
          st_relaxed4(gptr(xhi, gp) + xo::PT, pack_bf16(y[2] * ry, y[3] * ry), pack_bf16(y[4] * ry, y[5] * ry), pack_bf16(y[6] * ry, y[7] * ry), pack_bf16(y[8] * ry, y[9] * ry));
          const uint32_t l12 = lv - (lv >> 2);
          st_relaxed1(gptr(xhi, gp - l12) + xo::PM, pack_bf16(y[0] * ry, y[1] * ry));
        }
        if (!xok && more) wait_x();
      }
    }
    if (more) {
      float acc[16];
      const uint32_t xph = (s + 1) & 1;
      auto batch = [&](const uint32_t (&a)[24][4], int o) {
        wg_fence();
#pragma unroll
        for (int ks = NTMP; ks < 8; ks++) wgmma_m64n32_ss_ta(acc, wdesc<WG>(o, ks), xdesc<WG>(24 + ks), ks != NTMP);
#pragma unroll
        for (int ks = 0; ks < NTMP; ks++) wgmma_m64n32_rs(acc, tmp[ks], xdesc<WG>(24 + ks), 1);
#pragma unroll
        for (int ks = 0; ks < 24; ks++) wgmma_m64n32_rs(acc, a[ks], xdesc<WG>(ks), 1);
        wg_commit();
        SFENCE(50 + o);
      };
      if (WG == 0) named_bar(12, 256);
      else if (__builtin_expect(s >= 0, 1)) named_bar(10, 256);
      batch(aW[1], 1);
      named_bar_arrive(WG ? 12 : 13, 256);
      wg_wait<0>();
      acc_fence(acc);
      load_tmp(0);
#pragma unroll
      for (int i = 0; i < 4; i++) sts128f(sb + OFF_FP + WG * 8192 + t16 + i * 512, make_float4(acc[4 * i], acc[4 * i + 1], acc[4 * i + 2], acc[4 * i + 3]));
      NEWZ(4);
      if (WG == 0 && s >= 0) {
        const uint32_t g1 = xh + slot_off(sv + 1);
        if (J == 0) gather_issue(sb + OFF_VT + tv, gptr(xhi, g1) + xo::VT);
        else {
          st_relaxed4(gptr(xhi, g1) + xo::PT, EMPTY, EMPTY, EMPTY, EMPTY);
          st_relaxed1(gptr(xhi, g1 - lv + (lv >> 2)) + xo::PM, EMPTY);
        }
      }
      uint32_t esrc = 0;
      if (WG == 1) { esrc = xm + t16 - l16 + 2048 + slot_off(sv + 1); tref += lds32(sb + CT_T); }
      named_bar(WG ? 13 : 14, 256);
      batch(aW[0], 0);
      NEWZ(5);
      if (WG == 1) {
        named_bar(14, 256);
        if (last_warp && s + 2 < NSEG) {
          expect_elect(sb + BAR_TOK + 8 * (xph ^ 1), 8192); expect_elect(sb + BAR_X, 32768); expect_elect(sb + BAR_X + 8, 32768);
          if (J == 0) expect_elect(sb + BAR_EX, 2048);
          if (s == NSEG - 3) asm volatile("griddepcontrol.launch_dependents;");
        }
      }
      const uint32_t tb = lds32(sb + CT_TT) + xph * 8192 + WG * 4096 + ((tv + l16) >> 1);
      float4 oth[4];
#pragma unroll
      for (int i = 0; i < 4; i++) oth[i] = lds128f(sb + OFF_FP + (WG ^ 1) * 8192 + t16 + i * 512);
      if (WG == 1 && __builtin_expect(s >= 0, 1)) {
        const uint32_t edst = sb + OFF_MEM + tv + t16 - l16;
        WAIT_UNTIL(tref, aW[0][0], 0, J ? 7 : 0);
        gather_issue<2, 2048>(edst, gptr(xhi, esrc) - 2048);
      }
      wg_wait<0>();
      acc_fence(acc);
      uint32_t lt[4], ht[4];
#pragma unroll
      for (int i = 0; i < 4; i++) {
        const float4 o = oth[i];
        lt[i] = pack_bf16(acc[4 * i] + o.x, acc[4 * i + 1] + o.y); ht[i] = pack_bf16(acc[4 * i + 2] + o.z, acc[4 * i + 3] + o.w);
      }
      stsm_x4_t(tb, lt[0], ht[0], lt[1], ht[1]); stsm_x4_t(tb + 512, lt[2], ht[2], lt[3], ht[3]);
      NEWZ(6);
      if (WG == 0 && last_warp) {
        load_ws();
        named_bar(11, 256);
        fence_async_smem();
        const uint32_t tt = (J ? OFF_KT : OFF_QT) + xph * 8192;
        asm volatile("{.reg .pred p; elect.sync _|p, 0xffffffff;\n"
                     "@p cp.async.bulk.shared::cluster.shared::cta.mbarrier::complete_tx::bytes [%0], [%1], 8192, [%2];}"
                     ::"r"(rsb + tt), "r"(sb + tt), "r"(rsb + BAR_TOK + 8 * xph) : "memory");
      } else {
        named_bar_arrive(11, 256);
        load_ws();
      }
    }
    if (!more) break;
    if (__builtin_expect(s < 0, 0)) {
      tref = gtime() / T_SLIP * T_SLIP - T_SLIP;
    }
  }
  cp_async_wait_group<0>();
  if (J == 0) mbar_wait(sb + BAR_TOK + 8, 1);
}

template <int WG>
__device__ __forceinline__ void role_v(const ChainMaps& maps, const bf16* __restrict__ mem0, const uint32_t sb, const uint32_t xbase_hi) {
  using namespace chain;
  const int h = blockIdx.x >> 2;
  const uint32_t u16 = (threadIdx.x & 96) * 64 + (threadIdx.x & 31) * 16;
  const uint32_t t16 = keep(u16), l16 = keep((threadIdx.x & 31) * 16);
  const uint32_t xhi = keep(xbase_hi + (t16 >> 16));
#define j (sb >> 24)
  auto wv_addr = [&](uint32_t t) { return WG * 32768 + ((t & 256) << 2) + ((t & 112) << 3) + ((((t >> 6) & 96) + ((t >> 3) & 16)) ^ (t & 112)); };
  auto wo_addr = [&](uint32_t t) { return OFF_WOR + WG * 32768 + ((t & 6144) << 2) + ((t & 256) << 1) + ((t & 112) << 2) + ((((j ^ 1) << 5) + ((t >> 3) & 16)) ^ ((t >> 1) & 48)); };
#define ovt (((tv + l16) >> 1) + (xo::VT + WG * 512 + j * 4096))
#define ovm (((tv & 4096) >> 1) + ((tv & 2048) >> 3) + (lv >> 1) + (xo::VM + j * 4096))
#define xvt (lds32(sb + CT_HEAD) + ovt)
#define xvm (lds32(sb + CT_HEAD) + ovm)
#define xom (lds32(sb + CT_OM) + t16 + WG * 8192)
#define warp_is(q) __any_sync(0xffffffffu, (tv >> 11) == (q))
#define upper_warps (WG == 1 || __any_sync(0xffffffffu, tv >= 4096))

  uint32_t aV[16][4];
  uint32_t aO[16][4];
  uint32_t bO[16][4];
  uint32_t rot[16][4];
  if (WG == 1 && __any_sync(0xffffffffu, t16 >= 6144)) {
    expect_elect(sb + BAR_X, 32768); expect_elect(sb + BAR_X + 8, 32768);
    issue_x(sb, &maps.x, 0, 0); issue_x(sb, &maps.x, 0, 1);
    prefetch_l2(maps.xp + 65536 + (h * 2 + j) * 3072, 3072);
  }
  cluster_arrive();
  { uint2 m0[8]; load_mem0(m0, mem0); store_mem0(sb, m0); }
  mbar_wait(sb + BAR_P, 0);
#pragma unroll
  for (int ks = 0; ks < 16; ks++) ldsm_x4_t(aV[ks], sb + wv_addr(t16) + OFF_WOR + ks * 2048);
  auto load_v = [&](uint32_t t) {
#pragma unroll
    for (int ks = 0; ks < 16; ks++) ldsm_x4_t(rot[ks], sb + wv_addr(t) + OFF_WVR + ks * 2048);
  };
  load_v(t16);
  named_bar(0, 256);
  if (threadIdx.x == 0) {
    fence_async_smem();
    mbar_expect_tx(sb + BAR_P + 8, 4 * 16384);
    for (int q = 0; q < 4; q++) tma_load_2d(sb + OFF_WOR + q * 16384, &maps.wo, h * 32, j * 2048 + q * 256, sb + BAR_P + 8);
    for (int q = 0; q < 4; q++) tma_prefetch_2d(&maps.wo, h * 32, j * 2048 + 1024 + q * 256);
  }
  __syncwarp();
  cluster_wait();
  const uint32_t rsb = sb ^ RANK_BIT;

  uint32_t tref = 0;
#pragma unroll 1
  for (int n = 0; n <= NSEG; n++) {
    const bool more = __builtin_expect(s + 1 < NSEG, 1);
    uint32_t zr = loop_zero<0>(n);
    bool xok = false;
    if (__builtin_expect(s >= 0, 1)) {
      if (__builtin_expect(s > 0, 1)) {
        const uint32_t dst = sb + OFF_MEM + WG * 8192 + t16 + ((lv >> 5) & 12);
        uint32_t tries = zr;
#pragma unroll 1
        do {
          if (tries) { const char* src = gptr(xhi, xm + WG * 8192 + slot_off(sv)); tref += T_SLIP; WAIT_UNTIL(tref, aV[0], 1, -1); gather_issue(sb + OFF_MEM + WG * 8192 + tv, src); }
          KEEPALIVE(aV[0], zr);
          cp_async_wait_group<0>();
        } while (gather_incomplete<1, 0>(dst) && ++tries < POLL_LIMIT);
        named_bar(1 + WG, 128);
      }
      const uint32_t a_mem = sb + OFF_MEM + WG * 8192 + l16;
      float c[2][4];
      c[0][0] = c[0][1] = c[0][2] = c[0][3] = c[1][0] = c[1][1] = c[1][2] = c[1][3] = 0.f;
      constexpr int NBUF = (48 - 8 - 4 * O_FIX) / 4;
      uint32_t b[NBUF][4];
#pragma unroll
      for (int p = 0; p < NBUF - 1; p++) ldsm_x4_t(b[p], a_mem + p * 512);
#pragma unroll
      for (int p = 0; p < 16; p++) {
        if (p + NBUF - 1 < 16) ldsm_x4_t(b[(p + NBUF - 1) % NBUF], a_mem + (p + NBUF - 1) * 512);
        if (p < 8) { mma16816(c[0], aV[2 * p], b[p % NBUF][0], b[p % NBUF][1]); mma16816(c[1], aV[2 * p + 1], b[p % NBUF][2], b[p % NBUF][3]); }
        else { mma16816(c[0], rot[2 * p - 16], b[p % NBUF][0], b[p % NBUF][1]); mma16816(c[1], rot[2 * p - 15], b[p % NBUF][2], b[p % NBUF][3]); }
      }
      xok = mbar_test(sb + BAR_X + 8 * WG, n & 1);
      SFENCE(15);
      const float4 own = make_float4(c[0][0] + c[1][0], c[0][1] + c[1][1], c[0][2] + c[1][2], c[0][3] + c[1][3]);
      NEWZ(1);
      const uint32_t pvm = WG == 0 ? xvm + slot_off(sv) : 0;
      if (WG == 1) sts128f(sb + OFF_VPX + wq * 512 + l16, own);
      named_bar(3, 256);
      if (WG == 0) {
        const float4 o = lds128f(sb + OFF_VPX + wq * 512 + l16);
        st_relaxed2(gptr(xhi, pvm), pack_bf16(own.x + o.x, own.y + o.y), pack_bf16(own.z + o.z, own.w + o.w));
      }
    }
    auto token_pv = [&](int seg, bool staged) {
      constexpr int NU = 2 - WG;
      uint4 pt0, pt1, v0[NU], v1[NU]; uint32_t pm0, pm1; uint2 vm[NU];
      const uint32_t ap = l16 + WG * 4096 + xo::PT, am = (lv >> 2) + WG * 4096 + xo::PM;
      const uint32_t at = ovt - WG * 512;
      if (staged) {
        const uint32_t b = sb + OFF_MEM;
        pt0 = lds128(b + ap); pt1 = lds128(b + ap + 2048); pm0 = lds32(b + am); pm1 = lds32(b + am + 2048);
#pragma unroll
        for (int u = 0; u < NU; u++) { v0[u] = lds128(b + at - u * 2048); v1[u] = lds128(b + at + 512 - u * 2048); vm[u] = lds64(b + ovm - u * 2048); }
      } else {
        const uint32_t b = lds32(sb + CT_HEAD) + slot_off(seg);
        pt0.x = EMPTY;
#pragma unroll
        for (int u = 0; u < NU; u++) {
          v0[u] = ld_relaxed4(gptr(xhi, b + at) - u * 2048); v1[u] = ld_relaxed4(gptr(xhi, b + at) + 512 - u * 2048);
          vm[u] = ld_relaxed2(gptr(xhi, b + ovm) - u * 2048);
        }
      }
      const bool odd = lv & 16;
      char* op = gptr(xhi, lds32(sb + CT_O) + (seg * SEG + WG * 16 + (lv >> 6)) * (HD * 2) + wq * 32 + (lv & 16) + ((lv >> 2) & 8));
      if (!staged || __builtin_expect(warp_incomplete(umax4(pt0.x, pt1.x, pm0, pm1)), 0)) {
        const uint32_t b = lds32(sb + CT_HEAD) + slot_off(seg);
        uint32_t tries = zr;
#pragma unroll 1
        do {
          pt0 = ld_relaxed4(gptr(xhi, b + ap)); pt1 = ld_relaxed4(gptr(xhi, b + ap) + 2048);
          pm0 = ld_relaxed1(gptr(xhi, b + am)); pm1 = ld_relaxed1(gptr(xhi, b + am) + 2048);
        } while (warp_incomplete(umax4(pt0.x, pt1.x, pm0, pm1)) && ++tries < POLL_LIMIT);
      }
      const uint32_t pa[4] = {pt0.x, pt1.x, pt0.y, pt1.y}, pb[4] = {pt0.z, pt1.z, pt0.w, pt1.w};
#pragma unroll
      for (int u = 0; u < NU; u++) {
        float o0[4] = {0.f, 0.f, 0.f, 0.f}, o1[4] = {0.f, 0.f, 0.f, 0.f};
        mma1688(o0, pm0, pm1, vm[u].x); mma1688(o1, pm0, pm1, vm[u].y);
        mma16816(o0, pa, v0[u].x, v0[u].y); mma16816(o1, pa, v1[u].x, v1[u].y);
        if (WG) { mma16816(o0, pb, v0[u].z, v0[u].w); mma16816(o1, pb, v1[u].z, v1[u].w); }
#pragma unroll
        for (int r = 0; r < 2; r++) {
          const uint32_t w0 = pack_bf16(o0[2 * r], o0[2 * r + 1]), w1 = pack_bf16(o1[2 * r], o1[2 * r + 1]);
          const uint32_t rv = __shfl_xor_sync(~0u, odd ? w0 : w1, 1);
          asm volatile("st.global.v2.u32 [%0], {%1, %2};" ::"l"(op + r * 8 * HD * 2 - u * 64), "r"(odd ? rv : w0), "r"(odd ? w1 : rv) : "memory");
        }
      }
    };
    if (!more) {
      named_bar(3, 256);
      if (upper_warps) {
#pragma unroll 1
        for (int seg = NSEG - 2; seg < NSEG; seg++) token_pv(seg, false);
      }
      break;
    }
    {
      if (__builtin_expect(s > 0, 1)) {
        const uint32_t o = WG ? ovt - 512 : tv + 512;
        const char* src = gptr(xhi, lds32(sb + CT_HEAD) + slot_off(sv - 1) + o);
#pragma unroll
        for (int i = 0; i < 3 - WG; i++) cp_async16(sb + OFF_MEM + o + i * 512, src + i * 512);
        cp_async_commit();
      }
      bool xw;
      {
        float acc[16];
        if (__builtin_expect(!xok, 0)) mbar_wait<0>(sb + BAR_X + 8 * WG, (s + 1) & 1);
        wg_fence();
#pragma unroll
        for (int ks = 0; ks < 16; ks++) wgmma_m64n32_rs(acc, rot[ks], xdesc<WG>(16 + ks), ks != 0);
        wg_commit();
#pragma unroll
        for (int ks = 0; ks < 16; ks++) wgmma_m64n32_rs(acc, aV[ks], xdesc<WG>(ks), 1);
        wg_commit();
        SFENCE(50);
        NEWZ(2);
        xw = warp_is(3) && s + 2 < NSEG;
        tref += lds32(sb + CT_T + 4) + WG * T_LAG - T_SLIP;
        const uint32_t pvt = xvt + slot_off(sv + 1), awo = sb + wo_addr(tv);
        if (WG == 0 && warp_is(1) && s >= 0) expect_elect(sb + BAR_EX, 512);
        if (xw) {
          expect_elect(sb + BAR_X + 8 * WG, 32768);
          if (WG == 1 && s == NSEG - 3) asm volatile("griddepcontrol.launch_dependents;");
          if (WG == 1 && s + 5 < NSEG) prefetch_l2(maps.xp + (s + 5) * 65536 + lds32(sb + CT_PF), 1024);
        }
        wg_wait<1>();
        if (xw) { named_bar(4 + WG, 128); issue_x(sb, &maps.xq, s + 2, WG, 1); }
        else if (s + 2 < NSEG) named_bar_arrive(4 + WG, 128);
        if (__builtin_expect(s == 0, 0)) {
          mbar_wait(sb + BAR_P + 16, 0);
#pragma unroll
          for (int ks = 16 - O_FIX; ks < 16; ks++) ldsm_x4_t(bO[ks], (awo ^ 32) + (ks & 7) * 1024);
        }
#pragma unroll
        for (int ks = 0; ks < 16 - O_FIX; ks++) ldsm_x4_t(bO[ks], (ks < 8 ? awo : awo ^ 32) + (ks & 7) * 1024);
        wg_wait<0>();
        acc_fence(acc);
        constexpr int K = WG * 2, G = 2 - K;
        sts128f(sb + OFF_RED + WG * 1024 + t16, make_float4(acc[G], acc[G + 1], acc[4 + G], acc[5 + G]));
        sts128f(sb + OFF_RED + WG * 1024 + 512 + t16, make_float4(acc[8 + G], acc[9 + G], acc[12 + G], acc[13 + G]));
        cp_async_wait_group<0>();
        named_bar(3, 256);
        const float4 o0 = lds128f(sb + OFF_RED + (WG ^ 1) * 1024 + t16), o1 = lds128f(sb + OFF_RED + (WG ^ 1) * 1024 + 512 + t16);
        st_relaxed4(gptr(xhi, pvt),
                    pack_bf16(acc[K] + o0.x, acc[K + 1] + o0.y), pack_bf16(acc[4 + K] + o0.z, acc[5 + K] + o0.w),
                    pack_bf16(acc[8 + K] + o1.x, acc[9 + K] + o1.y), pack_bf16(acc[12 + K] + o1.z, acc[13 + K] + o1.w));
      }
      if (__builtin_expect(s >= 0, 1)) {
        uint32_t tries = 0;
#pragma unroll
        for (int ks = 0; ks < 16 - O_FIX; ks++) tries |= bO[ks][0];
        const char* po = gptr(xhi, xom + slot_off(sv) + (tries & zr));
        tries = zr;
        float d[2][2][4];
        uint32_t mx;
#pragma unroll 1
        do {
          tref += T_SLIP;
          WAIT_UNTIL(tref, aV[0], 1, 1);
          uint4 o[8];
#pragma unroll
          for (int i = 0; i < 4; i++) o[i] = ld_relaxed4(po + i * 512);
#pragma unroll
          for (int i = 0; i < 4; i++) o[4 + i] = ld_relaxed4(po + 16384 + i * 512);
          __syncwarp();
#pragma unroll
          for (int i = 0; i < 2; i++)
#pragma unroll
            for (int q = 0; q < 2; q++) { d[i][q][0] = d[i][q][1] = d[i][q][2] = d[i][q][3] = 0.f; }
#pragma unroll
          for (int i = 0; i < 4; i++) {
            mma16816(d[0][0], aO[2 * i], o[i].x, o[i].y); mma16816(d[1][0], aO[8 + 2 * i], o[i].x, o[i].y);
            mma16816(d[0][1], aO[2 * i + 1], o[i].z, o[i].w); mma16816(d[1][1], aO[9 + 2 * i], o[i].z, o[i].w);
          }
          mx = umax4(o[0].w, o[1].w, o[2].w, o[3].w);
          SFENCE(33 + tries);
#pragma unroll
          for (int i = 0; i < 4; i++) {
            mma16816(d[0][0], bO[2 * i], o[4 + i].x, o[4 + i].y); mma16816(d[1][0], bO[8 + 2 * i], o[4 + i].x, o[4 + i].y);
            mma16816(d[0][1], bO[2 * i + 1], o[4 + i].z, o[4 + i].w); mma16816(d[1][1], bO[9 + 2 * i], o[4 + i].z, o[4 + i].w);
          }
          mx = max(mx, umax4(o[4].w, o[5].w, o[6].w, o[7].w));
        } while (warp_incomplete(mx) && ++tries < POLL_LIMIT);
        NEWZ(3);
        const uint32_t rd = sb + OFF_RED + (WG ^ 1) * 1024 + t16;
        sts128f(rd, make_float4(d[0][0][0] + d[0][1][0], d[0][0][1] + d[0][1][1], d[0][0][2] + d[0][1][2], d[0][0][3] + d[0][1][3]));
        sts128f(rd + 512, make_float4(d[1][0][0] + d[1][1][0], d[1][0][1] + d[1][1][1], d[1][0][2] + d[1][1][2], d[1][0][3] + d[1][1][3]));
        if (upper_warps) {
          named_bar_arrive(7, 256);
          if (xw) issue_x(sb, &maps.xq, s + 2, WG, 0);
          if (__builtin_expect(s > 0, 1)) token_pv(sv - 1, true);
        } else {
          uint32_t mp = lds32(sb + CT_MP) + (lv >> 2);
          named_bar(7, 256);
          float4 p[8];
#pragma unroll
          for (int i = 0; i < 8; i++) p[i] = lds128f(sb + OFF_RED + lv + wq * 512 + i * 1024);
          float4 r;
          r.x = ((p[0].x + p[1].x) + (p[2].x + p[3].x)) + ((p[4].x + p[5].x) + (p[6].x + p[7].x));
          r.y = ((p[0].y + p[1].y) + (p[2].y + p[3].y)) + ((p[4].y + p[5].y) + (p[6].y + p[7].y));
          r.z = ((p[0].z + p[1].z) + (p[2].z + p[3].z)) + ((p[4].z + p[5].z) + (p[6].z + p[7].z));
          r.w = ((p[0].w + p[1].w) + (p[2].w + p[3].w)) + ((p[4].w + p[5].w) + (p[6].w + p[7].w));
          const bool w0 = warp_is(0);
          if (w0) st_async4(rsb + OFF_RX + lv, __float_as_uint(r.x), __float_as_uint(r.y), __float_as_uint(r.z), __float_as_uint(r.w), rsb + BAR_EX);
          if (!w0) {
            char* pp = gptr(xhi, mp + slot_off(sv + 1));
            mbar_wait(sb + BAR_EX, s & 1);
            const float4 q = lds128f(sb + OFF_RX + l16);
            st_relaxed1(pp, pack_bf16(r.x + q.x, r.y + q.y)); st_relaxed1(pp + 128, pack_bf16(r.z + q.z, r.w + q.w));
            pp = gptr(xhi, mp + slot_off(sv + 3));
            st_relaxed1(pp, EMPTY); st_relaxed1(pp + 128, EMPTY);
          }
        }
        NEWZ(4);
        const char* src = gptr(xhi, xm + WG * 8192 + slot_off(sv + 1));
        const uint32_t awv = sb + wv_addr(tv) + OFF_WVR;
        tref += lds32(sb + CT_T + 8) - WG * T_LAG;
        named_bar(8, 256);
#pragma unroll
        for (int ks = 0; ks < V_PRE; ks++) ldsm_x4_t(rot[ks], awv + ks * 2048);
        WAIT_UNTIL(tref, aV[0], 1, 2);
        gather_issue(sb + OFF_MEM + WG * 8192 + tv, src);
#pragma unroll
        for (int ks = V_PRE; ks < 16; ks++) ldsm_x4_t(rot[ks], awv + ks * 2048);
        NEWZ(6);
        st_relaxed4(gptr(xhi, xvt + slot_off(sv + 2)), EMPTY, EMPTY, EMPTY, EMPTY);
        if (WG == 0) st_relaxed2(gptr(xhi, xvm + slot_off(sv + 2)), EMPTY, EMPTY);
      } else {
        load_v(tv);
        if (xw) issue_x(sb, &maps.xq, s + 2, WG, 0);
        mbar_wait(sb + BAR_P + 8, 0);
#pragma unroll
        for (int ks = 0; ks < 8; ks++) { ldsm_x4_t(aO[ks], sb + wo_addr(tv) + ks * 1024); ldsm_x4_t(aO[8 + ks], sb + (wo_addr(tv) ^ 32) + ks * 1024); }
        named_bar(0, 256);
        if (threadIdx.x == 0) {
          fence_async_smem();
          mbar_expect_tx(sb + BAR_P + 16, 4 * 16384);
          for (int q = 0; q < 4; q++) tma_load_2d(sb + OFF_WOR + q * 16384, &maps.wo, h * 32, j * 2048 + 1024 + q * 256, sb + BAR_P + 16);
        }
        __syncwarp();
        tref = gtime() / T_SLIP * T_SLIP - T_SLIP;
      }
    }
  }
}

#undef j
#undef s
#undef sv
#undef xm
#undef wq

__global__ void __launch_bounds__(256, 1) __cluster_dims__(2, 1, 1)
chain_kernel(const __grid_constant__ ChainMaps maps, const bf16* __restrict__ mem0, const uint64_t xbase) {
  using namespace chain;
  extern __shared__ uint8_t smem_raw[];
  uint32_t sb = smem_u32(smem_raw);
  PIN(sb);
  if (sb != SB_LO + (blockIdx.x & 1) * RANK_BIT || mapa(sb, (blockIdx.x & 1) ^ 1) != (sb ^ RANK_BIT)) __trap();
  const int tid = threadIdx.x;
  const int h = blockIdx.x >> 2, role = (blockIdx.x >> 1) & 1, j = blockIdx.x & 1;
  if (tid == 0) {
    for (int i = 0; i < 9; i++) mbar_init(sb + OFF_BAR + 8 * i, 1);
    asm volatile("fence.mbarrier_init.release.cluster;" ::: "memory");
    const uint32_t xl = (uint32_t)xbase;
    sts32(sb + CT_BASE, xl); sts32(sb + CT_HEAD, xl + h * xo::HEAD); sts32(sb + CT_OM, xl + xo::OM + (role ? j * 32768 : h * 2048));
    sts32(sb + CT_MP, xl + xo::MEM + (h * 2 + j) * 256); sts32(sb + CT_O, xl + xo::O + (h * 2 + j) * 128); sts32(sb + CT_PF, (h * 2 + j) * 1024);
    sts32(sb + CT_TT, sb + (j ? OFF_KT : OFF_QT));
    if (role == 0) {
      const CUtensorMap* wm = j ? &maps.wk : &maps.wq;
      mbar_expect_tx(sb + BAR_P, 6 * 16384);
      for (int c = 0; c < 3; c++)
        for (int q = 0; q < 2; q++) tma_load_2d(sb + OFF_X + (q * 3 + c) * 16384, wm, h * DH + q * 64, q * 512 + c * 128, sb + BAR_P);
      mbar_expect_tx(sb + BAR_P + 8, 4 * 16384);
      for (int c = 0; c < 2; c++)
        for (int q = 0; q < 2; q++) tma_load_2d(sb + OFF_X + (6 + q * 2 + c) * 16384, wm, h * DH + (q ^ 1) * 64, q * 512 + c * 128, sb + BAR_P + 8);
      mbar_expect_tx(sb + BAR_P + 24, 4 * 16384);
      for (int q = 0; q < 2; q++)
        for (int o = 0; o < 2; o++) tma_load_2d(sb + OFF_WS + (q * 2 + o) * 16384, wm, h * DH + (q ^ o) * 64, q * 512 + 384, sb + BAR_P + 24);
      for (int q = 0; q < 2; q++) tma_prefetch_2d(wm, h * DH + (q ^ 1) * 64, q * 512 + 256);
    } else {
      mbar_expect_tx(sb + BAR_P, 8 * 16384);
      for (int q = 0; q < 4; q++) tma_load_2d(sb + OFF_WOR + q * 16384, &maps.wv, h * DH + j * 64, (q >> 1) * 512 + (q & 1) * 128, sb + BAR_P);
      for (int q = 0; q < 4; q++) tma_load_2d(sb + OFF_WVR + q * 16384, &maps.wv, h * DH + j * 64, (q >> 1) * 512 + 256 + (q & 1) * 128, sb + BAR_P);
    }
  }
  for (int r = 0; r < RING; r++) {
    char* p = (char*)xbase + r * xo::SLOT;
    const int wq = (tid >> 5) & 3;
    if (role == 1) st_relaxed4(p + h * xo::HEAD + xo::VT + (8 * j + 2 * wq + (tid >> 7)) * 512 + (tid & 31) * 16, EMPTY, EMPTY, EMPTY, EMPTY);
    else if (j == 0) st_relaxed4(p + (tid < 128 ? xo::OM + h * 2048 + tid * 16 : h * xo::HEAD + wq * 2048 + xo::VM + (tid & 31) * 16), EMPTY, EMPTY, EMPTY, EMPTY);
    else {
      st_relaxed4(p + h * xo::HEAD + (tid >> 6) * 2048 + 1024 + (tid & 63) * 16, EMPTY, EMPTY, EMPTY, EMPTY);
      if (tid < 32) st_relaxed4(p + xo::MEM + h * 512 + tid * 16, EMPTY, EMPTY, EMPTY, EMPTY);
    }
  }
  __syncthreads();
  if (__shfl_sync(0xffffffffu, tid >> 5, 0) == 0) {
    uint32_t t[2], c[2], ka[4] = {0, 0, 0, 0};
    const uint32_t z = maps.t_step >> 24;
#pragma unroll
    for (int i = 0; i < 2; i++) {
      const uint32_t end = (gtime() & ~31u) + (i ? 2048 : 1024);
      for (int g = z; g < 256 && (int)(gtime() - (end - 96)) < 0; g++) KEEPALIVE(ka, z);
      for (int g = z; g < 256 && (int)((t[i] = gtime()) - end) < 0; g++) {}
      c[i] = (uint32_t)clock64();
    }
    uint32_t v = 0, target = 0;
    if (tid == 0) {
      st_relaxed1(&g_rate[blockIdx.x], (t[1] - t[0]) * 4096u / (c[1] - c[0]));
      __threadfence();
      target = (atomicAdd(&g_epoch, 1u) & ~127u) + 128u;
    }
    target = __shfl_sync(0xffffffffu, target, 0);
    int guard = 0;
    do { asm volatile("ld.acquire.gpu.global.u32 %0, [%1];" : "=r"(v) : "l"(&g_epoch) : "memory"); }
    while (__any_sync(0xffffffffu, (int)(v - target) < 0) && ++guard < (1 << 20));
    const uint4 r4 = ld_relaxed4(&g_rate[tid * 4]);
    uint32_t r = min(__reduce_max_sync(0xffffffffu, umax4(r4.x, r4.y, r4.z, r4.w)), 4 * RATE0);
    if (r < RATE0 + 28) r = RATE0;
    const uint32_t a = (maps.t_step * r / RATE0 + 31) & ~31u, b = (maps.t_phase * r / RATE0 + 31) & ~31u;
    sts128(sb + CT_T, make_uint4(a, b, a - b, r));
  }
  const uint32_t xhi = (uint32_t)(xbase >> 32);
  const int wg = __shfl_sync(0xffffffffu, tid >> 7, 0);
  if (role == 0) {
    if (wg == 0) role_a<0>(maps, mem0, sb, xhi); else role_a<1>(maps, mem0, sb, xhi);
  } else {
    if (wg == 0) role_v<0>(maps, mem0, sb, xhi); else role_v<1>(maps, mem0, sb, xhi);
  }
  __syncwarp();
  cluster_arrive();
  cluster_wait();
}

struct BMaps {
  CUtensorMap q, k, v, out, k8;
  const bf16 *shift_k, *ssm_k, *ssm_D;
};

#define B_SLEEP 200
namespace bp {
constexpr int U_PITCH = (2048 + 128) * 2 + 16;
constexpr int KR_WORDS = 1048;
constexpr int KR_PITCH = 8704;
constexpr int OFF_U = 0;
constexpr int OFF_KR = (8 * U_PITCH + 127) / 128 * 128;
constexpr int Q_OFF = 4352;
constexpr int OFF_BAR = OFF_KR + 8 * KR_PITCH;
constexpr int GROUP_BYTES = OFF_BAR + 128;
constexpr int SMEM = 2 * GROUP_BYTES + 128;
constexpr int NTASK = DM / 8;
static_assert(Q_OFF >= 4224 && Q_OFF + 4096 <= KR_PITCH, "staging does not fit");
}

__device__ __forceinline__ uint32_t bmul2(uint32_t a, uint32_t b) { uint32_t r; asm("mul.rn.bf16x2 %0, %1, %2;" : "=r"(r) : "r"(a), "r"(b)); return r; }
__device__ __forceinline__ uint32_t badd2(uint32_t a, uint32_t b) { uint32_t r; asm("add.rn.bf16x2 %0, %1, %2;" : "=r"(r) : "r"(a), "r"(b)); return r; }

__device__ __forceinline__ void mbar_wait_sleep(uint32_t bar, uint32_t parity) {
  int guard = 0;
  while (!mbar_try(bar, parity)) { __nanosleep(B_SLEEP); if (++guard > (1 << 22)) __trap(); }
}

__device__ __forceinline__ void bpart_body(const BMaps& maps, int first, int stride, int end) {
  using namespace bp;
  extern __shared__ uint8_t smem_all[];
  const int grp = __shfl_sync(0xffffffffu, threadIdx.x >> 8, 0);
  const int lane = keep(threadIdx.x & 31), g = lane >> 2, t = lane & 3;
  const int w = __shfl_sync(0xffffffffu, (threadIdx.x >> 5) & 7, 0);
  const uint32_t sb = ((smem_u32(smem_all) + 127) & ~127u) + grp * GROUP_BYTES;
  const uint32_t kr = sb + OFF_KR + w * KR_PITCH, bar_k = sb + OFF_BAR + 8 * w, bar_q = bar_k + 64;
  if (lane == 0) { mbar_init(bar_k, 1); mbar_init(bar_q, 1); asm volatile("fence.mbarrier_init.release.cluster;" ::: "memory"); }
  if (lane < 16) sts128(sb + OFF_U + w * U_PITCH + lane * 16, make_uint4(0, 0, 0, 0));
  __syncwarp();
  if (grp == 1) { named_bar_arrive(3, 512); named_bar(5, 512); }
  const int lm = lane >> 3, lr = lane & 7;
  uint32_t ph = 0;
  for (int task = first + grp; task < end; task += stride, ph ^= 1) {
    const int d0 = task * 8;
    uint4 x[8];
    {
      const uint4* kf = (const uint4*)(maps.ssm_k + (size_t)(d0 + w) * S_LEN);
#pragma unroll
      for (int it = 0; it < 8; it++) x[it] = __ldg(kf + it * 32 + lane);
    }
    const uint4 ska = __ldg((const uint4*)(maps.shift_k + (d0 + 2 * t) * 4));
    __syncwarp();
    if (lane == 0) {
      mbar_expect_tx(bar_k, 2 * 4096 + 128);
      tma_load_2d(kr + 4096, &maps.k8, d0, w * 256 + 248, bar_k);
      tma_load_2d(kr, &maps.k, d0, w * 256 - 8, bar_k);
      bulk_wait_read<0>();
      tma_load_2d(kr + Q_OFF, &maps.v, d0, w * 256, bar_k);
    }
    __syncwarp();
    if (task == first) named_bar_arrive(5, 512);
    const uint32_t sk[4] = {__byte_perm(ska.x, ska.z, 0x5410), __byte_perm(ska.x, ska.z, 0x7632), __byte_perm(ska.y, ska.w, 0x5410), __byte_perm(ska.y, ska.w, 0x7632)};
    mbar_wait_sleep(bar_k, ph);
    {
      const uint32_t ka = kr + (lane + 8) * 16;
#pragma unroll
      for (int i = 0; i < 8; i++) {
        uint32_t k0[4], k1[4], k2[4], k3[4], v[4], r[4];
        ldsm_x4(k3, ka + i * 512 - 48); ldsm_x4(k2, ka + i * 512 - 32); ldsm_x4(k1, ka + i * 512 - 16); ldsm_x4(k0, ka + i * 512);
        ldsm_x4(v, ka + (Q_OFF - 128) + i * 512);
#pragma unroll
        for (int b = 0; b < 4; b++) {
          uint32_t acc = bmul2(k3[b], sk[3]);
          acc = badd2(acc, bmul2(k2[b], sk[2]));
          acc = badd2(acc, bmul2(k1[b], sk[1]));
          acc = badd2(acc, bmul2(k0[b], sk[0]));
          r[b] = bmul2(acc, v[b]);
        }
        const int ch = 16 + w * 32 + i * 4 + lm;
        stsm_x4_t(sb + OFF_U + lr * U_PITCH + ((ch ^ ((ch >> 3) & 1)) << 4), r[0], r[1], r[2], r[3]);
      }
    }
    __syncwarp();
    {
      const uint32_t c0 = kr, c1 = c0 + (KR_WORDS + 16) * 4;
      uint32_t carry = 0;
#pragma unroll
      for (int it = 0; it < 8; it++) {
        const int blk = it * 32 + lane;
        uint32_t prev = __shfl_up_sync(0xffffffffu, x[it].w, 1);
        if (lane == 0) prev = carry;
        carry = __shfl_sync(0xffffffffu, x[it].w, 31);
        sts128(c0 + (1028 - 4 * blk) * 4, make_uint4(__byte_perm(x[it].w, 0, 0x1032), __byte_perm(x[it].z, 0, 0x1032),
                                                     __byte_perm(x[it].y, 0, 0x1032), __byte_perm(x[it].x, 0, 0x1032)));
        sts128(c1 + (1028 - 4 * blk) * 4, make_uint4(__byte_perm(x[it].w, x[it].z, 0x7610), __byte_perm(x[it].z, x[it].y, 0x7610),
                                                     __byte_perm(x[it].y, x[it].x, 0x7610), __byte_perm(x[it].x, prev, 0x7610)));
      }
      if (lane < 4) { sts128(c0 + (1032 + 4 * lane) * 4, make_uint4(0, 0, 0, 0)); sts128(c1 + (1032 + 4 * lane) * 4, make_uint4(0, 0, 0, 0)); }
      __syncwarp();
    }
    named_bar(3 + grp, 512);
    float acc[16][4];
#pragma unroll
    for (int jn = 0; jn < 16; jn++) { acc[jn][0] = acc[jn][1] = acc[jn][2] = acc[jn][3] = 0.f; }
    {
      const uint32_t ub = sb + OFF_U + w * U_PITCH;
      uint32_t kd = kr + (((g & 1) ? 0 : KR_WORDS + 16) + ((((g & 1) ? 2063 : 2062) - (g - 2 * t)) >> 1)) * 4;
      uint32_t uc = 2 * (8 + lr + (lm >> 1) * 8) + (lm & 1);
#pragma unroll 1
      for (int d0s = 0; d0s < 8; d0s++, kd -= 32, uc -= 2) {
        const uint32_t uf = ub + ((uc ^ ((uc >> 3) & 1)) << 4);
        uint32_t A[3][4];
        A[0][0] = lds32v(kd); A[0][1] = lds32v(kd - 16); A[0][2] = lds32v(kd + 16); A[0][3] = lds32v(kd);
        uint32_t F[8][4];
#pragma unroll
        for (int m = 7; m >= 0; m--) ldsm_x4(F[m], uf + m * 512);
#pragma unroll
        for (int i = 0; i < 16; i++) {
          if (i + 1 < 16) {
            A[(i + 1) % 3][0] = lds32v(kd - 256 * (i + 1)); A[(i + 1) % 3][1] = lds32v(kd - 256 * (i + 1) - 16);
            A[(i + 1) % 3][2] = lds32v(kd - 256 * (i + 1) + 16); A[(i + 1) % 3][3] = lds32v(kd - 256 * (i + 1));
          }
#pragma unroll
          for (int jn = 15; jn >= i; jn--) mma16816(acc[jn], A[i % 3], F[(jn - i) >> 1][((jn - i) & 1) * 2], F[(jn - i) >> 1][((jn - i) & 1) * 2 + 1]);
        }
      }
    }
    named_bar_arrive(3 + (grp ^ 1), 512);
    __syncwarp();
    fence_async_smem();
    __syncwarp();
    if (lane == 0) { mbar_expect_tx(bar_q, 4096); tma_load_2d(kr + Q_OFF, &maps.q, d0, w * 256, bar_q); }
    const uint32_t dpair = __ldg((const uint32_t*)(maps.ssm_D + d0) + t);
    {
      const uint32_t ya = kr + w * 16 + (((lm >> 1) * 8 + lr) * 32) + (lm & 1) * 16;
#pragma unroll
      for (int jn = 0; jn < 16; jn += 2)
        stsm_x4_t(ya + jn * 256, pack_bf16(acc[jn][0], acc[jn][1]), pack_bf16(acc[jn][2], acc[jn][3]),
                  pack_bf16(acc[jn + 1][0], acc[jn + 1][1]), pack_bf16(acc[jn + 1][2], acc[jn + 1][3]));
    }
    named_bar(1 + grp, 256);
    mbar_wait_sleep(bar_q, ph);
    {
      const uint32_t ya = sb + OFF_KR + lr * (KR_PITCH + 16) + (w * 256 + lm * 8) * 2;
#pragma unroll
      for (int i = 0; i < 8; i++) {
        uint32_t y[4], u[4], q[4], r[4];
        ldsm_x4(q, kr + Q_OFF + lane * 16 + i * 512);
        ldsm_x4_t(y, ya + i * 64);
        const int ch = 16 + w * 32 + i * 4 + lm;
        ldsm_x4_t(u, sb + OFF_U + lr * U_PITCH + ((ch ^ ((ch >> 3) & 1)) << 4));
#pragma unroll
        for (int b = 0; b < 4; b++) r[b] = bmul2(q[b], badd2(y[b], bmul2(u[b], dpair)));
        stsm_x4(kr + Q_OFF + lane * 16 + i * 512, r[0], r[1], r[2], r[3]);
      }
      fence_async_smem();
      __syncwarp();
      if (lane == 0) { tma_store_2d(&maps.out, kr + Q_OFF, DM + d0, w * 256); bulk_commit(); }
    }
    named_bar(1 + grp, 256);
  }
  if (lane == 0) bulk_wait<0>();
}

__global__ void __launch_bounds__(512, 1) __cluster_dims__(2, 1, 1) bpart_kernel(const __grid_constant__ BMaps maps, int end) {
  bpart_body(maps, blockIdx.x * 2, gridDim.x * 2, end);
}

struct GemmMaps {
  CUtensorMap o;
  CUtensorMap w;
  CUtensorMap c;
};
namespace k3 {
constexpr int STAGES = 6;
constexpr int W_BYTES = 2 * 8192, O_BYTES = K3_N * 128, STAGE_BYTES = W_BYTES + O_BYTES;
constexpr int TT = (S_LEN + K3_N - 1) / K3_N, NGEMM = TT * (DM / 128), NB = 128 - NGEMM, KSTEPS = HD / 64;
constexpr int SMEM_G = STAGES * STAGE_BYTES + 1024 + 256;
constexpr int SMEM = SMEM_G > bp::SMEM ? SMEM_G : bp::SMEM;
static_assert(STAGE_BYTES % 1024 == 0, "swizzle atoms");
}

__global__ void __launch_bounds__(512, 1)
tail_kernel(const __grid_constant__ GemmMaps maps, const __grid_constant__ BMaps bmaps) {
  using namespace k3;
  if (blockIdx.x < NB) {
    bpart_body(bmaps, bp::NTASK - 2 * NB + 2 * blockIdx.x, bp::NTASK, bp::NTASK);
    return;
  }
  extern __shared__ uint8_t smem_raw[];
  const uint32_t sbase = (smem_u32(smem_raw) + 1023) & ~1023u;
  const uint32_t bars = sbase + STAGES * STAGE_BYTES;
  const int tid = threadIdx.x, warp = tid >> 5;
  const int tt = (blockIdx.x - NB) / 8, ct = (blockIdx.x - NB) % 8;

  if (tid == 0) {
    for (int s = 0; s < STAGES; s++) { mbar_init(bars + 8 * s, 1); mbar_init(bars + 8 * (STAGES + s), 2); }
    asm volatile("fence.mbarrier_init.release.cluster;" ::: "memory");
  }
  __syncthreads();

  if (warp >= 8) {
    if (tid == 256) {
      tma_prefetch_desc(&maps.o);
      for (int k = 0; k < STAGES; k++) {
        const uint32_t full = bars + 8 * k, sa = sbase + k * STAGE_BYTES;
        mbar_expect_tx(full, STAGE_BYTES);
#pragma unroll
        for (int j = 0; j < 2; j++) tma_load_2d(sa + j * 8192, &maps.w, ct * 128 + j * 64, k * 64, full);
      }
      asm volatile("griddepcontrol.wait;" ::: "memory");
      int stage = 0; uint32_t ph = 1;
      for (int k = 0; k < KSTEPS; k++) {
        mbar_wait(bars + 8 * (STAGES + stage), ph);
        const uint32_t full = bars + 8 * stage, sa = sbase + stage * STAGE_BYTES;
        const bool pre = k < STAGES;
        if (!pre) mbar_expect_tx(full, STAGE_BYTES);
        tma_load_2d(sa + W_BYTES, &maps.o, k * 64, tt * K3_N, full);
        if (!pre) {
#pragma unroll
          for (int j = 0; j < 2; j++) tma_load_2d(sa + j * 8192, &maps.w, ct * 128 + j * 64, k * 64, full);
        }
        if (++stage == STAGES) { stage = 0; ph ^= 1; }
      }
    }
  } else {
    const int wg = warp >> 2, lane = tid & 31, wq = warp & 3;
    int stage = 0; uint32_t ph = 0;
    float acc[K3_N / 2];
    int prev = -1;
    for (int k = 0; k < KSTEPS; k++) {
      mbar_wait(bars + 8 * stage, ph);
      const uint32_t sa = sbase + stage * STAGE_BYTES;
      wg_fence();
#pragma unroll
      for (int kk = 0; kk < 4; kk++) {
        const uint64_t da = make_desc(sa + wg * 8192 + kk * 2048, 16, 1024, 1);
        const uint64_t db = make_desc(sa + W_BYTES + kk * 32, 16, 1024, 1);
        wgmma_k3_ss_ta(acc, da, db, (k | kk) != 0);
      }
      wg_commit();
      if (prev >= 0) { wg_wait<1>(); if ((tid & 127) == 0) mbar_arrive(bars + 8 * (STAGES + prev)); }
      prev = stage;
      if (++stage == STAGES) { stage = 0; ph ^= 1; }
    }
    wg_wait<0>();
#pragma unroll
    for (int i = 0; i < K3_N / 2; i++) asm volatile("" : "+f"(acc[i]) :: "memory");
    named_bar(1, 256);
    const uint32_t ebuf = sbase + wg * STAGE_BYTES;
    const uint32_t ea = ebuf + ((lane >> 4) * 8 + (lane & 7)) * 128 + (((2 * wq + ((lane >> 3) & 1)) ^ (lane & 7)) << 4);
#pragma unroll
    for (int i = 0; i < K3_N / 8; i += 2) {
      const int i1 = i + 1 < K3_N / 8 ? i + 1 : i;
      stsm_x4_t(ea + i * 1024, pack_bf16(acc[4 * i], acc[4 * i + 1]), pack_bf16(acc[4 * i + 2], acc[4 * i + 3]),
                pack_bf16(acc[4 * i1], acc[4 * i1 + 1]), pack_bf16(acc[4 * i1 + 2], acc[4 * i1 + 3]));
    }
    fence_async_smem();
    named_bar(2 + wg, 128);
    if ((tid & 127) == 0) {
      tma_store_2d(&maps.c, ebuf, ct * 128 + wg * 64, tt * K3_N);
      bulk_commit();
      bulk_wait<0>();
    }
  }
}

typedef CUresult (*EncodeFn)(CUtensorMap*, CUtensorMapDataType, cuuint32_t, void*, const cuuint64_t*, const cuuint64_t*,
                             const cuuint32_t*, const cuuint32_t*, CUtensorMapInterleave, CUtensorMapSwizzle,
                             CUtensorMapL2promotion, CUtensorMapFloatOOBfill);

void make_map(EncodeFn enc, CUtensorMap* m, const void* ptr, uint64_t cols, uint64_t rows, uint64_t pitch_elems,
              uint32_t box_cols, uint32_t box_rows, CUtensorMapSwizzle swz,
              CUtensorMapL2promotion promo = CU_TENSOR_MAP_L2_PROMOTION_L2_128B) {
  cuuint64_t dims[2] = {cols, rows};
  cuuint64_t strides[1] = {pitch_elems * 2};
  cuuint32_t box[2] = {box_cols, box_rows};
  cuuint32_t es[2] = {1, 1};
  enc(m, CU_TENSOR_MAP_DATA_TYPE_BFLOAT16, 2, const_cast<void*>(ptr), dims, strides, box, es, CU_TENSOR_MAP_INTERLEAVE_NONE, swz,
      promo, CU_TENSOR_MAP_FLOAT_OOB_FILL_NONE);
}

void make_map_nd(EncodeFn enc, CUtensorMap* m, const void* ptr, int rank, const uint64_t* dims, const uint64_t* strides_elems,
                 const uint32_t* box, CUtensorMapSwizzle swz) {
  cuuint64_t d[5], st[4]; cuuint32_t b[5], es[5];
  for (int i = 0; i < rank; i++) { d[i] = dims[i]; b[i] = box[i]; es[i] = 1; if (i) st[i - 1] = strides_elems[i] * 2; }
  enc(m, CU_TENSOR_MAP_DATA_TYPE_BFLOAT16, rank, const_cast<void*>(ptr), d, st, b, es, CU_TENSOR_MAP_INTERLEAVE_NONE, swz,
      CU_TENSOR_MAP_L2_PROMOTION_L2_128B, CU_TENSOR_MAP_FLOAT_OOB_FILL_NONE);
}

}

extern "C" void kernel_launch(void* const* d_in, const int* in_sizes, int n_in, void* d_out, int out_size) {
  (void)in_sizes; (void)n_in; (void)out_size;
  const bf16* x = (const bf16*)d_in[0];
  const bf16* mem0 = (const bf16*)d_in[1];
  const bf16* Wq = (const bf16*)d_in[2];
  const bf16* Wk = (const bf16*)d_in[3];
  const bf16* Wv = (const bf16*)d_in[4];
  const bf16* Wo = (const bf16*)d_in[5];
  const bf16* Bq = (const bf16*)d_in[7];
  const bf16* Bk = (const bf16*)d_in[8];
  const bf16* Bv = (const bf16*)d_in[9];
  const bf16* shift_k = (const bf16*)d_in[10];
  const bf16* ssm_k = (const bf16*)d_in[11];
  const bf16* ssm_D = (const bf16*)d_in[12];
  bf16* out = (bf16*)d_out;

  static EncodeFn enc = nullptr;
  static uint64_t xbase0;
  static int nsm = 132;
  static cudaStream_t s1;
  static cudaEvent_t ev_fork, ev_join;
  if (!enc) {
    cudaDriverEntryPointQueryResult qr;
    void* fn = nullptr;
    cudaGetDriverEntryPoint("cuTensorMapEncodeTiled", &fn, cudaEnableDefault, &qr);
    enc = (EncodeFn)fn;
    void* ps = nullptr;
    cudaGetSymbolAddress(&ps, g_scratch);
    xbase0 = (uint64_t)ps;
    if ((xbase0 >> 32) != ((xbase0 + xo::BYTES - 1) >> 32)) xbase0 += xo::BYTES;
    cudaFuncSetAttribute(tail_kernel, cudaFuncAttributeMaxDynamicSharedMemorySize, k3::SMEM);
    cudaFuncSetAttribute(chain_kernel, cudaFuncAttributeMaxDynamicSharedMemorySize, chain::SMEM);
    cudaFuncSetAttribute(bpart_kernel, cudaFuncAttributeMaxDynamicSharedMemorySize, bp::SMEM);
    cudaStreamCreateWithFlags(&s1, cudaStreamNonBlocking);
    cudaEventCreateWithFlags(&ev_fork, cudaEventDisableTiming);
    cudaEventCreateWithFlags(&ev_join, cudaEventDisableTiming);
    int dev = 0; cudaGetDevice(&dev);
    cudaDeviceGetAttribute(&nsm, cudaDevAttrMultiProcessorCount, dev);
  }
  uint64_t xbase = xbase0;
  const CUtensorMapSwizzle SW128 = CU_TENSOR_MAP_SWIZZLE_128B, SW64 = CU_TENSOR_MAP_SWIZZLE_64B;
  GemmMaps m3; ChainMaps mc;
  make_map(enc, &m3.o, (void*)(xbase + xo::O), HD, S_LEN, HD, 64, K3_N, SW128);
  make_map(enc, &m3.w, Wo, DM, HD, DM, 64, 64, SW128);
  make_map(enc, &m3.c, out, DM, S_LEN, OUT_LD, 64, K3_N, SW128);
  const CUtensorMapL2promotion P256 = CU_TENSOR_MAP_L2_PROMOTION_L2_256B;
  make_map(enc, &mc.wq, Wq, HD, DM, HD, 64, 128, SW128, P256);
  make_map(enc, &mc.wk, Wk, HD, DM, HD, 64, 128, SW128, P256);
  make_map(enc, &mc.wv, Wv, HD, DM, HD, 64, 128, SW128, P256);
  make_map(enc, &mc.wo, Wo, DM, HD, DM, 32, 256, SW64, P256);
  {
    const uint64_t dx[3] = {64, S_LEN, DM / 64}, sx[3] = {1, DM, 64};
    const uint32_t bx[3] = {64, SEG, 8};
    make_map_nd(enc, &mc.x, x, 3, dx, sx, bx, SW128);
    const uint32_t bq[3] = {64, SEG, 4};
    make_map_nd(enc, &mc.xq, x, 3, dx, sx, bq, SW128);
    mc.xp = (const char*)x;
  }

  const int skip = 0;
  mc.t_step = T_STEP; mc.t_phase = T_PHASE;
  BMaps mb;
  const CUtensorMapSwizzle SWN = CU_TENSOR_MAP_SWIZZLE_NONE;
  make_map(enc, &mb.k, Bk, DM, S_LEN, DM, 8, 256, SWN);
  make_map(enc, &mb.q, Bq, DM, S_LEN, DM, 8, 256, SWN);
  make_map(enc, &mb.v, Bv, DM, S_LEN, DM, 8, 256, SWN);
  mb.shift_k = shift_k; mb.ssm_k = ssm_k; mb.ssm_D = ssm_D;
  make_map(enc, &mb.out, out, OUT_LD, S_LEN, OUT_LD, 8, 256, SWN);
  make_map(enc, &mb.k8, Bk, DM, S_LEN, DM, 8, 8, SWN);
  cudaStream_t s0 = cudaStreamPerThread;
  const int nb = nsm >= 132 ? 4 : 2, ntask1 = bp::NTASK - 2 * k3::NB;
  const bool fork = nsm >= 130 && !(skip & 16);
  if (fork) {
    cudaEventRecord(ev_fork, s0);
    cudaStreamWaitEvent(s1, ev_fork, 0);
    if (!(skip & 1)) bpart_kernel<<<nb, 512, bp::SMEM, s1>>>(mb, ntask1);
    cudaEventRecord(ev_join, s1);
  } else if (!(skip & 1)) {
    bpart_kernel<<<ntask1 / 2, 512, bp::SMEM, s0>>>(mb, ntask1);
  }
  if (!(skip & 4)) chain_kernel<<<128, 256, chain::SMEM, s0>>>(mc, mem0, xbase);
  if (!(skip & 8)) {
    cudaLaunchAttribute pdl[1];
    pdl[0].id = cudaLaunchAttributeProgrammaticStreamSerialization;
    pdl[0].val.programmaticStreamSerializationAllowed = 1;
    cudaLaunchConfig_t cfg = {};
    cfg.gridDim = dim3(128); cfg.blockDim = dim3(512); cfg.dynamicSmemBytes = k3::SMEM; cfg.stream = s0;
    cfg.attrs = pdl; cfg.numAttrs = 1;
    cudaLaunchKernelEx(&cfg, tail_kernel, m3, mb);
  }
  if (fork) cudaStreamWaitEvent(s0, ev_join, 0);
}
```

```cpp
#include <cuda_runtime.h>
#include <cuda_bf16.h>
#include <cuda.h>
#include <stdint.h>

namespace {

constexpr int S_LEN = 2048;
constexpr int DM = 1024;
constexpr int NH = 32;
constexpr int DH = 128;
constexpr int HD = NH * DH;
constexpr int SEG = 32;
constexpr int NSEG = S_LEN / SEG;
constexpr int OUT_LD = 2048;

typedef __nv_bfloat16 bf16;
#define K3_N 160

__device__ __forceinline__ uint32_t smem_u32(const void* p) { return (uint32_t)__cvta_generic_to_shared(p); }

__device__ __forceinline__ void mbar_init(uint32_t bar, uint32_t count) {
  asm volatile("mbarrier.init.shared::cta.b64 [%0], %1;" ::"r"(bar), "r"(count) : "memory");
}
__device__ __forceinline__ void mbar_expect_tx(uint32_t bar, uint32_t bytes) {
  asm volatile("mbarrier.arrive.expect_tx.shared::cta.b64 _, [%0], %1;" ::"r"(bar), "r"(bytes) : "memory");
}
__device__ __forceinline__ void mbar_arrive(uint32_t bar) {
  asm volatile("mbarrier.arrive.shared::cta.b64 _, [%0];" ::"r"(bar) : "memory");
}
__device__ __forceinline__ bool mbar_try(uint32_t bar, uint32_t parity) {
  uint32_t ok;
  asm volatile("{.reg .pred p; mbarrier.try_wait.parity.shared::cta.b64 p, [%1], %2; selp.u32 %0, 1, 0, p;}"
               : "=r"(ok) : "r"(bar), "r"(parity) : "memory");
  return ok;
}
__device__ __forceinline__ bool mbar_test(uint32_t bar, uint32_t parity) {
  uint32_t ok;
  asm volatile("{.reg .pred p; mbarrier.test_wait.parity.shared::cta.b64 p, [%1], %2; selp.u32 %0, 1, 0, p;}"
               : "=r"(ok) : "r"(bar), "r"(parity) : "memory");
  return ok;
}
template <int HINT = 1>
__device__ __forceinline__ void mbar_wait(uint32_t bar, uint32_t parity) {
  int guard = 0;
  while (__builtin_expect(!mbar_try(bar, parity), HINT)) { if (++guard > (1 << 22)) __trap(); }
}
__device__ __forceinline__ void tma_load_2d(uint32_t dst, const CUtensorMap* map, int c0, int c1, uint32_t bar) {
  asm volatile("cp.async.bulk.tensor.2d.shared::cluster.global.mbarrier::complete_tx::bytes [%0], [%1, {%3, %4}], [%2];"
               ::"r"(dst), "l"(map), "r"(bar), "r"(c0), "r"(c1) : "memory");
}
__device__ __forceinline__ void tma_store_2d(const CUtensorMap* map, uint32_t src, int c0, int c1) {
  asm volatile("cp.async.bulk.tensor.2d.global.shared::cta.bulk_group [%0, {%2, %3}], [%1];"
               ::"l"(map), "r"(src), "r"(c0), "r"(c1) : "memory");
}
__device__ __forceinline__ void tma_prefetch_2d(const CUtensorMap* map, int c0, int c1) {
  asm volatile("cp.async.bulk.prefetch.tensor.2d.L2.global [%0, {%1, %2}];" ::"l"(map), "r"(c0), "r"(c1) : "memory");
}
__device__ __forceinline__ void tma_prefetch_desc(const CUtensorMap* map) {
  asm volatile("prefetch.tensormap [%0];" ::"l"(map) : "memory");
}
__device__ __forceinline__ void fence_async_smem() { asm volatile("fence.proxy.async.shared::cta;" ::: "memory"); }
__device__ __forceinline__ void bulk_commit() { asm volatile("cp.async.bulk.commit_group;" ::: "memory"); }
template <int N> __device__ __forceinline__ void bulk_wait_read() { asm volatile("cp.async.bulk.wait_group.read %0;" ::"n"(N) : "memory"); }
template <int N> __device__ __forceinline__ void bulk_wait() { asm volatile("cp.async.bulk.wait_group %0;" ::"n"(N) : "memory"); }
__device__ __forceinline__ void named_bar(int id, int n) { asm volatile("bar.sync %0, %1;" ::"r"(id), "r"(n) : "memory"); }

__device__ __forceinline__ void named_bar_arrive(int id, int n) { asm volatile("bar.arrive %0, %1;" ::"r"(id), "r"(n) : "memory"); }
__device__ __forceinline__ float ex2(float x) { float y; asm("ex2.approx.ftz.f32 %0, %1;" : "=f"(y) : "f"(x)); return y; }
__device__ __forceinline__ float rcp(float x) { float y; asm("rcp.approx.ftz.f32 %0, %1;" : "=f"(y) : "f"(x)); return y; }

__device__ __forceinline__ void sts32(uint32_t a, uint32_t x) { asm volatile("st.shared.b32 [%0], %1;" ::"r"(a), "r"(x) : "memory"); }
__device__ __forceinline__ uint32_t lds32(uint32_t a) { uint32_t x; asm volatile("ld.shared.b32 %0, [%1];" : "=r"(x) : "r"(a) : "memory"); return x; }
__device__ __forceinline__ uint32_t lds32v(uint32_t a) { uint32_t x; asm volatile("ld.volatile.shared.b32 %0, [%1];" : "=r"(x) : "r"(a) : "memory"); return x; }
__device__ __forceinline__ void sts128(uint32_t a, const uint4& v) { asm volatile("st.shared.v4.b32 [%0], {%1,%2,%3,%4};" ::"r"(a), "r"(v.x), "r"(v.y), "r"(v.z), "r"(v.w) : "memory"); }
__device__ __forceinline__ void sts128f(uint32_t a, const float4& v) { asm volatile("st.shared.v4.f32 [%0], {%1,%2,%3,%4};" ::"r"(a), "f"(v.x), "f"(v.y), "f"(v.z), "f"(v.w) : "memory"); }
__device__ __forceinline__ uint4 lds128(uint32_t a) { uint4 v; asm volatile("ld.shared.v4.b32 {%0,%1,%2,%3}, [%4];" : "=r"(v.x), "=r"(v.y), "=r"(v.z), "=r"(v.w) : "r"(a) : "memory"); return v; }
__device__ __forceinline__ float4 lds128f(uint32_t a) { float4 v; asm volatile("ld.shared.v4.f32 {%0,%1,%2,%3}, [%4];" : "=f"(v.x), "=f"(v.y), "=f"(v.z), "=f"(v.w) : "r"(a) : "memory"); return v; }

__device__ __forceinline__ void cp_async16(uint32_t dst, const void* src) { asm volatile("cp.async.cg.shared.global [%0], [%1], 16;" ::"r"(dst), "l"(src) : "memory"); }
__device__ __forceinline__ void cp_async_commit() { asm volatile("cp.async.commit_group;" ::: "memory"); }
template <int N> __device__ __forceinline__ void cp_async_wait_group() { asm volatile("cp.async.wait_group %0;" ::"n"(N) : "memory"); }

__device__ __forceinline__ void wg_fence() { asm volatile("wgmma.fence.sync.aligned;" ::: "memory"); }
__device__ __forceinline__ void wg_commit() { asm volatile("wgmma.commit_group.sync.aligned;" ::: "memory"); }
template <int N> __device__ __forceinline__ void wg_wait() { asm volatile("wgmma.wait_group.sync.aligned %0;" ::"n"(N) : "memory"); }
__device__ __forceinline__ uint64_t make_desc(uint32_t addr, uint32_t lbo, uint32_t sbo, uint32_t swz) {
  return (uint64_t)((addr & 0x3FFFF) >> 4) | ((uint64_t)(lbo >> 4) << 16) | ((uint64_t)(sbo >> 4) << 32) | ((uint64_t)swz << 62);
}

__device__ __forceinline__ void ldsm_x4(uint32_t (&r)[4], uint32_t addr) {
  asm volatile("ldmatrix.sync.aligned.m8n8.x4.shared.b16 {%0,%1,%2,%3}, [%4];"
               : "=r"(r[0]), "=r"(r[1]), "=r"(r[2]), "=r"(r[3]) : "r"(addr) : "memory");
}
__device__ __forceinline__ void ldsm_x4_t(uint32_t (&r)[4], uint32_t addr) {
  asm volatile("ldmatrix.sync.aligned.m8n8.x4.trans.shared.b16 {%0,%1,%2,%3}, [%4];"
               : "=r"(r[0]), "=r"(r[1]), "=r"(r[2]), "=r"(r[3]) : "r"(addr) : "memory");
}
__device__ __forceinline__ void stsm_x4(uint32_t addr, uint32_t r0, uint32_t r1, uint32_t r2, uint32_t r3) {
  asm volatile("stmatrix.sync.aligned.m8n8.x4.shared.b16 [%0], {%1,%2,%3,%4};"
               ::"r"(addr), "r"(r0), "r"(r1), "r"(r2), "r"(r3) : "memory");
}
__device__ __forceinline__ void stsm_x4_t(uint32_t addr, uint32_t r0, uint32_t r1, uint32_t r2, uint32_t r3) {
  asm volatile("stmatrix.sync.aligned.m8n8.x4.trans.shared.b16 [%0], {%1,%2,%3,%4};" ::"r"(addr), "r"(r0), "r"(r1), "r"(r2), "r"(r3) : "memory");
}
__device__ __forceinline__ void mma16816(float (&c)[4], const uint32_t (&a)[4], uint32_t b0, uint32_t b1) {
  asm volatile("mma.sync.aligned.m16n8k16.row.col.f32.bf16.bf16.f32 {%0,%1,%2,%3}, {%4,%5,%6,%7}, {%8,%9}, {%0,%1,%2,%3};"
               : "+f"(c[0]), "+f"(c[1]), "+f"(c[2]), "+f"(c[3])
               : "r"(a[0]), "r"(a[1]), "r"(a[2]), "r"(a[3]), "r"(b0), "r"(b1));
}
__device__ __forceinline__ void mma1688(float (&c)[4], uint32_t a0, uint32_t a1, uint32_t b0) {
  asm volatile("mma.sync.aligned.m16n8k8.row.col.f32.bf16.bf16.f32 {%0,%1,%2,%3}, {%4,%5}, {%6}, {%0,%1,%2,%3};"
               : "+f"(c[0]), "+f"(c[1]), "+f"(c[2]), "+f"(c[3]) : "r"(a0), "r"(a1), "r"(b0));
}
__device__ __forceinline__ uint32_t pack_bf16(float lo, float hi) {
  uint32_t r;
  asm("cvt.rn.bf16x2.f32 %0, %1, %2;" : "=r"(r) : "f"(hi), "f"(lo));
  return r;
}
__device__ __forceinline__ float bf_lo(uint32_t w) { return __uint_as_float(w << 16); }
__device__ __forceinline__ float bf_hi(uint32_t w) { return __uint_as_float(w & 0xFFFF0000u); }

__device__ __forceinline__ uint4 ld_relaxed4(const void* p) {
  uint4 v;
  asm volatile("ld.relaxed.gpu.global.v4.u32 {%0,%1,%2,%3}, [%4];" : "=r"(v.x), "=r"(v.y), "=r"(v.z), "=r"(v.w) : "l"(p) : "memory");
  return v;
}
__device__ __forceinline__ void st_relaxed4(void* p, uint32_t a, uint32_t b, uint32_t c, uint32_t d) {
  asm volatile("st.relaxed.gpu.global.v4.u32 [%0], {%1,%2,%3,%4};" ::"l"(p), "r"(a), "r"(b), "r"(c), "r"(d) : "memory");
}
__device__ __forceinline__ void st_relaxed2(void* p, uint32_t a, uint32_t b) {
  asm volatile("st.relaxed.gpu.global.v2.u32 [%0], {%1,%2};" ::"l"(p), "r"(a), "r"(b) : "memory");
}
__device__ __forceinline__ void st_relaxed1(void* p, uint32_t a) {
  asm volatile("st.relaxed.gpu.global.u32 [%0], %1;" ::"l"(p), "r"(a) : "memory");
}

__device__ __forceinline__ uint2 ld_relaxed2(const void* p) {
  uint2 v;
  asm volatile("ld.relaxed.gpu.global.v2.u32 {%0,%1}, [%2];" : "=r"(v.x), "=r"(v.y) : "l"(p) : "memory");
  return v;
}
__device__ __forceinline__ void sts64(uint32_t a, uint32_t x, uint32_t y) { asm volatile("st.shared.v2.b32 [%0], {%1,%2};" ::"r"(a), "r"(x), "r"(y) : "memory"); }
__device__ __forceinline__ uint2 lds64(uint32_t a) { uint2 v; asm volatile("ld.shared.v2.b32 {%0,%1}, [%2];" : "=r"(v.x), "=r"(v.y) : "r"(a) : "memory"); return v; }
__device__ __forceinline__ void lds128r(uint32_t (&r)[4], uint32_t a) {
  asm volatile("ld.shared.v4.b32 {%0,%1,%2,%3}, [%4];" : "=r"(r[0]), "=r"(r[1]), "=r"(r[2]), "=r"(r[3]) : "r"(a) : "memory");
}
__device__ __forceinline__ uint32_t mapa(uint32_t addr, uint32_t rank) { uint32_t r; asm volatile("mapa.shared::cluster.u32 %0, %1, %2;" : "=r"(r) : "r"(addr), "r"(rank)); return r; }
__device__ __forceinline__ void st_async1(uint32_t dst, uint32_t a, uint32_t bar) {
  asm volatile("st.async.weak.shared::cluster.mbarrier::complete_tx::bytes.b32 [%0], %1, [%2];" ::"r"(dst), "r"(a), "r"(bar) : "memory");
}
__device__ __forceinline__ void st_async2(uint32_t dst, uint32_t a, uint32_t b, uint32_t bar) {
  asm volatile("st.async.weak.shared::cluster.mbarrier::complete_tx::bytes.v2.b32 [%0], {%1,%2}, [%3];" ::"r"(dst), "r"(a), "r"(b), "r"(bar) : "memory");
}
__device__ __forceinline__ void cluster_arrive() { asm volatile("barrier.cluster.arrive.relaxed.aligned;" ::: "memory"); }
__device__ __forceinline__ void cluster_wait() { asm volatile("barrier.cluster.wait.acquire.aligned;" ::: "memory"); }

__device__ __forceinline__ void wgmma_k3_ss_ta(float (&d)[80], uint64_t da, uint64_t db, int scale_d) {
  asm volatile("{.reg .pred p; setp.ne.b32 p, %82, 0;\n"
    "wgmma.mma_async.sync.aligned.m64n160k16.f32.bf16.bf16 {%0, %1, %2, %3, %4, %5, %6, %7, %8, %9, %10, %11, %12, %13, %14, %15, %16, %17, %18, %19, %20, %21, %22, %23, %24, %25, %26, %27, %28, %29, %30, %31, %32, %33, %34, %35, %36, %37, %38, %39, %40, %41, %42, %43, %44, %45, %46, %47, %48, %49, %50, %51, %52, %53, %54, %55, %56, %57, %58, %59, %60, %61, %62, %63, %64, %65, %66, %67, %68, %69, %70, %71, %72, %73, %74, %75, %76, %77, %78, %79}, %80, %81, p, 1, 1, 1, 0;}"
    : "+f"(d[0]), "+f"(d[1]), "+f"(d[2]), "+f"(d[3]), "+f"(d[4]), "+f"(d[5]), "+f"(d[6]), "+f"(d[7]), "+f"(d[8]), "+f"(d[9]), "+f"(d[10]), "+f"(d[11]), "+f"(d[12]), "+f"(d[13]), "+f"(d[14]), "+f"(d[15]), "+f"(d[16]), "+f"(d[17]), "+f"(d[18]), "+f"(d[19]), "+f"(d[20]), "+f"(d[21]), "+f"(d[22]), "+f"(d[23]), "+f"(d[24]), "+f"(d[25]), "+f"(d[26]), "+f"(d[27]), "+f"(d[28]), "+f"(d[29]), "+f"(d[30]), "+f"(d[31]), "+f"(d[32]), "+f"(d[33]), "+f"(d[34]), "+f"(d[35]), "+f"(d[36]), "+f"(d[37]), "+f"(d[38]), "+f"(d[39]), "+f"(d[40]), "+f"(d[41]), "+f"(d[42]), "+f"(d[43]), "+f"(d[44]), "+f"(d[45]), "+f"(d[46]), "+f"(d[47]), "+f"(d[48]), "+f"(d[49]), "+f"(d[50]), "+f"(d[51]), "+f"(d[52]), "+f"(d[53]), "+f"(d[54]), "+f"(d[55]), "+f"(d[56]), "+f"(d[57]), "+f"(d[58]), "+f"(d[59]), "+f"(d[60]), "+f"(d[61]), "+f"(d[62]), "+f"(d[63]), "+f"(d[64]), "+f"(d[65]), "+f"(d[66]), "+f"(d[67]), "+f"(d[68]), "+f"(d[69]), "+f"(d[70]), "+f"(d[71]), "+f"(d[72]), "+f"(d[73]), "+f"(d[74]), "+f"(d[75]), "+f"(d[76]), "+f"(d[77]), "+f"(d[78]), "+f"(d[79])
    : "l"(da), "l"(db), "r"(scale_d));
}
__device__ __forceinline__ void wgmma_m64n32_ss_ta(float (&d)[16], uint64_t da, uint64_t db, int scale_d) {
  asm volatile("{.reg .pred p; setp.ne.b32 p, %18, 0;\n"
    "wgmma.mma_async.sync.aligned.m64n32k16.f32.bf16.bf16 {%0, %1, %2, %3, %4, %5, %6, %7, %8, %9, %10, %11, %12, %13, %14, %15}, %16, %17, p, 1, 1, 1, 0;}"
    : "+f"(d[0]), "+f"(d[1]), "+f"(d[2]), "+f"(d[3]), "+f"(d[4]), "+f"(d[5]), "+f"(d[6]), "+f"(d[7]), "+f"(d[8]), "+f"(d[9]), "+f"(d[10]), "+f"(d[11]), "+f"(d[12]), "+f"(d[13]), "+f"(d[14]), "+f"(d[15])
    : "l"(da), "l"(db), "r"(scale_d));
}

__device__ __forceinline__ void wgmma_m64n32_rs(float (&d)[16], const uint32_t (&a)[4], uint64_t db, int scale_d) {
  asm volatile("{.reg .pred p; setp.ne.b32 p, %21, 0;\n"
    "wgmma.mma_async.sync.aligned.m64n32k16.f32.bf16.bf16 {%0, %1, %2, %3, %4, %5, %6, %7, %8, %9, %10, %11, %12, %13, %14, %15}, {%16, %17, %18, %19}, %20, p, 1, 1, 0;}"
    : "+f"(d[0]), "+f"(d[1]), "+f"(d[2]), "+f"(d[3]), "+f"(d[4]), "+f"(d[5]), "+f"(d[6]), "+f"(d[7]), "+f"(d[8]), "+f"(d[9]), "+f"(d[10]), "+f"(d[11]), "+f"(d[12]), "+f"(d[13]), "+f"(d[14]), "+f"(d[15])
    : "r"(a[0]), "r"(a[1]), "r"(a[2]), "r"(a[3]), "l"(db), "r"(scale_d));
}

#define X_POS 5
#define T_STEP 2816
#define T_PHASE 1792
#define RATE0 2295
#define T_LAG 32
#define T_TOL 192
#define T_SLIP 640
#define O_FIX 5
#define NTMP 4
#define V_PRE 6
#define SFENCE(i) asm volatile("{.reg .pred p; setp.eq.u32 p, %0, %1; @p trap;}" ::"r"(n), "r"(4096 + (i)) : "memory")
constexpr int RING = 4;
constexpr uint32_t EMPTY = 0xFFFFFFFFu;
namespace xo {
constexpr uint32_t SLOT = 1u << 20, HEAD = 16384;
constexpr uint32_t VM = 512;
constexpr uint32_t PT = 1024;
constexpr uint32_t PM = 1536;
constexpr uint32_t VT = 8192;
constexpr uint32_t MEM = NH * HEAD;
constexpr uint32_t OM = MEM + 16384;
constexpr uint32_t O = RING * SLOT;
constexpr uint32_t BYTES = O + S_LEN * HD * 2;
}
__device__ __align__(1024) uint4 g_scratch[2 * (xo::BYTES / 16)];
__device__ unsigned g_epoch;
__device__ __align__(16) unsigned g_rate[128];

struct ChainMaps {
  CUtensorMap wq, wk, wv;
  CUtensorMap wo;
  CUtensorMap x, xq;
  const char* xp;
  uint32_t t_step, t_phase;
};

namespace chain {
constexpr int OFF_X = 65536;
constexpr int OFF_MEM = 131072;
constexpr int OFF_WS = 0;
constexpr int OFF_FP = 147456;
constexpr int OFF_KT = 163840;
constexpr int OFF_QT = 180224;
constexpr int OFF_VT = 196608;
constexpr int OFF_PX = 204800;
constexpr int OFF_S4 = OFF_PX + 1536;
constexpr int OFF_QM = 212992;
constexpr int OFF_KM = 215040;
constexpr int OFF_S1 = 217088;
constexpr int OFF_WVR = 0;
constexpr int OFF_WOR = 147456;
constexpr int OFF_RED = 212992;
constexpr int OFF_VPX = 221184;
constexpr int OFF_RX = 223232;
constexpr int OFF_BAR = 229376;
constexpr int BAR_X = OFF_BAR, BAR_TOK = OFF_BAR + 16, BAR_EX = OFF_BAR + 32, BAR_P = OFF_BAR + 40, GRID_TGT = OFF_BAR + 128;
constexpr int CT_BASE = GRID_TGT + 4, CT_HEAD = GRID_TGT + 8, CT_OM = GRID_TGT + 12, CT_MP = GRID_TGT + 16, CT_O = GRID_TGT + 20, CT_PF = GRID_TGT + 24;
constexpr int CT_TT = GRID_TGT + 28, CT_T = GRID_TGT + 32;
constexpr uint32_t RANK_BIT = 1u << 24;
constexpr int OFF_RX1 = OFF_BAR + 256;
constexpr int SMEM = OFF_RX1 + 2048;
constexpr uint32_t SB_LO = 1024;
constexpr float SCALE = 0.08838834764831845f, L2E = 1.4426950408889634f;
}

__device__ __forceinline__ uint32_t umax4(uint32_t a, uint32_t b, uint32_t c, uint32_t d) { return max(max(a, b), max(c, d)); }
__device__ __forceinline__ bool warp_incomplete(uint32_t m) { return __any_sync(0xffffffffu, m == EMPTY); }
#define PIN(x) asm volatile("" : "+r"(x))
#define KEEPALIVE(a, z) do { float _d0, _d1, _d2, _d3; asm volatile("mma.sync.aligned.m16n8k16.row.col.f32.bf16.bf16.f32 {%0,%1,%2,%3}, {%4,%5,%6,%7}, {%4,%5}, {%8,%8,%8,%8};" \
    : "=f"(_d0), "=f"(_d1), "=f"(_d2), "=f"(_d3) : "r"(a[0]), "r"(a[1]), "r"(a[2]), "r"(a[3]), "f"(0.f)); \
      \
    asm volatile("{.reg .pred p; setp.ne.u32 p, %0, 0; @p st.shared.f32 [%0], %1;}" ::"r"(z), "f"(_d0 + _d3) : "memory"); } while (0)
constexpr int POLL_LIMIT = 1 << 15;

__device__ __forceinline__ uint32_t keep(uint32_t x) { return __shfl_sync(0xffffffffu, x, threadIdx.x & 31); }
__device__ __forceinline__ char* gptr(uint32_t hi, uint32_t lo) { return (char*)(((uint64_t)hi << 32) | lo); }
__device__ __forceinline__ uint32_t slot_off(int n) { return ((uint32_t)n & (RING - 1)) * xo::SLOT; }
__device__ __forceinline__ float quad_max(float x) {
  const float a = __shfl_xor_sync(~0u, x, 1), b = __shfl_xor_sync(~0u, x, 2), c = __shfl_xor_sync(~0u, x, 3);
  return fmaxf(fmaxf(x, a), fmaxf(b, c));
}
__device__ __forceinline__ void acc_fence(float (&a)[16]) {
#pragma unroll
  for (int i = 0; i < 16; i++) asm volatile("" : "+f"(a[i]) :: "memory");
}
template <int NB = 1, int STRIDE = 0>
__device__ __forceinline__ void gather_issue(uint32_t dst, const char* src) {
#pragma unroll
  for (int b = 0; b < NB; b++)
#pragma unroll
    for (int i = 0; i < 4; i++) cp_async16(dst + b * STRIDE + i * 512, src + b * STRIDE + i * 512);
  cp_async_commit();
}
template <int NB, int STRIDE>
__device__ __forceinline__ bool gather_incomplete(uint32_t chk) {
  uint32_t m = 0;
#pragma unroll
  for (int b = 0; b < NB; b++) m = max(m, umax4(lds32(chk + b * STRIDE), lds32(chk + b * STRIDE + 512), lds32(chk + b * STRIDE + 1024), lds32(chk + b * STRIDE + 1536)));
  return warp_incomplete(m);
}
__device__ __forceinline__ uint32_t ld_relaxed1(const void* p) {
  uint32_t v;
  asm volatile("ld.relaxed.gpu.global.u32 %0, [%1];" : "=r"(v) : "l"(p) : "memory");
  return v;
}
__device__ __forceinline__ uint32_t gtime() { uint64_t g; asm volatile("mov.u64 %0, %%globaltimer;" : "=l"(g) :: "memory"); return (uint32_t)g; }
#define WAIT_UNTIL(t, ka, alive, id) do { \
    int _d = gtime() - (t); \
    if (__builtin_expect(_d > T_TOL, 0)) do { t += T_SLIP; _d -= T_SLIP; } while (_d > T_TOL); \
    if (alive) for (int _k = 64; _d < -96 && --_k; _d = gtime() - (t)) KEEPALIVE(ka, zr); \
    for (uint32_t _g = 0xFFFFFF80u; (int)(_d & ++_g) < 0;) _d = gtime() - (t); } while (0)
__device__ __forceinline__ void issue_x(uint32_t sb, const CUtensorMap* map, int n, int part, int q = 0) {
  asm volatile("{.reg .pred p; elect.sync _|p, 0xffffffff;\n"
               "@p cp.async.bulk.tensor.3d.shared::cluster.global.mbarrier::complete_tx::bytes [%0], [%1, {%3, %4, %5}], [%2];}"
               ::"r"(sb + chain::OFF_X + part * 32768 + q * 16384), "l"(map), "r"(sb + chain::BAR_X + 8 * part), "r"(0), "r"(n * SEG), "r"(part * 8 + q * 4) : "memory");
}
__device__ __forceinline__ void issue_x_if(uint32_t sb, const CUtensorMap* map, int n, int part, uint32_t on) {
  asm volatile("{.reg .pred p, q; elect.sync _|p, 0xffffffff; setp.ne.and.u32 q, %6, 0, p;\n"
               "@q cp.async.bulk.tensor.3d.shared::cluster.global.mbarrier::complete_tx::bytes [%0], [%1, {%3, %4, %5}], [%2];}"
               ::"r"(sb + chain::OFF_X + part * 32768), "l"(map), "r"(sb + chain::BAR_X + 8 * part), "r"(0), "r"(n * SEG), "r"(part * 8), "r"(on) : "memory");
}
__device__ __forceinline__ void prefetch_l2(const char* p, uint32_t bytes) {
  asm volatile("{.reg .pred p; elect.sync _|p, 0xffffffff; @p cp.async.bulk.prefetch.L2.global [%0], %1;}" ::"l"(p), "r"(bytes) : "memory");
}
__device__ __forceinline__ void expect_elect(uint32_t bar, uint32_t bytes) {
  asm volatile("{.reg .pred p; elect.sync _|p, 0xffffffff; @p mbarrier.arrive.expect_tx.shared::cta.b64 _, [%0], %1;}" ::"r"(bar), "r"(bytes) : "memory");
}
template <int WG> __device__ __forceinline__ constexpr uint64_t xdesc(int ks) {
  return (uint64_t)(((chain::SB_LO + chain::OFF_X + WG * 32768 + (ks >> 2) * 4096 + (ks & 3) * 32) >> 4) + (1u << 16)) |
         ((uint64_t)(64u | (1u << 30)) << 32);
}
template <int WG> __device__ __forceinline__ constexpr uint64_t wdesc(int o, int ks) {
  return (uint64_t)(((chain::SB_LO + chain::OFF_WS + WG * 32768 + o * 16384 + ks * 2048) >> 4) + (1u << 16)) | ((uint64_t)(64u | (1u << 30)) << 32);
}
__device__ __forceinline__ void load_mem0(uint2 (&m)[8], const bf16* __restrict__ mem0) {
#pragma unroll
  for (int r = 0; r < 8; r++) m[r] = ld_relaxed2((const uint2*)(mem0 + r * DM) + threadIdx.x);
}
__device__ __forceinline__ void store_mem0(uint32_t sb, const uint2 (&m)[8]) {
  const uint32_t d = sb + chain::OFF_MEM + threadIdx.x * 64;
  sts128(d, make_uint4(__byte_perm(m[0].x, m[1].x, 0x5410), __byte_perm(m[2].x, m[3].x, 0x5410), __byte_perm(m[4].x, m[5].x, 0x5410), __byte_perm(m[6].x, m[7].x, 0x5410)));
  sts128(d + 16, make_uint4(__byte_perm(m[0].x, m[1].x, 0x7632), __byte_perm(m[2].x, m[3].x, 0x7632), __byte_perm(m[4].x, m[5].x, 0x7632), __byte_perm(m[6].x, m[7].x, 0x7632)));
  sts128(d + 32, make_uint4(__byte_perm(m[0].y, m[1].y, 0x5410), __byte_perm(m[2].y, m[3].y, 0x5410), __byte_perm(m[4].y, m[5].y, 0x5410), __byte_perm(m[6].y, m[7].y, 0x5410)));
  sts128(d + 48, make_uint4(__byte_perm(m[0].y, m[1].y, 0x7632), __byte_perm(m[2].y, m[3].y, 0x7632), __byte_perm(m[4].y, m[5].y, 0x7632), __byte_perm(m[6].y, m[7].y, 0x7632)));
}
template <int K> __device__ __forceinline__ uint32_t loop_zero(int n) { uint32_t z; asm volatile("shr.u32 %0, %1, %2;" : "=r"(z) : "r"(n), "n"(16 + K)); return z; }
#define NEWZ(k) zr = loop_zero<k>(n)

template <int WG>
__device__ __forceinline__ void role_a(const ChainMaps& maps, const bf16* __restrict__ mem0, const uint32_t sb, const uint32_t xbase_hi) {
  using namespace chain;
  const int h = blockIdx.x >> 2;
  const bool J = sb >= RANK_BIT;
  const uint32_t u16 = (threadIdx.x & 96) * 64 + (threadIdx.x & 31) * 16;
  const uint32_t t16 = keep(u16), l16 = keep((threadIdx.x & 31) * 16);
  const uint32_t a_wl = keep((((threadIdx.x >> 4) & 1) * 8 + (threadIdx.x & 7)) * 128 + (((((threadIdx.x >> 4) & 6) + ((threadIdx.x >> 3) & 1)) ^ (threadIdx.x & 7)) << 4));
  const uint32_t xhi = keep(xbase_hi + (t16 >> 16));
#define xh (lds32(sb + CT_HEAD) + t16)
#define xm (lds32(sb + CT_BASE) + t16 + xo::MEM)
#define last_warp __any_sync(0xffffffffu, tv >= 6144)
#define tv (t16 ^ zr)
  const CUtensorMap* wm = J ? &maps.wk : &maps.wq;

  uint32_t aW[2][24][4];
  uint2 m0[8];
  load_mem0(m0, mem0);
  mbar_wait(sb + BAR_P, 0);
#pragma unroll
  for (int ks = 0; ks < 24; ks++) ldsm_x4_t(aW[0][ks], sb + a_wl + OFF_X + WG * 49152 + ks * 2048);
  named_bar(0, 256);
  if (WG == 1 && __any_sync(0xffffffffu, t16 >= 6144)) {
    fence_async_smem();
    if (l16 == 0) {
      mbar_expect_tx(sb + BAR_P + 16, 2 * 16384);
      for (int q = 0; q < 2; q++) tma_load_2d(sb + OFF_X + (4 + q) * 16384, wm, h * DH + (q ^ 1) * 64, q * 512 + 256, sb + BAR_P + 16);
    }
    __syncwarp();
    expect_elect(sb + BAR_X, 32768); expect_elect(sb + BAR_X + 8, 32768); expect_elect(sb + BAR_TOK, 8192);
    issue_x(sb, &maps.x, 0, 0); issue_x(sb, &maps.x, 0, 1);
  }
  mbar_wait(sb + BAR_P + 8, 0);
#pragma unroll
  for (int ks = 0; ks < 16; ks++) ldsm_x4_t(aW[1][ks], sb + a_wl + OFF_X + 6 * 16384 + WG * 32768 + ks * 2048);
  mbar_wait(sb + BAR_P + 16, 0);
#pragma unroll
  for (int ks = 0; ks < 8; ks++) ldsm_x4_t(aW[1][16 + ks], sb + a_wl + OFF_X + (4 + WG) * 16384 + ks * 2048);
  named_bar(0, 256);
  cluster_arrive();
  store_mem0(sb, m0);
  mbar_wait(sb + BAR_P + 24, 0);
  cluster_wait();
  const uint32_t rsb = sb ^ RANK_BIT;
  const uint32_t a_ws = sb + a_wl + OFF_WS + WG * 32768;

  uint32_t ws[2][4][4];
  auto load_ws = [&]() {
#pragma unroll
    for (int q = 0; q < 2; q++) {
      const uint32_t a = a_ws + q * 4096;
      ldsm_x4_t(ws[q][0], a); ldsm_x4_t(ws[q][1], a + 16384); ldsm_x4_t(ws[q][2], a + 2048); ldsm_x4_t(ws[q][3], a + 16384 + 2048);
    }
  };
  uint32_t tref = 0;
#pragma unroll 1
  for (int n = 0; n <= (J ? NSEG : NSEG - 1); n++) {
#define s (n - 1)
#define sv ((int)(n ^ zr) - 1)
    const bool more = __builtin_expect(s + 1 < NSEG, 1);
    uint32_t zr = loop_zero<0>(n);
#define wq ((int)(tv >> 11))
#define lv (l16 ^ zr)
#define gh (xh + slot_off(sv))
    uint32_t tmp[NTMP][4];
    auto load_tmp = [&](int o) {
#pragma unroll
      for (int ks = 0; ks < NTMP; ks++) ldsm_x4_t(tmp[ks], a_ws + o * 16384 + ks * 2048);
    };
    auto wait_x = [&]() { mbar_wait<0>(sb + BAR_X + 8 * WG, n & 1); };
    if (__builtin_expect(s < 0, 0)) { load_tmp(1); wait_x(); }
    else {
      {
        if (WG == 1) { if (__builtin_expect(s > 0, 1)) {
          const uint32_t dst = sb + OFF_MEM + tv + t16 - l16, chk = dst + ((lv >> 5) & 12);
          uint32_t tries = zr;
#pragma unroll 1
          do {
            if (tries) {
              const char* src = gptr(xhi, xm + t16 - l16 + slot_off(sv));
              tref += T_SLIP;
              WAIT_UNTIL(tref, aW[0][0], 1, -1);
              gather_issue<2, 2048>(dst, src);
            }
            KEEPALIVE(aW[0][0], zr);
            cp_async_wait_group<0>();
          } while (gather_incomplete<2, 2048>(chk) && ++tries < POLL_LIMIT);
        } } else if (J == 0) {
          uint32_t tries = s == 0;
#pragma unroll 1
          do {
            if (tries) gather_issue(sb + OFF_VT + tv, gptr(xhi, gh) + xo::VT);
            cp_async_wait_group<0>();
          } while (gather_incomplete<1, 0>(sb + OFF_VT + t16 + ((lv >> 5) & 12)) && ++tries < POLL_LIMIT);
        }
        named_bar(1, 256);
      }
      float c[2][2][4];
#pragma unroll
      for (int i = 0; i < 4; i++) c[i >> 1][i & 1][0] = c[i >> 1][i & 1][1] = c[i >> 1][i & 1][2] = c[i >> 1][i & 1][3] = 0.f;
      {
        const uint32_t a_mem = sb + OFF_MEM + WG * 8192 + l16;
        uint32_t b[4][4];
        bool tok;
        constexpr int PR[16] = {12, 13, 0, 1, 2, 3, 4, 14, 5, 6, 7, 8, 9, 15, 10, 11};
        ldsm_x4_t(b[0], a_mem + PR[0] * 512); ldsm_x4_t(b[1], a_mem + PR[1] * 512);
#pragma unroll
        for (int i = 0; i < 16; i++) {
          if ((i & 1) == 0 && i < 14) {
            ldsm_x4_t(b[(i + 2) & 3], a_mem + PR[i + 2] * 512); ldsm_x4_t(b[(i + 3) & 3], a_mem + PR[i + 3] * 512);
            if (i == 2 || i == 8) { ldsm_x4_t(ws[1][0], a_ws + (i == 2 ? 2 : 3) * 4096); ldsm_x4_t(ws[1][1], a_ws + (i == 2 ? 2 : 3) * 4096 + 16384); }
            if (i == 4 || i == 10) { ldsm_x4_t(ws[1][2], a_ws + (i == 4 ? 2 : 3) * 4096 + 2048); ldsm_x4_t(ws[1][3], a_ws + (i == 4 ? 2 : 3) * 4096 + 16384 + 2048); }
          }
          const int p = PR[i];
          if (p >= 12) {
            const int z = i != 0;
            mma16816(c[0][0], ws[z][0], b[i & 3][0], b[i & 3][1]); mma16816(c[1][0], ws[z][1], b[i & 3][0], b[i & 3][1]);
            mma16816(c[0][1], ws[z][2], b[i & 3][2], b[i & 3][3]); mma16816(c[1][1], ws[z][3], b[i & 3][2], b[i & 3][3]);
          } else {
            mma16816(c[1][0], aW[1][2 * p], b[i & 3][0], b[i & 3][1]); mma16816(c[1][1], aW[1][2 * p + 1], b[i & 3][2], b[i & 3][3]);
            mma16816(c[0][0], aW[0][2 * p], b[i & 3][0], b[i & 3][1]); mma16816(c[0][1], aW[0][2 * p + 1], b[i & 3][2], b[i & 3][3]);
          }
          if (i == 12) tok = mbar_test(sb + BAR_TOK + 8 * (s & 1), (s >> 1) & 1);
          if (i == 15 && __builtin_expect(!tok, 0)) mbar_wait(sb + BAR_TOK + 8 * (s & 1), (s >> 1) & 1);
          if (i == X_POS + 4 * (1 - WG)) { issue_x_if(sb, &maps.x, s + 1, WG, t16 >= 6144 && more); if (WG) __syncwarp(); }
        }
      }
      sts128f(sb + OFF_PX + WG * 512 + t16, make_float4(c[1][0][0] + c[1][1][0], c[1][0][1] + c[1][1][1], c[1][0][2] + c[1][1][2], c[1][0][3] + c[1][1][3]));
      const float4 own = make_float4(c[0][0][0] + c[0][1][0], c[0][0][1] + c[0][1][1], c[0][0][2] + c[0][1][2], c[0][0][3] + c[0][1][3]);
      NEWZ(1);
      uint32_t a = (J ? OFF_KM : OFF_QM) + WG * 1024 + wq * 256 + (lv >> 2);
      uint32_t ra = rsb + a, ra2 = ra + 128, rx = rsb + BAR_EX + zr;
      PIN(a); PIN(ra); PIN(ra2); PIN(rx);
      const uint32_t kt = sb + OFF_KT + (s & 1) * 8192;
#define k_lane ((lv & 240) + ((lv & 256) << 2))
#define a_lane (((lv & 128) << 1) + ((lv & 256) >> 1) + (lv & 112))
      uint32_t kb[4][4], aq = sb + OFF_QM + a_lane;
      PIN(aq);
      SFENCE(16);
      named_bar(3, 256);
      {
        const float4 o = lds128f(sb + OFF_PX + (WG ^ 1) * 512 + t16);
        const uint32_t lo = pack_bf16(own.x + o.x, own.y + o.y), hi = pack_bf16(own.z + o.z, own.w + o.w);
        if (J == 1 && more) { st_async1(ra, lo, rx); st_async1(ra2, hi, rx); }
        sts32(sb + a, lo); sts32(sb + a + 128, hi);
      }
      if (J == 0) {
        uint32_t am[4][4];
        uint2 vm0, vm1;
        const char* pvm = WG == 0 ? gptr(xhi, gh - (lv >> 1)) + xo::VM : nullptr;
        if (WG == 1) {
#pragma unroll
          for (int p = 0; p < 4; p++) ldsm_x4(kb[p], kt + wq * 256 + k_lane + p * 2048);
        }
        named_bar(7, 256);
#pragma unroll
        for (int p = 0; p < 4; p++) ldsm_x4_t(am[p], aq + p * 512);
        auto scores = [&]() {
          float c0[2][4], c1[2][4];
#pragma unroll
          for (int i = 0; i < 2; i++) { c0[i][0] = c0[i][1] = c0[i][2] = c0[i][3] = 0.f; c1[i][0] = c1[i][1] = c1[i][2] = c1[i][3] = 0.f; }
#pragma unroll
          for (int p = 0; p < 4; p++) { mma16816(c0[p & 1], am[p], kb[p][0], kb[p][1]); mma16816(c1[p & 1], am[p], kb[p][2], kb[p][3]); }
          const uint32_t r1 = pack_bf16((c0[0][0] + c0[1][0]) + (c1[0][2] + c1[1][2]), (c0[0][1] + c0[1][1]) + (c1[0][3] + c1[1][3]));
          return pack_bf16(bf_lo(r1) * SCALE, bf_hi(r1) * SCALE);
        };
        if (WG == 1) {
          const uint32_t st = scores();
          uint32_t vb[4][4];
          sts32(sb + OFF_S4 + l16 + wq * 4, st);
          named_bar(8, 128);
          const uint4 sc = lds128(sb + OFF_S4 + l16);
          float x[8] = {bf_lo(sc.x), bf_hi(sc.x), bf_lo(sc.y), bf_hi(sc.y), bf_lo(sc.z), bf_hi(sc.z), bf_lo(sc.w), bf_hi(sc.w)};
          float mx = fmaxf(fmaxf(fmaxf(x[0], x[1]), fmaxf(x[2], x[3])), fmaxf(fmaxf(x[4], x[5]), fmaxf(x[6], x[7])));
          {
            const uint32_t va = sb + OFF_VT + t16 + (sc.x & zr);
#pragma unroll
            for (int e = 0; e < 4; e++) lds128r(vb[e], va + e * 512);
          }
          mx = quad_max(mx);
          const float mb = mx * L2E;
#pragma unroll
          for (int i = 0; i < 8; i++) x[i] = ex2(fmaf(x[i], L2E, -mb));
          uint32_t pa[4], pb[4];
          asm volatile("" : "=r"(pa[1]), "=r"(pa[3]), "=r"(pb[1]), "=r"(pb[3]));
          pa[0] = pack_bf16(x[0], x[1]); pa[2] = pack_bf16(x[2], x[3]);
          pb[0] = pack_bf16(x[4], x[5]); pb[2] = pack_bf16(x[6], x[7]);
          float oa[4][4];
#pragma unroll
          for (int e = 0; e < 4; e++) { oa[e][0] = oa[e][1] = oa[e][2] = oa[e][3] = 0.f; mma16816(oa[e], pa, vb[e][0], vb[e][1]); }
#pragma unroll
          for (int e = 0; e < 4; e++) mma16816(oa[e], pb, vb[e][2], vb[e][3]);
          sts64(sb + OFF_PX + 1024 + t16, __float_as_uint(mx), __float_as_uint(((x[0] + x[1]) + (x[2] + x[3])) + ((x[4] + x[5]) + (x[6] + x[7]))));
          sts128f(sb + OFF_PX + t16, make_float4(oa[0][0], oa[0][1], oa[1][0], oa[1][1]));
          sts128f(sb + OFF_PX + 512 + t16, make_float4(oa[2][0], oa[2][1], oa[3][0], oa[3][1]));
          named_bar_arrive(9, 256);
          wait_x();
          load_tmp(1);
        } else {
          const uint32_t xo0 = lds32(sb + CT_OM) + wq * 512 + l16;
          mbar_wait<0>(sb + BAR_EX, s & 1);
          vm0 = ld_relaxed2(pvm); vm1 = ld_relaxed2(pvm + 256);
#pragma unroll
          for (int p = 0; p < 4; p++) ldsm_x4_t(kb[p], sb + OFF_KM + p * 512 + l16);
          const uint32_t sm = scores();
          float mx = quad_max(fmaxf(bf_lo(sm), bf_hi(sm)));
          auto check_vm = [&]() {
            if (__builtin_expect(warp_incomplete(max(vm0.x, vm1.x)), 0)) {
              uint32_t tries = zr;
#pragma unroll 1
              do { vm0 = ld_relaxed2(pvm); vm1 = ld_relaxed2(pvm + 256); } while (warp_incomplete(max(vm0.x, vm1.x)) && ++tries < POLL_LIMIT);
            }
          };
          SFENCE(25);
          named_bar(9, 256);
          const uint2 ms = lds64(sb + OFF_PX + 1024 + t16);
          const float4 t0 = lds128f(sb + OFF_PX + t16), t1 = lds128f(sb + OFF_PX + 512 + t16);
          mx = fmaxf(mx, __uint_as_float(ms.x));
          const float mb = mx * L2E;
          const float e0 = ex2(fmaf(bf_lo(sm), L2E, -mb)), e1 = ex2(fmaf(bf_hi(sm), L2E, -mb)), ct = ex2(fmaf(__uint_as_float(ms.x), L2E, -mb));
          uint32_t p4 = pack_bf16(e0, e1), p5;
          asm volatile("" : "=r"(p5));
          float sx = fmaf(ct, __uint_as_float(ms.y), e0 + e1);
          float oa[4][4] = {{t0.x * ct, t0.y * ct, 0.f, 0.f}, {t0.z * ct, t0.w * ct, 0.f, 0.f}, {t1.x * ct, t1.y * ct, 0.f, 0.f}, {t1.z * ct, t1.w * ct, 0.f, 0.f}};
          const float s1 = __shfl_xor_sync(~0u, sx, 1), s2 = __shfl_xor_sync(~0u, sx, 2), s3 = __shfl_xor_sync(~0u, sx, 3);
          check_vm();
          mma1688(oa[0], p4, p5, vm0.x); mma1688(oa[1], p4, p5, vm0.y); mma1688(oa[2], p4, p5, vm1.x); mma1688(oa[3], p4, p5, vm1.y);
          const float rx = rcp((sx + s1) + (s2 + s3));
          st_relaxed4(gptr(xhi, xo0 + slot_off(sv)), pack_bf16(oa[0][0] * rx, oa[0][1] * rx), pack_bf16(oa[1][0] * rx, oa[1][1] * rx),
                      pack_bf16(oa[2][0] * rx, oa[2][1] * rx), pack_bf16(oa[3][0] * rx, oa[3][1] * rx));
          SFENCE(24);
          named_bar_arrive(10, 256);
          st_relaxed4(gptr(xhi, xo0 + slot_off(sv + 3)), EMPTY, EMPTY, EMPTY, EMPTY);
          load_tmp(1);
          wait_x();
        }
      } else {
        bool xok;
        {
          const int mt = WG | (wq == 3), ktile = wq == 3 ? 2 + WG : wq - 1;
          const uint32_t qt = sb + OFF_QT + (s & 1) * 8192 + mt * 512 + a_lane;
          uint32_t q[8][4];
          if (__any_sync(0xffffffffu, tv < 2048)) {
            named_bar(7, 256);
#pragma unroll
            for (int p = 0; p < 4; p++) ldsm_x4_t(kb[p], sb + OFF_KM + p * 512 + l16);
          } else {
            named_bar_arrive(7, 256);
#pragma unroll
            for (int p = 0; p < 4; p++) ldsm_x4(kb[p], kt + ktile * 256 + k_lane + p * 2048);
          }
#pragma unroll
          for (int i = 0; i < 8; i++) ldsm_x4(q[i], qt + i * 1024);
          __syncwarp();
          float c0[4][4];
#pragma unroll
          for (int i = 0; i < 4; i++) { c0[i][0] = c0[i][1] = c0[i][2] = c0[i][3] = 0.f; mma16816(c0[i], q[i], kb[i >> 1][(i & 1) * 2], kb[i >> 1][(i & 1) * 2 + 1]); }
#pragma unroll
          for (int i = 0; i < 4; i++) mma16816(c0[i], q[4 + i], kb[2 + (i >> 1)][(i & 1) * 2], kb[2 + (i >> 1)][(i & 1) * 2 + 1]);
          load_tmp(1);
          xok = mbar_test(sb + BAR_X + 8 * WG, n & 1);
          NEWZ(3);
          const uint32_t r0 = pack_bf16((c0[0][0] + c0[1][0]) + (c0[2][0] + c0[3][0]), (c0[0][1] + c0[1][1]) + (c0[2][1] + c0[3][1]));
          const uint32_t r1 = pack_bf16((c0[0][2] + c0[1][2]) + (c0[2][2] + c0[3][2]), (c0[0][3] + c0[1][3]) + (c0[2][3] + c0[3][3]));
          const uint32_t sa = wq == 0 ? sb + OFF_S1 + (lv >> 2) + mt * 256 : sb + OFF_S4 + l16 + mt * 4096 + ktile * 4;
          sts32(sa, pack_bf16(bf_lo(r0) * SCALE, bf_hi(r0) * SCALE));
          sts32(sa + (wq == 0 ? 128 : 2048), pack_bf16(bf_lo(r1) * SCALE, bf_hi(r1) * SCALE));
        }
        if (WG == 1) named_bar_arrive(8, 256);
        else {
          if (more) named_bar_arrive(10, 256);
          const uint32_t gp = gh;
          named_bar(8, 256);
          const uint4 sc = lds128(sb + OFF_S4 + t16); const uint32_t s1 = lds32(sb + OFF_S1 + wq * 128 + (lv >> 2));
          float y[10] = {bf_lo(s1), bf_hi(s1), bf_lo(sc.x), bf_hi(sc.x), bf_lo(sc.y), bf_hi(sc.y), bf_lo(sc.z), bf_hi(sc.z), bf_lo(sc.w), bf_hi(sc.w)};
          const int rel = wq * 8 + (int)(lv >> 6) - (int)((lv >> 3) & 6);
          const float NEG = -999292928.f;
#pragma unroll
          for (int e = 0; e < 4; e++) {
            if (e * 8 > rel) y[2 * e + 2] = NEG;
            if (e * 8 + 1 > rel) y[2 * e + 3] = NEG;
          }
          float my = fmaxf(fmaxf(fmaxf(y[0], y[1]), fmaxf(y[2], y[3])), fmaxf(fmaxf(y[4], y[5]), fmaxf(y[6], y[7])));
          my = quad_max(fmaxf(my, fmaxf(y[8], y[9])));
#pragma unroll
          for (int i = 0; i < 10; i++) y[i] = ex2((y[i] - my) * L2E);
          float sy = ((y[0] + y[1]) + (y[2] + y[3])) + ((y[4] + y[5]) + (y[6] + y[7])) + (y[8] + y[9]);
          const float ry = rcp((sy + __shfl_xor_sync(~0u, sy, 1)) + (__shfl_xor_sync(~0u, sy, 2) + __shfl_xor_sync(~0u, sy, 3)));
          st_relaxed4(gptr(xhi, gp) + xo::PT, pack_bf16(y[2] * ry, y[3] * ry), pack_bf16(y[4] * ry, y[5] * ry), pack_bf16(y[6] * ry, y[7] * ry), pack_bf16(y[8] * ry, y[9] * ry));
          const uint32_t l12 = lv - (lv >> 2);
          st_relaxed1(gptr(xhi, gp - l12) + xo::PM, pack_bf16(y[0] * ry, y[1] * ry));
        }
        if (!xok && more) wait_x();
      }
    }
    if (more) {
      float acc[16];
      const uint32_t xph = (s + 1) & 1;
      auto batch = [&](const uint32_t (&a)[24][4], int o) {
        wg_fence();
#pragma unroll
        for (int ks = NTMP; ks < 8; ks++) wgmma_m64n32_ss_ta(acc, wdesc<WG>(o, ks), xdesc<WG>(24 + ks), ks != NTMP);
#pragma unroll
        for (int ks = 0; ks < NTMP; ks++) wgmma_m64n32_rs(acc, tmp[ks], xdesc<WG>(24 + ks), 1);
#pragma unroll
        for (int ks = 0; ks < 24; ks++) wgmma_m64n32_rs(acc, a[ks], xdesc<WG>(ks), 1);
        wg_commit();
        SFENCE(50 + o);
      };
      if (WG == 0) named_bar(12, 256);
      else if (__builtin_expect(s >= 0, 1)) named_bar(10, 256);
      batch(aW[1], 1);
      named_bar_arrive(WG ? 12 : 13, 256);
      wg_wait<0>();
      acc_fence(acc);
      load_tmp(0);
#pragma unroll
      for (int i = 0; i < 4; i++) sts128f(sb + OFF_FP + WG * 8192 + t16 + i * 512, make_float4(acc[4 * i], acc[4 * i + 1], acc[4 * i + 2], acc[4 * i + 3]));
      NEWZ(4);
      if (WG == 0 && s >= 0) {
        const uint32_t g1 = xh + slot_off(sv + 1);
        if (J == 0) gather_issue(sb + OFF_VT + tv, gptr(xhi, g1) + xo::VT);
        else {
          st_relaxed4(gptr(xhi, g1) + xo::PT, EMPTY, EMPTY, EMPTY, EMPTY);
          st_relaxed1(gptr(xhi, g1 - lv + (lv >> 2)) + xo::PM, EMPTY);
        }
      }
      uint32_t esrc = 0;
      if (WG == 1) { esrc = xm + t16 - l16 + 2048 + slot_off(sv + 1); tref += lds32(sb + CT_T); }
      named_bar(WG ? 13 : 14, 256);
      batch(aW[0], 0);
      NEWZ(5);
      if (WG == 1) {
        named_bar(14, 256);
        if (last_warp && s + 2 < NSEG) {
          expect_elect(sb + BAR_TOK + 8 * (xph ^ 1), 8192); expect_elect(sb + BAR_X, 32768); expect_elect(sb + BAR_X + 8, 32768);
          if (J == 0) expect_elect(sb + BAR_EX, 2048);
          if (s == NSEG - 3) asm volatile("griddepcontrol.launch_dependents;");
        }
      }
      const uint32_t tb = lds32(sb + CT_TT) + xph * 8192 + WG * 4096 + ((tv + l16) >> 1);
      float4 oth[4];
#pragma unroll
      for (int i = 0; i < 4; i++) oth[i] = lds128f(sb + OFF_FP + (WG ^ 1) * 8192 + t16 + i * 512);
      if (WG == 1 && __builtin_expect(s >= 0, 1)) {
        const uint32_t edst = sb + OFF_MEM + tv + t16 - l16;
        WAIT_UNTIL(tref, aW[0][0], 0, J ? 7 : 0);
        gather_issue<2, 2048>(edst, gptr(xhi, esrc) - 2048);
      }
      wg_wait<0>();
      acc_fence(acc);
      uint32_t lt[4], ht[4];
#pragma unroll
      for (int i = 0; i < 4; i++) {
        const float4 o = oth[i];
        lt[i] = pack_bf16(acc[4 * i] + o.x, acc[4 * i + 1] + o.y); ht[i] = pack_bf16(acc[4 * i + 2] + o.z, acc[4 * i + 3] + o.w);
      }
      stsm_x4_t(tb, lt[0], ht[0], lt[1], ht[1]); stsm_x4_t(tb + 512, lt[2], ht[2], lt[3], ht[3]);
      NEWZ(6);
      if (WG == 0 && last_warp) {
        load_ws();
        named_bar(11, 256);
        fence_async_smem();
        const uint32_t tt = (J ? OFF_KT : OFF_QT) + xph * 8192;
        asm volatile("{.reg .pred p; elect.sync _|p, 0xffffffff;\n"
                     "@p cp.async.bulk.shared::cluster.shared::cta.mbarrier::complete_tx::bytes [%0], [%1], 8192, [%2];}"
                     ::"r"(rsb + tt), "r"(sb + tt), "r"(rsb + BAR_TOK + 8 * xph) : "memory");
      } else {
        named_bar_arrive(11, 256);
        load_ws();
      }
    }
    if (!more) break;
    if (__builtin_expect(s < 0, 0)) {
      tref = gtime() / T_SLIP * T_SLIP - T_SLIP;
    }
  }
  cp_async_wait_group<0>();
  if (J == 0) mbar_wait(sb + BAR_TOK + 8, 1);
}

template <int WG>
__device__ __forceinline__ void role_v(const ChainMaps& maps, const bf16* __restrict__ mem0, const uint32_t sb, const uint32_t xbase_hi) {
  using namespace chain;
  const int h = blockIdx.x >> 2;
  const uint32_t u16 = (threadIdx.x & 96) * 64 + (threadIdx.x & 31) * 16;
  const uint32_t t16 = keep(u16), l16 = keep((threadIdx.x & 31) * 16);
  const uint32_t xhi = keep(xbase_hi + (t16 >> 16));
#define j (sb >> 24)
  auto wv_addr = [&](uint32_t t) { return WG * 32768 + ((t & 256) << 2) + ((t & 112) << 3) + ((((t >> 6) & 96) + ((t >> 3) & 16)) ^ (t & 112)); };
  auto wo_addr = [&](uint32_t t) { return OFF_WOR + WG * 32768 + ((t & 6144) << 2) + ((t & 256) << 1) + ((t & 112) << 2) + ((((j ^ 1) << 5) + ((t >> 3) & 16)) ^ ((t >> 1) & 48)); };
#define ovt (((tv + l16) >> 1) + (xo::VT + WG * 512 + j * 4096))
#define ovm (((tv & 4096) >> 1) + ((tv & 2048) >> 3) + (lv >> 1) + (xo::VM + j * 4096))
#define xvt (lds32(sb + CT_HEAD) + ovt)
#define xvm (lds32(sb + CT_HEAD) + ovm)
#define xom (lds32(sb + CT_OM) + t16 + WG * 8192)
#define warp_is(q) __any_sync(0xffffffffu, (tv >> 11) == (q))
#define upper_warps (WG == 1 || __any_sync(0xffffffffu, tv >= 4096))

  uint32_t aV[16][4];
  uint32_t aO[16][4];
  uint32_t bO[16][4];
  uint32_t rot[16][4];
  if (WG == 1 && __any_sync(0xffffffffu, t16 >= 6144)) {
    expect_elect(sb + BAR_X, 32768); expect_elect(sb + BAR_X + 8, 32768);
    issue_x(sb, &maps.x, 0, 0); issue_x(sb, &maps.x, 0, 1);
    prefetch_l2(maps.xp + 65536 + (h * 2 + j) * 3072, 3072);
  }
  cluster_arrive();
  { uint2 m0[8]; load_mem0(m0, mem0); store_mem0(sb, m0); }
  mbar_wait(sb + BAR_P, 0);
#pragma unroll
  for (int ks = 0; ks < 16; ks++) ldsm_x4_t(aV[ks], sb + wv_addr(t16) + OFF_WOR + ks * 2048);
  auto load_v = [&](uint32_t t) {
#pragma unroll
    for (int ks = 0; ks < 16; ks++) ldsm_x4_t(rot[ks], sb + wv_addr(t) + OFF_WVR + ks * 2048);
  };
  load_v(t16);
  named_bar(0, 256);
  if (threadIdx.x == 0) {
    fence_async_smem();
    mbar_expect_tx(sb + BAR_P + 8, 4 * 16384);
    for (int q = 0; q < 4; q++) tma_load_2d(sb + OFF_WOR + q * 16384, &maps.wo, h * 32, j * 2048 + q * 256, sb + BAR_P + 8);
    for (int q = 0; q < 4; q++) tma_prefetch_2d(&maps.wo, h * 32, j * 2048 + 1024 + q * 256);
  }
  __syncwarp();
  cluster_wait();
  const uint32_t rsb = sb ^ RANK_BIT;

  uint32_t tref = 0;
#pragma unroll 1
  for (int n = 0; n <= NSEG; n++) {
    const bool more = __builtin_expect(s + 1 < NSEG, 1);
    uint32_t zr = loop_zero<0>(n);
    bool xok = false;
    if (__builtin_expect(s >= 0, 1)) {
      if (__builtin_expect(s > 0, 1)) {
        const uint32_t dst = sb + OFF_MEM + WG * 8192 + t16 + ((lv >> 5) & 12);
        uint32_t tries = zr;
#pragma unroll 1
        do {
          if (tries) { const char* src = gptr(xhi, xm + WG * 8192 + slot_off(sv)); tref += T_SLIP; WAIT_UNTIL(tref, aV[0], 1, -1); gather_issue(sb + OFF_MEM + WG * 8192 + tv, src); }
          KEEPALIVE(aV[0], zr);
          cp_async_wait_group<0>();
        } while (gather_incomplete<1, 0>(dst) && ++tries < POLL_LIMIT);
        named_bar(1 + WG, 128);
      }
      const uint32_t a_mem = sb + OFF_MEM + WG * 8192 + l16;
      float c[2][4];
      c[0][0] = c[0][1] = c[0][2] = c[0][3] = c[1][0] = c[1][1] = c[1][2] = c[1][3] = 0.f;
      constexpr int NBUF = (48 - 8 - 4 * O_FIX) / 4;
      uint32_t b[NBUF][4];
#pragma unroll
      for (int p = 0; p < NBUF - 1; p++) ldsm_x4_t(b[p], a_mem + p * 512);
#pragma unroll
      for (int p = 0; p < 16; p++) {
        if (p + NBUF - 1 < 16) ldsm_x4_t(b[(p + NBUF - 1) % NBUF], a_mem + (p + NBUF - 1) * 512);
        if (p < 8) { mma16816(c[0], aV[2 * p], b[p % NBUF][0], b[p % NBUF][1]); mma16816(c[1], aV[2 * p + 1], b[p % NBUF][2], b[p % NBUF][3]); }
        else { mma16816(c[0], rot[2 * p - 16], b[p % NBUF][0], b[p % NBUF][1]); mma16816(c[1], rot[2 * p - 15], b[p % NBUF][2], b[p % NBUF][3]); }
      }
      xok = mbar_test(sb + BAR_X + 8 * WG, n & 1);
      SFENCE(15);
      const float4 own = make_float4(c[0][0] + c[1][0], c[0][1] + c[1][1], c[0][2] + c[1][2], c[0][3] + c[1][3]);
      NEWZ(1);
      const uint32_t pvm = WG == 0 ? xvm + slot_off(sv) : 0;
      if (WG == 1) sts128f(sb + OFF_VPX + wq * 512 + l16, own);
      named_bar(3, 256);
      if (WG == 0) {
        const float4 o = lds128f(sb + OFF_VPX + wq * 512 + l16);
        st_relaxed2(gptr(xhi, pvm), pack_bf16(own.x + o.x, own.y + o.y), pack_bf16(own.z + o.z, own.w + o.w));
      }
    }
    auto token_pv = [&](int seg, bool staged) {
      constexpr int NU = 2 - WG;
      uint4 pt0, pt1, v0[NU], v1[NU]; uint32_t pm0, pm1; uint2 vm[NU];
      const uint32_t ap = l16 + WG * 4096 + xo::PT, am = (lv >> 2) + WG * 4096 + xo::PM;
      const uint32_t at = ovt - WG * 512;
      if (staged) {
        const uint32_t b = sb + OFF_MEM;
        pt0 = lds128(b + ap); pt1 = lds128(b + ap + 2048); pm0 = lds32(b + am); pm1 = lds32(b + am + 2048);
#pragma unroll
        for (int u = 0; u < NU; u++) { v0[u] = lds128(b + at - u * 2048); v1[u] = lds128(b + at + 512 - u * 2048); vm[u] = lds64(b + ovm - u * 2048); }
      } else {
        const uint32_t b = lds32(sb + CT_HEAD) + slot_off(seg);
        pt0.x = EMPTY;
#pragma unroll
        for (int u = 0; u < NU; u++) {
          v0[u] = ld_relaxed4(gptr(xhi, b + at) - u * 2048); v1[u] = ld_relaxed4(gptr(xhi, b + at) + 512 - u * 2048);
          vm[u] = ld_relaxed2(gptr(xhi, b + ovm) - u * 2048);
        }
      }
      const bool odd = lv & 16;
      char* op = gptr(xhi, lds32(sb + CT_O) + (seg * SEG + WG * 16 + (lv >> 6)) * (HD * 2) + wq * 32 + (lv & 16) + ((lv >> 2) & 8));
      if (!staged || __builtin_expect(warp_incomplete(umax4(pt0.x, pt1.x, pm0, pm1)), 0)) {
        const uint32_t b = lds32(sb + CT_HEAD) + slot_off(seg);
        uint32_t tries = zr;
#pragma unroll 1
        do {
          pt0 = ld_relaxed4(gptr(xhi, b + ap)); pt1 = ld_relaxed4(gptr(xhi, b + ap) + 2048);
          pm0 = ld_relaxed1(gptr(xhi, b + am)); pm1 = ld_relaxed1(gptr(xhi, b + am) + 2048);
        } while (warp_incomplete(umax4(pt0.x, pt1.x, pm0, pm1)) && ++tries < POLL_LIMIT);
      }
      const uint32_t pa[4] = {pt0.x, pt1.x, pt0.y, pt1.y}, pb[4] = {pt0.z, pt1.z, pt0.w, pt1.w};
#pragma unroll
      for (int u = 0; u < NU; u++) {
        float o0[4] = {0.f, 0.f, 0.f, 0.f}, o1[4] = {0.f, 0.f, 0.f, 0.f};
        mma1688(o0, pm0, pm1, vm[u].x); mma1688(o1, pm0, pm1, vm[u].y);
        mma16816(o0, pa, v0[u].x, v0[u].y); mma16816(o1, pa, v1[u].x, v1[u].y);
        if (WG) { mma16816(o0, pb, v0[u].z, v0[u].w); mma16816(o1, pb, v1[u].z, v1[u].w); }
#pragma unroll
        for (int r = 0; r < 2; r++) {
          const uint32_t w0 = pack_bf16(o0[2 * r], o0[2 * r + 1]), w1 = pack_bf16(o1[2 * r], o1[2 * r + 1]);
          const uint32_t rv = __shfl_xor_sync(~0u, odd ? w0 : w1, 1);
          asm volatile("st.global.v2.u32 [%0], {%1, %2};" ::"l"(op + r * 8 * HD * 2 - u * 64), "r"(odd ? rv : w0), "r"(odd ? w1 : rv) : "memory");
        }
      }
    };
    if (!more) {
      named_bar(3, 256);
      if (upper_warps) {
#pragma unroll 1
        for (int seg = NSEG - 2; seg < NSEG; seg++) token_pv(seg, false);
      }
      break;
    }
    {
      if (__builtin_expect(s > 0, 1)) {
        const uint32_t o = WG ? ovt - 512 : tv + 512;
        const char* src = gptr(xhi, lds32(sb + CT_HEAD) + slot_off(sv - 1) + o);
#pragma unroll
        for (int i = 0; i < 3 - WG; i++) cp_async16(sb + OFF_MEM + o + i * 512, src + i * 512);
        cp_async_commit();
      }
      bool xw;
      {
        float acc[16];
        if (__builtin_expect(!xok, 0)) mbar_wait<0>(sb + BAR_X + 8 * WG, (s + 1) & 1);
        wg_fence();
#pragma unroll
        for (int ks = 0; ks < 16; ks++) wgmma_m64n32_rs(acc, rot[ks], xdesc<WG>(16 + ks), ks != 0);
        wg_commit();
#pragma unroll
        for (int ks = 0; ks < 16; ks++) wgmma_m64n32_rs(acc, aV[ks], xdesc<WG>(ks), 1);
        wg_commit();
        SFENCE(50);
        NEWZ(2);
        xw = warp_is(3) && s + 2 < NSEG;
        tref += lds32(sb + CT_T + 4) + WG * T_LAG - T_SLIP;
        const uint32_t pvt = xvt + slot_off(sv + 1), awo = sb + wo_addr(tv);
        if (WG == 0 && warp_is(1) && s >= 0) expect_elect(sb + BAR_EX, 4096);
        if (xw) {
          expect_elect(sb + BAR_X + 8 * WG, 32768);
          if (WG == 1 && s == NSEG - 3) asm volatile("griddepcontrol.launch_dependents;");
          if (WG == 1 && s + 5 < NSEG) prefetch_l2(maps.xp + (s + 5) * 65536 + lds32(sb + CT_PF), 1024);
        }
        wg_wait<1>();
        if (xw) { named_bar(4 + WG, 128); issue_x(sb, &maps.xq, s + 2, WG, 1); }
        else if (s + 2 < NSEG) named_bar_arrive(4 + WG, 128);
        if (__builtin_expect(s == 0, 0)) {
          mbar_wait(sb + BAR_P + 16, 0);
#pragma unroll
          for (int ks = 16 - O_FIX; ks < 16; ks++) ldsm_x4_t(bO[ks], (awo ^ 32) + (ks & 7) * 1024);
        }
#pragma unroll
        for (int ks = 0; ks < 16 - O_FIX; ks++) ldsm_x4_t(bO[ks], (ks < 8 ? awo : awo ^ 32) + (ks & 7) * 1024);
        wg_wait<0>();
        acc_fence(acc);
        constexpr int K = WG * 2, G = 2 - K;
        sts128f(sb + OFF_RED + WG * 1024 + t16, make_float4(acc[G], acc[G + 1], acc[4 + G], acc[5 + G]));
        sts128f(sb + OFF_RED + WG * 1024 + 512 + t16, make_float4(acc[8 + G], acc[9 + G], acc[12 + G], acc[13 + G]));
        cp_async_wait_group<0>();
        named_bar(3, 256);
        const float4 o0 = lds128f(sb + OFF_RED + (WG ^ 1) * 1024 + t16), o1 = lds128f(sb + OFF_RED + (WG ^ 1) * 1024 + 512 + t16);
        st_relaxed4(gptr(xhi, pvt),
                    pack_bf16(acc[K] + o0.x, acc[K + 1] + o0.y), pack_bf16(acc[4 + K] + o0.z, acc[5 + K] + o0.w),
                    pack_bf16(acc[8 + K] + o1.x, acc[9 + K] + o1.y), pack_bf16(acc[12 + K] + o1.z, acc[13 + K] + o1.w));
      }
      if (__builtin_expect(s >= 0, 1)) {
        uint32_t tries = 0;
#pragma unroll
        for (int ks = 0; ks < 16 - O_FIX; ks++) tries |= bO[ks][0];
        const char* po = gptr(xhi, xom + slot_off(sv) + (tries & zr));
        tries = zr;
        float d[2][2][4];
        uint32_t mx;
#pragma unroll 1
        do {
          tref += T_SLIP;
          WAIT_UNTIL(tref, aV[0], 1, 1);
          uint4 o[8];
#pragma unroll
          for (int i = 0; i < 4; i++) o[i] = ld_relaxed4(po + i * 512);
#pragma unroll
          for (int i = 0; i < 4; i++) o[4 + i] = ld_relaxed4(po + 16384 + i * 512);
          __syncwarp();
#pragma unroll
          for (int i = 0; i < 2; i++)
#pragma unroll
            for (int q = 0; q < 2; q++) { d[i][q][0] = d[i][q][1] = d[i][q][2] = d[i][q][3] = 0.f; }
#pragma unroll
          for (int i = 0; i < 4; i++) {
            mma16816(d[0][0], aO[2 * i], o[i].x, o[i].y); mma16816(d[1][0], aO[8 + 2 * i], o[i].x, o[i].y);
            mma16816(d[0][1], aO[2 * i + 1], o[i].z, o[i].w); mma16816(d[1][1], aO[9 + 2 * i], o[i].z, o[i].w);
          }
          mx = umax4(o[0].w, o[1].w, o[2].w, o[3].w);
          SFENCE(33 + tries);
#pragma unroll
          for (int i = 0; i < 4; i++) {
            mma16816(d[0][0], bO[2 * i], o[4 + i].x, o[4 + i].y); mma16816(d[1][0], bO[8 + 2 * i], o[4 + i].x, o[4 + i].y);
            mma16816(d[0][1], bO[2 * i + 1], o[4 + i].z, o[4 + i].w); mma16816(d[1][1], bO[9 + 2 * i], o[4 + i].z, o[4 + i].w);
          }
          mx = max(mx, umax4(o[4].w, o[5].w, o[6].w, o[7].w));
        } while (warp_incomplete(mx) && ++tries < POLL_LIMIT);
        NEWZ(3);
        {
          const uint32_t rr = rsb + (WG ? OFF_RX1 : OFF_RX) + wq * 512 + (lv >> 1);
          st_async2(rr, __float_as_uint(d[0][0][0] + d[0][1][0]), __float_as_uint(d[0][0][1] + d[0][1][1]), rsb + BAR_EX);
          st_async2(rr + 256, __float_as_uint(d[0][0][2] + d[0][1][2]), __float_as_uint(d[0][0][3] + d[0][1][3]), rsb + BAR_EX);
          const uint32_t rd = sb + OFF_RED + (WG ^ 1) * 1024 + t16 - (lv >> 1);
          sts64(rd, __float_as_uint(d[1][0][0] + d[1][1][0]), __float_as_uint(d[1][0][1] + d[1][1][1]));
          sts64(rd + 256, __float_as_uint(d[1][0][2] + d[1][1][2]), __float_as_uint(d[1][0][3] + d[1][1][3]));
        }
        if (upper_warps) {
          named_bar_arrive(7, 256);
          if (xw) issue_x(sb, &maps.xq, s + 2, WG, 0);
          if (__builtin_expect(s > 0, 1)) token_pv(sv - 1, true);
        } else {
          const uint32_t mp = lds32(sb + CT_MP) + (lv >> 2) + wq * 128, ra = sb + wq * 256 + (lv >> 1);
          char* pp = gptr(xhi, mp + slot_off(sv + 1));
          named_bar(7, 256);
          uint2 p[8];
#pragma unroll
          for (int i = 0; i < 8; i++) p[i] = lds64(ra + OFF_RED + i * 1024);
#define SUM8(c) (((__uint_as_float(p[0].c) + __uint_as_float(p[1].c)) + (__uint_as_float(p[2].c) + __uint_as_float(p[3].c))) + \
                 ((__uint_as_float(p[4].c) + __uint_as_float(p[5].c)) + (__uint_as_float(p[6].c) + __uint_as_float(p[7].c))))
          const float r0 = SUM8(x), r1 = SUM8(y);
          mbar_wait(sb + BAR_EX, s & 1);
#pragma unroll
          for (int i = 0; i < 8; i++) p[i] = lds64(ra + (i < 4 ? OFF_RX : OFF_RX1) + (i & 3) * 512);
          st_relaxed1(pp, pack_bf16(r0 + SUM8(x), r1 + SUM8(y)));
          st_relaxed1(gptr(xhi, mp + slot_off(sv + 3)), EMPTY);
        }
        NEWZ(4);
        const char* src = gptr(xhi, xm + WG * 8192 + slot_off(sv + 1));
        const uint32_t awv = sb + wv_addr(tv) + OFF_WVR;
        tref += lds32(sb + CT_T + 8) - WG * T_LAG;
        named_bar(8, 256);
#pragma unroll
        for (int ks = 0; ks < V_PRE; ks++) ldsm_x4_t(rot[ks], awv + ks * 2048);
        WAIT_UNTIL(tref, aV[0], 1, 2);
        gather_issue(sb + OFF_MEM + WG * 8192 + tv, src);
#pragma unroll
        for (int ks = V_PRE; ks < 16; ks++) ldsm_x4_t(rot[ks], awv + ks * 2048);
        NEWZ(6);
        st_relaxed4(gptr(xhi, xvt + slot_off(sv + 2)), EMPTY, EMPTY, EMPTY, EMPTY);
        if (WG == 0) st_relaxed2(gptr(xhi, xvm + slot_off(sv + 2)), EMPTY, EMPTY);
      } else {
        load_v(tv);
        if (xw) issue_x(sb, &maps.xq, s + 2, WG, 0);
        mbar_wait(sb + BAR_P + 8, 0);
#pragma unroll
        for (int ks = 0; ks < 8; ks++) { ldsm_x4_t(aO[ks], sb + wo_addr(tv) + ks * 1024); ldsm_x4_t(aO[8 + ks], sb + (wo_addr(tv) ^ 32) + ks * 1024); }
        named_bar(0, 256);
        if (threadIdx.x == 0) {
          fence_async_smem();
          mbar_expect_tx(sb + BAR_P + 16, 4 * 16384);
          for (int q = 0; q < 4; q++) tma_load_2d(sb + OFF_WOR + q * 16384, &maps.wo, h * 32, j * 2048 + 1024 + q * 256, sb + BAR_P + 16);
        }
        __syncwarp();
        tref = gtime() / T_SLIP * T_SLIP - T_SLIP;
      }
    }
  }
}

#undef j
#undef s
#undef sv
#undef xm
#undef wq

__global__ void __launch_bounds__(256, 1) __cluster_dims__(2, 1, 1)
chain_kernel(const __grid_constant__ ChainMaps maps, const bf16* __restrict__ mem0, const uint64_t xbase) {
  using namespace chain;
  extern __shared__ uint8_t smem_raw[];
  uint32_t sb = smem_u32(smem_raw);
  PIN(sb);
  if (sb != SB_LO + (blockIdx.x & 1) * RANK_BIT || mapa(sb, (blockIdx.x & 1) ^ 1) != (sb ^ RANK_BIT)) __trap();
  const int tid = threadIdx.x;
  const int h = blockIdx.x >> 2, role = (blockIdx.x >> 1) & 1, j = blockIdx.x & 1;
  if (tid == 0) {
    for (int i = 0; i < 9; i++) mbar_init(sb + OFF_BAR + 8 * i, 1);
    asm volatile("fence.mbarrier_init.release.cluster;" ::: "memory");
    const uint32_t xl = (uint32_t)xbase;
    sts32(sb + CT_BASE, xl); sts32(sb + CT_HEAD, xl + h * xo::HEAD); sts32(sb + CT_OM, xl + xo::OM + (role ? j * 32768 : h * 2048));
    sts32(sb + CT_MP, xl + xo::MEM + (h * 2 + j) * 256); sts32(sb + CT_O, xl + xo::O + (h * 2 + j) * 128); sts32(sb + CT_PF, (h * 2 + j) * 1024);
    sts32(sb + CT_TT, sb + (j ? OFF_KT : OFF_QT));
    if (role == 0) {
      const CUtensorMap* wm = j ? &maps.wk : &maps.wq;
      mbar_expect_tx(sb + BAR_P, 6 * 16384);
      for (int c = 0; c < 3; c++)
        for (int q = 0; q < 2; q++) tma_load_2d(sb + OFF_X + (q * 3 + c) * 16384, wm, h * DH + q * 64, q * 512 + c * 128, sb + BAR_P);
      mbar_expect_tx(sb + BAR_P + 8, 4 * 16384);
      for (int c = 0; c < 2; c++)
        for (int q = 0; q < 2; q++) tma_load_2d(sb + OFF_X + (6 + q * 2 + c) * 16384, wm, h * DH + (q ^ 1) * 64, q * 512 + c * 128, sb + BAR_P + 8);
      mbar_expect_tx(sb + BAR_P + 24, 4 * 16384);
      for (int q = 0; q < 2; q++)
        for (int o = 0; o < 2; o++) tma_load_2d(sb + OFF_WS + (q * 2 + o) * 16384, wm, h * DH + (q ^ o) * 64, q * 512 + 384, sb + BAR_P + 24);
      for (int q = 0; q < 2; q++) tma_prefetch_2d(wm, h * DH + (q ^ 1) * 64, q * 512 + 256);
    } else {
      mbar_expect_tx(sb + BAR_P, 8 * 16384);
      for (int q = 0; q < 4; q++) tma_load_2d(sb + OFF_WOR + q * 16384, &maps.wv, h * DH + j * 64, (q >> 1) * 512 + (q & 1) * 128, sb + BAR_P);
      for (int q = 0; q < 4; q++) tma_load_2d(sb + OFF_WVR + q * 16384, &maps.wv, h * DH + j * 64, (q >> 1) * 512 + 256 + (q & 1) * 128, sb + BAR_P);
    }
  }
  for (int r = 0; r < RING; r++) {
    char* p = (char*)xbase + r * xo::SLOT;
    const int wq = (tid >> 5) & 3;
    if (role == 1) st_relaxed4(p + h * xo::HEAD + xo::VT + (8 * j + 2 * wq + (tid >> 7)) * 512 + (tid & 31) * 16, EMPTY, EMPTY, EMPTY, EMPTY);
    else if (j == 0) st_relaxed4(p + (tid < 128 ? xo::OM + h * 2048 + tid * 16 : h * xo::HEAD + wq * 2048 + xo::VM + (tid & 31) * 16), EMPTY, EMPTY, EMPTY, EMPTY);
    else {
      st_relaxed4(p + h * xo::HEAD + (tid >> 6) * 2048 + 1024 + (tid & 63) * 16, EMPTY, EMPTY, EMPTY, EMPTY);
      if (tid < 32) st_relaxed4(p + xo::MEM + h * 512 + tid * 16, EMPTY, EMPTY, EMPTY, EMPTY);
    }
  }
  __syncthreads();
  if (__shfl_sync(0xffffffffu, tid >> 5, 0) == 0) {
    uint32_t t[2], c[2], ka[4] = {0, 0, 0, 0};
    const uint32_t z = maps.t_step >> 24;
#pragma unroll
    for (int i = 0; i < 2; i++) {
      const uint32_t end = (gtime() & ~31u) + (i ? 2048 : 1024);
      for (int g = z; g < 256 && (int)(gtime() - (end - 96)) < 0; g++) KEEPALIVE(ka, z);
      for (int g = z; g < 256 && (int)((t[i] = gtime()) - end) < 0; g++) {}
      c[i] = (uint32_t)clock64();
    }
    uint32_t v = 0, target = 0;
    if (tid == 0) {
      st_relaxed1(&g_rate[blockIdx.x], (t[1] - t[0]) * 4096u / (c[1] - c[0]));
      __threadfence();
      target = (atomicAdd(&g_epoch, 1u) & ~127u) + 128u;
    }
    target = __shfl_sync(0xffffffffu, target, 0);
    int guard = 0;
    do { asm volatile("ld.acquire.gpu.global.u32 %0, [%1];" : "=r"(v) : "l"(&g_epoch) : "memory"); }
    while (__any_sync(0xffffffffu, (int)(v - target) < 0) && ++guard < (1 << 20));
    const uint4 r4 = ld_relaxed4(&g_rate[tid * 4]);
    uint32_t r = min(__reduce_max_sync(0xffffffffu, umax4(r4.x, r4.y, r4.z, r4.w)), 4 * RATE0);
    if (r < RATE0 + 28) r = RATE0;
    const uint32_t a = (maps.t_step * r / RATE0 + 31) & ~31u, b = (maps.t_phase * r / RATE0 + 31) & ~31u;
    sts128(sb + CT_T, make_uint4(a, b, a - b, r));
  }
  const uint32_t xhi = (uint32_t)(xbase >> 32);
  const int wg = __shfl_sync(0xffffffffu, tid >> 7, 0);
  if (role == 0) {
    if (wg == 0) role_a<0>(maps, mem0, sb, xhi); else role_a<1>(maps, mem0, sb, xhi);
  } else {
    if (wg == 0) role_v<0>(maps, mem0, sb, xhi); else role_v<1>(maps, mem0, sb, xhi);
  }
  __syncwarp();
  cluster_arrive();
  cluster_wait();
}

struct BMaps {
  CUtensorMap q, k, v, out, k8;
  const bf16 *shift_k, *ssm_k, *ssm_D;
};

#define B_SLEEP 200
namespace bp {
constexpr int U_PITCH = (2048 + 128) * 2 + 16;
constexpr int KR_WORDS = 1048;
constexpr int KR_PITCH = 8704;
constexpr int OFF_U = 0;
constexpr int OFF_KR = (8 * U_PITCH + 127) / 128 * 128;
constexpr int Q_OFF = 4352;
constexpr int OFF_BAR = OFF_KR + 8 * KR_PITCH;
constexpr int GROUP_BYTES = OFF_BAR + 128;
constexpr int SMEM = 2 * GROUP_BYTES + 128;
constexpr int NTASK = DM / 8;
static_assert(Q_OFF >= 4224 && Q_OFF + 4096 <= KR_PITCH, "staging does not fit");
}

__device__ __forceinline__ uint32_t bmul2(uint32_t a, uint32_t b) { uint32_t r; asm("mul.rn.bf16x2 %0, %1, %2;" : "=r"(r) : "r"(a), "r"(b)); return r; }
__device__ __forceinline__ uint32_t badd2(uint32_t a, uint32_t b) { uint32_t r; asm("add.rn.bf16x2 %0, %1, %2;" : "=r"(r) : "r"(a), "r"(b)); return r; }

__device__ __forceinline__ void mbar_wait_sleep(uint32_t bar, uint32_t parity) {
  int guard = 0;
  while (!mbar_try(bar, parity)) { __nanosleep(B_SLEEP); if (++guard > (1 << 22)) __trap(); }
}

__device__ __forceinline__ void bpart_body(const BMaps& maps, int first, int stride, int end) {
  using namespace bp;
  extern __shared__ uint8_t smem_all[];
  const int grp = __shfl_sync(0xffffffffu, threadIdx.x >> 8, 0);
  const int lane = keep(threadIdx.x & 31), g = lane >> 2, t = lane & 3;
  const int w = __shfl_sync(0xffffffffu, (threadIdx.x >> 5) & 7, 0);
  const uint32_t sb = ((smem_u32(smem_all) + 127) & ~127u) + grp * GROUP_BYTES;
  const uint32_t kr = sb + OFF_KR + w * KR_PITCH, bar_k = sb + OFF_BAR + 8 * w, bar_q = bar_k + 64;
  if (lane == 0) { mbar_init(bar_k, 1); mbar_init(bar_q, 1); asm volatile("fence.mbarrier_init.release.cluster;" ::: "memory"); }
  if (lane < 16) sts128(sb + OFF_U + w * U_PITCH + lane * 16, make_uint4(0, 0, 0, 0));
  __syncwarp();
  if (grp == 1) { named_bar_arrive(3, 512); named_bar(5, 512); }
  const int lm = lane >> 3, lr = lane & 7;
  uint32_t ph = 0;
  for (int task = first + grp; task < end; task += stride, ph ^= 1) {
    const int d0 = task * 8;
    uint4 x[8];
    {
      const uint4* kf = (const uint4*)(maps.ssm_k + (size_t)(d0 + w) * S_LEN);
#pragma unroll
      for (int it = 0; it < 8; it++) x[it] = __ldg(kf + it * 32 + lane);
    }
    const uint4 ska = __ldg((const uint4*)(maps.shift_k + (d0 + 2 * t) * 4));
    __syncwarp();
    if (lane == 0) {
      mbar_expect_tx(bar_k, 2 * 4096 + 128);
      tma_load_2d(kr + 4096, &maps.k8, d0, w * 256 + 248, bar_k);
      tma_load_2d(kr, &maps.k, d0, w * 256 - 8, bar_k);
      bulk_wait_read<0>();
      tma_load_2d(kr + Q_OFF, &maps.v, d0, w * 256, bar_k);
    }
    __syncwarp();
    if (task == first) named_bar_arrive(5, 512);
    const uint32_t sk[4] = {__byte_perm(ska.x, ska.z, 0x5410), __byte_perm(ska.x, ska.z, 0x7632), __byte_perm(ska.y, ska.w, 0x5410), __byte_perm(ska.y, ska.w, 0x7632)};
    mbar_wait_sleep(bar_k, ph);
    {
      const uint32_t ka = kr + (lane + 8) * 16;
#pragma unroll
      for (int i = 0; i < 8; i++) {
        uint32_t k0[4], k1[4], k2[4], k3[4], v[4], r[4];
        ldsm_x4(k3, ka + i * 512 - 48); ldsm_x4(k2, ka + i * 512 - 32); ldsm_x4(k1, ka + i * 512 - 16); ldsm_x4(k0, ka + i * 512);
        ldsm_x4(v, ka + (Q_OFF - 128) + i * 512);
#pragma unroll
        for (int b = 0; b < 4; b++) {
          uint32_t acc = bmul2(k3[b], sk[3]);
          acc = badd2(acc, bmul2(k2[b], sk[2]));
          acc = badd2(acc, bmul2(k1[b], sk[1]));
          acc = badd2(acc, bmul2(k0[b], sk[0]));
          r[b] = bmul2(acc, v[b]);
        }
        const int ch = 16 + w * 32 + i * 4 + lm;
        stsm_x4_t(sb + OFF_U + lr * U_PITCH + ((ch ^ ((ch >> 3) & 1)) << 4), r[0], r[1], r[2], r[3]);
      }
    }
    __syncwarp();
    {
      const uint32_t c0 = kr, c1 = c0 + (KR_WORDS + 16) * 4;
      uint32_t carry = 0;
#pragma unroll
      for (int it = 0; it < 8; it++) {
        const int blk = it * 32 + lane;
        uint32_t prev = __shfl_up_sync(0xffffffffu, x[it].w, 1);
        if (lane == 0) prev = carry;
        carry = __shfl_sync(0xffffffffu, x[it].w, 31);
        sts128(c0 + (1028 - 4 * blk) * 4, make_uint4(__byte_perm(x[it].w, 0, 0x1032), __byte_perm(x[it].z, 0, 0x1032),
                                                     __byte_perm(x[it].y, 0, 0x1032), __byte_perm(x[it].x, 0, 0x1032)));
        sts128(c1 + (1028 - 4 * blk) * 4, make_uint4(__byte_perm(x[it].w, x[it].z, 0x7610), __byte_perm(x[it].z, x[it].y, 0x7610),
                                                     __byte_perm(x[it].y, x[it].x, 0x7610), __byte_perm(x[it].x, prev, 0x7610)));
      }
      if (lane < 4) { sts128(c0 + (1032 + 4 * lane) * 4, make_uint4(0, 0, 0, 0)); sts128(c1 + (1032 + 4 * lane) * 4, make_uint4(0, 0, 0, 0)); }
      __syncwarp();
    }
    named_bar(3 + grp, 512);
    float acc[16][4];
#pragma unroll
    for (int jn = 0; jn < 16; jn++) { acc[jn][0] = acc[jn][1] = acc[jn][2] = acc[jn][3] = 0.f; }
    {
      const uint32_t ub = sb + OFF_U + w * U_PITCH;
      uint32_t kd = kr + (((g & 1) ? 0 : KR_WORDS + 16) + ((((g & 1) ? 2063 : 2062) - (g - 2 * t)) >> 1)) * 4;
      uint32_t uc = 2 * (8 + lr + (lm >> 1) * 8) + (lm & 1);
#pragma unroll 1
      for (int d0s = 0; d0s < 8; d0s++, kd -= 32, uc -= 2) {
        const uint32_t uf = ub + ((uc ^ ((uc >> 3) & 1)) << 4);
        uint32_t A[3][4];
        A[0][0] = lds32v(kd); A[0][1] = lds32v(kd - 16); A[0][2] = lds32v(kd + 16); A[0][3] = lds32v(kd);
        uint32_t F[8][4];
#pragma unroll
        for (int m = 7; m >= 0; m--) ldsm_x4(F[m], uf + m * 512);
#pragma unroll
        for (int i = 0; i < 16; i++) {
          if (i + 1 < 16) {
            A[(i + 1) % 3][0] = lds32v(kd - 256 * (i + 1)); A[(i + 1) % 3][1] = lds32v(kd - 256 * (i + 1) - 16);
            A[(i + 1) % 3][2] = lds32v(kd - 256 * (i + 1) + 16); A[(i + 1) % 3][3] = lds32v(kd - 256 * (i + 1));
          }
#pragma unroll
          for (int jn = 15; jn >= i; jn--) mma16816(acc[jn], A[i % 3], F[(jn - i) >> 1][((jn - i) & 1) * 2], F[(jn - i) >> 1][((jn - i) & 1) * 2 + 1]);
        }
      }
    }
    named_bar_arrive(3 + (grp ^ 1), 512);
    __syncwarp();
    fence_async_smem();
    __syncwarp();
    if (lane == 0) { mbar_expect_tx(bar_q, 4096); tma_load_2d(kr + Q_OFF, &maps.q, d0, w * 256, bar_q); }
    const uint32_t dpair = __ldg((const uint32_t*)(maps.ssm_D + d0) + t);
    {
      const uint32_t ya = kr + w * 16 + (((lm >> 1) * 8 + lr) * 32) + (lm & 1) * 16;
#pragma unroll
      for (int jn = 0; jn < 16; jn += 2)
        stsm_x4_t(ya + jn * 256, pack_bf16(acc[jn][0], acc[jn][1]), pack_bf16(acc[jn][2], acc[jn][3]),
                  pack_bf16(acc[jn + 1][0], acc[jn + 1][1]), pack_bf16(acc[jn + 1][2], acc[jn + 1][3]));
    }
    named_bar(1 + grp, 256);
    mbar_wait_sleep(bar_q, ph);
    {
      const uint32_t ya = sb + OFF_KR + lr * (KR_PITCH + 16) + (w * 256 + lm * 8) * 2;
#pragma unroll
      for (int i = 0; i < 8; i++) {
        uint32_t y[4], u[4], q[4], r[4];
        ldsm_x4(q, kr + Q_OFF + lane * 16 + i * 512);
        ldsm_x4_t(y, ya + i * 64);
        const int ch = 16 + w * 32 + i * 4 + lm;
        ldsm_x4_t(u, sb + OFF_U + lr * U_PITCH + ((ch ^ ((ch >> 3) & 1)) << 4));
#pragma unroll
        for (int b = 0; b < 4; b++) r[b] = bmul2(q[b], badd2(y[b], bmul2(u[b], dpair)));
        stsm_x4(kr + Q_OFF + lane * 16 + i * 512, r[0], r[1], r[2], r[3]);
      }
      fence_async_smem();
      __syncwarp();
      if (lane == 0) { tma_store_2d(&maps.out, kr + Q_OFF, DM + d0, w * 256); bulk_commit(); }
    }
    named_bar(1 + grp, 256);
  }
  if (lane == 0) bulk_wait<0>();
}

__global__ void __launch_bounds__(512, 1) __cluster_dims__(2, 1, 1) bpart_kernel(const __grid_constant__ BMaps maps, int end) {
  bpart_body(maps, blockIdx.x * 2, gridDim.x * 2, end);
}

struct GemmMaps {
  CUtensorMap o;
  CUtensorMap w;
  CUtensorMap c;
};
namespace k3 {
constexpr int STAGES = 6;
constexpr int W_BYTES = 2 * 8192, O_BYTES = K3_N * 128, STAGE_BYTES = W_BYTES + O_BYTES;
constexpr int TT = (S_LEN + K3_N - 1) / K3_N, NGEMM = TT * (DM / 128), NB = 128 - NGEMM, KSTEPS = HD / 64;
constexpr int SMEM_G = STAGES * STAGE_BYTES + 1024 + 256;
constexpr int SMEM = SMEM_G > bp::SMEM ? SMEM_G : bp::SMEM;
static_assert(STAGE_BYTES % 1024 == 0, "swizzle atoms");
}

__global__ void __launch_bounds__(512, 1)
tail_kernel(const __grid_constant__ GemmMaps maps, const __grid_constant__ BMaps bmaps) {
  using namespace k3;
  if (blockIdx.x < NB) {
    bpart_body(bmaps, bp::NTASK - 2 * NB + 2 * blockIdx.x, bp::NTASK, bp::NTASK);
    return;
  }
  extern __shared__ uint8_t smem_raw[];
  const uint32_t sbase = (smem_u32(smem_raw) + 1023) & ~1023u;
  const uint32_t bars = sbase + STAGES * STAGE_BYTES;
  const int tid = threadIdx.x, warp = tid >> 5;
  const int tt = (blockIdx.x - NB) / 8, ct = (blockIdx.x - NB) % 8;

  if (tid == 0) {
    for (int s = 0; s < STAGES; s++) { mbar_init(bars + 8 * s, 1); mbar_init(bars + 8 * (STAGES + s), 2); }
    asm volatile("fence.mbarrier_init.release.cluster;" ::: "memory");
  }
  __syncthreads();

  if (warp >= 8) {
    if (tid == 256) {
      tma_prefetch_desc(&maps.o);
      for (int k = 0; k < STAGES; k++) {
        const uint32_t full = bars + 8 * k, sa = sbase + k * STAGE_BYTES;
        mbar_expect_tx(full, STAGE_BYTES);
#pragma unroll
        for (int j = 0; j < 2; j++) tma_load_2d(sa + j * 8192, &maps.w, ct * 128 + j * 64, k * 64, full);
      }
      asm volatile("griddepcontrol.wait;" ::: "memory");
      int stage = 0; uint32_t ph = 1;
      for (int k = 0; k < KSTEPS; k++) {
        mbar_wait(bars + 8 * (STAGES + stage), ph);
        const uint32_t full = bars + 8 * stage, sa = sbase + stage * STAGE_BYTES;
        const bool pre = k < STAGES;
        if (!pre) mbar_expect_tx(full, STAGE_BYTES);
        tma_load_2d(sa + W_BYTES, &maps.o, k * 64, tt * K3_N, full);
        if (!pre) {
#pragma unroll
          for (int j = 0; j < 2; j++) tma_load_2d(sa + j * 8192, &maps.w, ct * 128 + j * 64, k * 64, full);
        }
        if (++stage == STAGES) { stage = 0; ph ^= 1; }
      }
    }
  } else {
    const int wg = warp >> 2, lane = tid & 31, wq = warp & 3;
    int stage = 0; uint32_t ph = 0;
    float acc[K3_N / 2];
    int prev = -1;
    for (int k = 0; k < KSTEPS; k++) {
      mbar_wait(bars + 8 * stage, ph);
      const uint32_t sa = sbase + stage * STAGE_BYTES;
      wg_fence();
#pragma unroll
      for (int kk = 0; kk < 4; kk++) {
        const uint64_t da = make_desc(sa + wg * 8192 + kk * 2048, 16, 1024, 1);
        const uint64_t db = make_desc(sa + W_BYTES + kk * 32, 16, 1024, 1);
        wgmma_k3_ss_ta(acc, da, db, (k | kk) != 0);
      }
      wg_commit();
      if (prev >= 0) { wg_wait<1>(); if ((tid & 127) == 0) mbar_arrive(bars + 8 * (STAGES + prev)); }
      prev = stage;
      if (++stage == STAGES) { stage = 0; ph ^= 1; }
    }
    wg_wait<0>();
#pragma unroll
    for (int i = 0; i < K3_N / 2; i++) asm volatile("" : "+f"(acc[i]) :: "memory");
    named_bar(1, 256);
    const uint32_t ebuf = sbase + wg * STAGE_BYTES;
    const uint32_t ea = ebuf + ((lane >> 4) * 8 + (lane & 7)) * 128 + (((2 * wq + ((lane >> 3) & 1)) ^ (lane & 7)) << 4);
#pragma unroll
    for (int i = 0; i < K3_N / 8; i += 2) {
      const int i1 = i + 1 < K3_N / 8 ? i + 1 : i;
      stsm_x4_t(ea + i * 1024, pack_bf16(acc[4 * i], acc[4 * i + 1]), pack_bf16(acc[4 * i + 2], acc[4 * i + 3]),
                pack_bf16(acc[4 * i1], acc[4 * i1 + 1]), pack_bf16(acc[4 * i1 + 2], acc[4 * i1 + 3]));
    }
    fence_async_smem();
    named_bar(2 + wg, 128);
    if ((tid & 127) == 0) {
      tma_store_2d(&maps.c, ebuf, ct * 128 + wg * 64, tt * K3_N);
      bulk_commit();
      bulk_wait<0>();
    }
  }
}

typedef CUresult (*EncodeFn)(CUtensorMap*, CUtensorMapDataType, cuuint32_t, void*, const cuuint64_t*, const cuuint64_t*,
                             const cuuint32_t*, const cuuint32_t*, CUtensorMapInterleave, CUtensorMapSwizzle,
                             CUtensorMapL2promotion, CUtensorMapFloatOOBfill);

void make_map(EncodeFn enc, CUtensorMap* m, const void* ptr, uint64_t cols, uint64_t rows, uint64_t pitch_elems,
              uint32_t box_cols, uint32_t box_rows, CUtensorMapSwizzle swz,
              CUtensorMapL2promotion promo = CU_TENSOR_MAP_L2_PROMOTION_L2_128B) {
  cuuint64_t dims[2] = {cols, rows};
  cuuint64_t strides[1] = {pitch_elems * 2};
  cuuint32_t box[2] = {box_cols, box_rows};
  cuuint32_t es[2] = {1, 1};
  enc(m, CU_TENSOR_MAP_DATA_TYPE_BFLOAT16, 2, const_cast<void*>(ptr), dims, strides, box, es, CU_TENSOR_MAP_INTERLEAVE_NONE, swz,
      promo, CU_TENSOR_MAP_FLOAT_OOB_FILL_NONE);
}

void make_map_nd(EncodeFn enc, CUtensorMap* m, const void* ptr, int rank, const uint64_t* dims, const uint64_t* strides_elems,
                 const uint32_t* box, CUtensorMapSwizzle swz) {
  cuuint64_t d[5], st[4]; cuuint32_t b[5], es[5];
  for (int i = 0; i < rank; i++) { d[i] = dims[i]; b[i] = box[i]; es[i] = 1; if (i) st[i - 1] = strides_elems[i] * 2; }
  enc(m, CU_TENSOR_MAP_DATA_TYPE_BFLOAT16, rank, const_cast<void*>(ptr), d, st, b, es, CU_TENSOR_MAP_INTERLEAVE_NONE, swz,
      CU_TENSOR_MAP_L2_PROMOTION_L2_128B, CU_TENSOR_MAP_FLOAT_OOB_FILL_NONE);
}

}

extern "C" void kernel_launch(void* const* d_in, const int* in_sizes, int n_in, void* d_out, int out_size) {
  (void)in_sizes; (void)n_in; (void)out_size;
  const bf16* x = (const bf16*)d_in[0];
  const bf16* mem0 = (const bf16*)d_in[1];
  const bf16* Wq = (const bf16*)d_in[2];
  const bf16* Wk = (const bf16*)d_in[3];
  const bf16* Wv = (const bf16*)d_in[4];
  const bf16* Wo = (const bf16*)d_in[5];
  const bf16* Bq = (const bf16*)d_in[7];
  const bf16* Bk = (const bf16*)d_in[8];
  const bf16* Bv = (const bf16*)d_in[9];
  const bf16* shift_k = (const bf16*)d_in[10];
  const bf16* ssm_k = (const bf16*)d_in[11];
  const bf16* ssm_D = (const bf16*)d_in[12];
  bf16* out = (bf16*)d_out;

  static EncodeFn enc = nullptr;
  static uint64_t xbase0;
  static int nsm = 132;
  static cudaStream_t s1;
  static cudaEvent_t ev_fork, ev_join;
  if (!enc) {
    cudaDriverEntryPointQueryResult qr;
    void* fn = nullptr;
    cudaGetDriverEntryPoint("cuTensorMapEncodeTiled", &fn, cudaEnableDefault, &qr);
    enc = (EncodeFn)fn;
    void* ps = nullptr;
    cudaGetSymbolAddress(&ps, g_scratch);
    xbase0 = (uint64_t)ps;
    if ((xbase0 >> 32) != ((xbase0 + xo::BYTES - 1) >> 32)) xbase0 += xo::BYTES;
    cudaFuncSetAttribute(tail_kernel, cudaFuncAttributeMaxDynamicSharedMemorySize, k3::SMEM);
    cudaFuncSetAttribute(chain_kernel, cudaFuncAttributeMaxDynamicSharedMemorySize, chain::SMEM);
    cudaFuncSetAttribute(bpart_kernel, cudaFuncAttributeMaxDynamicSharedMemorySize, bp::SMEM);
    cudaStreamCreateWithFlags(&s1, cudaStreamNonBlocking);
    cudaEventCreateWithFlags(&ev_fork, cudaEventDisableTiming);
    cudaEventCreateWithFlags(&ev_join, cudaEventDisableTiming);
    int dev = 0; cudaGetDevice(&dev);
    cudaDeviceGetAttribute(&nsm, cudaDevAttrMultiProcessorCount, dev);
  }
  uint64_t xbase = xbase0;
  const CUtensorMapSwizzle SW128 = CU_TENSOR_MAP_SWIZZLE_128B, SW64 = CU_TENSOR_MAP_SWIZZLE_64B;
  GemmMaps m3; ChainMaps mc;
  make_map(enc, &m3.o, (void*)(xbase + xo::O), HD, S_LEN, HD, 64, K3_N, SW128);
  make_map(enc, &m3.w, Wo, DM, HD, DM, 64, 64, SW128);
  make_map(enc, &m3.c, out, DM, S_LEN, OUT_LD, 64, K3_N, SW128);
  const CUtensorMapL2promotion P256 = CU_TENSOR_MAP_L2_PROMOTION_L2_256B;
  make_map(enc, &mc.wq, Wq, HD, DM, HD, 64, 128, SW128, P256);
  make_map(enc, &mc.wk, Wk, HD, DM, HD, 64, 128, SW128, P256);
  make_map(enc, &mc.wv, Wv, HD, DM, HD, 64, 128, SW128, P256);
  make_map(enc, &mc.wo, Wo, DM, HD, DM, 32, 256, SW64, P256);
  {
    const uint64_t dx[3] = {64, S_LEN, DM / 64}, sx[3] = {1, DM, 64};
    const uint32_t bx[3] = {64, SEG, 8};
    make_map_nd(enc, &mc.x, x, 3, dx, sx, bx, SW128);
    const uint32_t bq[3] = {64, SEG, 4};
    make_map_nd(enc, &mc.xq, x, 3, dx, sx, bq, SW128);
    mc.xp = (const char*)x;
  }

  const int skip = 0;
  mc.t_step = T_STEP; mc.t_phase = T_PHASE;
  BMaps mb;
  const CUtensorMapSwizzle SWN = CU_TENSOR_MAP_SWIZZLE_NONE;
  make_map(enc, &mb.k, Bk, DM, S_LEN, DM, 8, 256, SWN);
  make_map(enc, &mb.q, Bq, DM, S_LEN, DM, 8, 256, SWN);
  make_map(enc, &mb.v, Bv, DM, S_LEN, DM, 8, 256, SWN);
  mb.shift_k = shift_k; mb.ssm_k = ssm_k; mb.ssm_D = ssm_D;
  make_map(enc, &mb.out, out, OUT_LD, S_LEN, OUT_LD, 8, 256, SWN);
  make_map(enc, &mb.k8, Bk, DM, S_LEN, DM, 8, 8, SWN);
  cudaStream_t s0 = cudaStreamPerThread;
  const int nb = nsm >= 132 ? 4 : 2, ntask1 = bp::NTASK - 2 * k3::NB;
  const bool fork = nsm >= 130 && !(skip & 16);
  if (fork) {
    cudaEventRecord(ev_fork, s0);
    cudaStreamWaitEvent(s1, ev_fork, 0);
    if (!(skip & 1)) bpart_kernel<<<nb, 512, bp::SMEM, s1>>>(mb, ntask1);
    cudaEventRecord(ev_join, s1);
  } else if (!(skip & 1)) {
    bpart_kernel<<<ntask1 / 2, 512, bp::SMEM, s0>>>(mb, ntask1);
  }
  if (!(skip & 4)) chain_kernel<<<128, 256, chain::SMEM, s0>>>(mc, mem0, xbase);
  if (!(skip & 8)) {
    cudaLaunchAttribute pdl[1];
    pdl[0].id = cudaLaunchAttributeProgrammaticStreamSerialization;
    pdl[0].val.programmaticStreamSerializationAllowed = 1;
    cudaLaunchConfig_t cfg = {};
    cfg.gridDim = dim3(128); cfg.blockDim = dim3(512); cfg.dynamicSmemBytes = k3::SMEM; cfg.stream = s0;
    cfg.attrs = pdl; cfg.numAttrs = 1;
    cudaLaunchKernelEx(&cfg, tail_kernel, m3, mb);
  }
  if (fork) cudaStreamWaitEvent(s0, ev_join, 0);
}
```

```cpp
#include <cuda_runtime.h>
#include <cuda_bf16.h>
#include <cuda.h>
#include <stdint.h>

namespace {

constexpr int S_LEN = 2048;
constexpr int DM = 1024;
constexpr int NH = 32;
constexpr int DH = 128;
constexpr int HD = NH * DH;
constexpr int SEG = 32;
constexpr int NSEG = S_LEN / SEG;
constexpr int OUT_LD = 2048;

typedef __nv_bfloat16 bf16;
#define K3_N 160

__device__ __forceinline__ uint32_t smem_u32(const void* p) { return (uint32_t)__cvta_generic_to_shared(p); }

__device__ __forceinline__ void mbar_init(uint32_t bar, uint32_t count) {
  asm volatile("mbarrier.init.shared::cta.b64 [%0], %1;" ::"r"(bar), "r"(count) : "memory");
}
__device__ __forceinline__ void mbar_expect_tx(uint32_t bar, uint32_t bytes) {
  asm volatile("mbarrier.arrive.expect_tx.shared::cta.b64 _, [%0], %1;" ::"r"(bar), "r"(bytes) : "memory");
}
__device__ __forceinline__ void mbar_arrive(uint32_t bar) {
  asm volatile("mbarrier.arrive.shared::cta.b64 _, [%0];" ::"r"(bar) : "memory");
}
__device__ __forceinline__ bool mbar_try(uint32_t bar, uint32_t parity) {
  uint32_t ok;
  asm volatile("{.reg .pred p; mbarrier.try_wait.parity.shared::cta.b64 p, [%1], %2; selp.u32 %0, 1, 0, p;}"
               : "=r"(ok) : "r"(bar), "r"(parity) : "memory");
  return ok;
}
__device__ __forceinline__ bool mbar_test(uint32_t bar, uint32_t parity) {
  uint32_t ok;
  asm volatile("{.reg .pred p; mbarrier.test_wait.parity.shared::cta.b64 p, [%1], %2; selp.u32 %0, 1, 0, p;}"
               : "=r"(ok) : "r"(bar), "r"(parity) : "memory");
  return ok;
}
template <int HINT = 1>
__device__ __forceinline__ void mbar_wait(uint32_t bar, uint32_t parity) {
  int guard = 0;
  while (__builtin_expect(!mbar_try(bar, parity), HINT)) { if (++guard > (1 << 22)) __trap(); }
}
__device__ __forceinline__ void tma_load_2d(uint32_t dst, const CUtensorMap* map, int c0, int c1, uint32_t bar) {
  asm volatile("cp.async.bulk.tensor.2d.shared::cluster.global.mbarrier::complete_tx::bytes [%0], [%1, {%3, %4}], [%2];"
               ::"r"(dst), "l"(map), "r"(bar), "r"(c0), "r"(c1) : "memory");
}
__device__ __forceinline__ void tma_store_2d(const CUtensorMap* map, uint32_t src, int c0, int c1) {
  asm volatile("cp.async.bulk.tensor.2d.global.shared::cta.bulk_group [%0, {%2, %3}], [%1];"
               ::"l"(map), "r"(src), "r"(c0), "r"(c1) : "memory");
}
__device__ __forceinline__ void tma_prefetch_2d(const CUtensorMap* map, int c0, int c1) {
  asm volatile("cp.async.bulk.prefetch.tensor.2d.L2.global [%0, {%1, %2}];" ::"l"(map), "r"(c0), "r"(c1) : "memory");
}
__device__ __forceinline__ void tma_prefetch_desc(const CUtensorMap* map) {
  asm volatile("prefetch.tensormap [%0];" ::"l"(map) : "memory");
}
__device__ __forceinline__ void fence_async_smem() { asm volatile("fence.proxy.async.shared::cta;" ::: "memory"); }
__device__ __forceinline__ void bulk_commit() { asm volatile("cp.async.bulk.commit_group;" ::: "memory"); }
template <int N> __device__ __forceinline__ void bulk_wait_read() { asm volatile("cp.async.bulk.wait_group.read %0;" ::"n"(N) : "memory"); }
template <int N> __device__ __forceinline__ void bulk_wait() { asm volatile("cp.async.bulk.wait_group %0;" ::"n"(N) : "memory"); }
__device__ __forceinline__ void named_bar(int id, int n) { asm volatile("bar.sync %0, %1;" ::"r"(id), "r"(n) : "memory"); }

__device__ __forceinline__ void named_bar_arrive(int id, int n) { asm volatile("bar.arrive %0, %1;" ::"r"(id), "r"(n) : "memory"); }
__device__ __forceinline__ float ex2(float x) { float y; asm("ex2.approx.ftz.f32 %0, %1;" : "=f"(y) : "f"(x)); return y; }
__device__ __forceinline__ float rcp(float x) { float y; asm("rcp.approx.ftz.f32 %0, %1;" : "=f"(y) : "f"(x)); return y; }

__device__ __forceinline__ void sts32(uint32_t a, uint32_t x) { asm volatile("st.shared.b32 [%0], %1;" ::"r"(a), "r"(x) : "memory"); }
__device__ __forceinline__ uint32_t lds32(uint32_t a) { uint32_t x; asm volatile("ld.shared.b32 %0, [%1];" : "=r"(x) : "r"(a) : "memory"); return x; }
__device__ __forceinline__ uint32_t lds32v(uint32_t a) { uint32_t x; asm volatile("ld.volatile.shared.b32 %0, [%1];" : "=r"(x) : "r"(a) : "memory"); return x; }
__device__ __forceinline__ void sts128(uint32_t a, const uint4& v) { asm volatile("st.shared.v4.b32 [%0], {%1,%2,%3,%4};" ::"r"(a), "r"(v.x), "r"(v.y), "r"(v.z), "r"(v.w) : "memory"); }
__device__ __forceinline__ void sts128f(uint32_t a, const float4& v) { asm volatile("st.shared.v4.f32 [%0], {%1,%2,%3,%4};" ::"r"(a), "f"(v.x), "f"(v.y), "f"(v.z), "f"(v.w) : "memory"); }
__device__ __forceinline__ uint4 lds128(uint32_t a) { uint4 v; asm volatile("ld.shared.v4.b32 {%0,%1,%2,%3}, [%4];" : "=r"(v.x), "=r"(v.y), "=r"(v.z), "=r"(v.w) : "r"(a) : "memory"); return v; }
__device__ __forceinline__ float4 lds128f(uint32_t a) { float4 v; asm volatile("ld.shared.v4.f32 {%0,%1,%2,%3}, [%4];" : "=f"(v.x), "=f"(v.y), "=f"(v.z), "=f"(v.w) : "r"(a) : "memory"); return v; }

__device__ __forceinline__ void cp_async16(uint32_t dst, const void* src) { asm volatile("cp.async.cg.shared.global [%0], [%1], 16;" ::"r"(dst), "l"(src) : "memory"); }
__device__ __forceinline__ void cp_async_commit() { asm volatile("cp.async.commit_group;" ::: "memory"); }
template <int N> __device__ __forceinline__ void cp_async_wait_group() { asm volatile("cp.async.wait_group %0;" ::"n"(N) : "memory"); }

__device__ __forceinline__ void wg_fence() { asm volatile("wgmma.fence.sync.aligned;" ::: "memory"); }
__device__ __forceinline__ void wg_commit() { asm volatile("wgmma.commit_group.sync.aligned;" ::: "memory"); }
template <int N> __device__ __forceinline__ void wg_wait() { asm volatile("wgmma.wait_group.sync.aligned %0;" ::"n"(N) : "memory"); }
__device__ __forceinline__ uint64_t make_desc(uint32_t addr, uint32_t lbo, uint32_t sbo, uint32_t swz) {
  return (uint64_t)((addr & 0x3FFFF) >> 4) | ((uint64_t)(lbo >> 4) << 16) | ((uint64_t)(sbo >> 4) << 32) | ((uint64_t)swz << 62);
}

__device__ __forceinline__ void ldsm_x4(uint32_t (&r)[4], uint32_t addr) {
  asm volatile("ldmatrix.sync.aligned.m8n8.x4.shared.b16 {%0,%1,%2,%3}, [%4];"
               : "=r"(r[0]), "=r"(r[1]), "=r"(r[2]), "=r"(r[3]) : "r"(addr) : "memory");
}
__device__ __forceinline__ void ldsm_x4_t(uint32_t (&r)[4], uint32_t addr) {
  asm volatile("ldmatrix.sync.aligned.m8n8.x4.trans.shared.b16 {%0,%1,%2,%3}, [%4];"
               : "=r"(r[0]), "=r"(r[1]), "=r"(r[2]), "=r"(r[3]) : "r"(addr) : "memory");
}
__device__ __forceinline__ void stsm_x4(uint32_t addr, uint32_t r0, uint32_t r1, uint32_t r2, uint32_t r3) {
  asm volatile("stmatrix.sync.aligned.m8n8.x4.shared.b16 [%0], {%1,%2,%3,%4};"
               ::"r"(addr), "r"(r0), "r"(r1), "r"(r2), "r"(r3) : "memory");
}
__device__ __forceinline__ void stsm_x4_t(uint32_t addr, uint32_t r0, uint32_t r1, uint32_t r2, uint32_t r3) {
  asm volatile("stmatrix.sync.aligned.m8n8.x4.trans.shared.b16 [%0], {%1,%2,%3,%4};" ::"r"(addr), "r"(r0), "r"(r1), "r"(r2), "r"(r3) : "memory");
}
__device__ __forceinline__ void mma16816(float (&c)[4], const uint32_t (&a)[4], uint32_t b0, uint32_t b1) {
  asm volatile("mma.sync.aligned.m16n8k16.row.col.f32.bf16.bf16.f32 {%0,%1,%2,%3}, {%4,%5,%6,%7}, {%8,%9}, {%0,%1,%2,%3};"
               : "+f"(c[0]), "+f"(c[1]), "+f"(c[2]), "+f"(c[3])
               : "r"(a[0]), "r"(a[1]), "r"(a[2]), "r"(a[3]), "r"(b0), "r"(b1));
}
__device__ __forceinline__ void mma1688(float (&c)[4], uint32_t a0, uint32_t a1, uint32_t b0) {
  asm volatile("mma.sync.aligned.m16n8k8.row.col.f32.bf16.bf16.f32 {%0,%1,%2,%3}, {%4,%5}, {%6}, {%0,%1,%2,%3};"
               : "+f"(c[0]), "+f"(c[1]), "+f"(c[2]), "+f"(c[3]) : "r"(a0), "r"(a1), "r"(b0));
}
__device__ __forceinline__ uint32_t pack_bf16(float lo, float hi) {
  uint32_t r;
  asm("cvt.rn.bf16x2.f32 %0, %1, %2;" : "=r"(r) : "f"(hi), "f"(lo));
  return r;
}
__device__ __forceinline__ float bf_lo(uint32_t w) { return __uint_as_float(w << 16); }
__device__ __forceinline__ float bf_hi(uint32_t w) { return __uint_as_float(w & 0xFFFF0000u); }

__device__ __forceinline__ uint4 ld_relaxed4(const void* p) {
  uint4 v;
  asm volatile("ld.relaxed.gpu.global.v4.u32 {%0,%1,%2,%3}, [%4];" : "=r"(v.x), "=r"(v.y), "=r"(v.z), "=r"(v.w) : "l"(p) : "memory");
  return v;
}
__device__ __forceinline__ void st_relaxed4(void* p, uint32_t a, uint32_t b, uint32_t c, uint32_t d) {
  asm volatile("st.relaxed.gpu.global.v4.u32 [%0], {%1,%2,%3,%4};" ::"l"(p), "r"(a), "r"(b), "r"(c), "r"(d) : "memory");
}
__device__ __forceinline__ void st_relaxed2(void* p, uint32_t a, uint32_t b) {
  asm volatile("st.relaxed.gpu.global.v2.u32 [%0], {%1,%2};" ::"l"(p), "r"(a), "r"(b) : "memory");
}
__device__ __forceinline__ void st_relaxed1(void* p, uint32_t a) {
  asm volatile("st.relaxed.gpu.global.u32 [%0], %1;" ::"l"(p), "r"(a) : "memory");
}

__device__ __forceinline__ uint2 ld_relaxed2(const void* p) {
  uint2 v;
  asm volatile("ld.relaxed.gpu.global.v2.u32 {%0,%1}, [%2];" : "=r"(v.x), "=r"(v.y) : "l"(p) : "memory");
  return v;
}
__device__ __forceinline__ void sts64(uint32_t a, uint32_t x, uint32_t y) { asm volatile("st.shared.v2.b32 [%0], {%1,%2};" ::"r"(a), "r"(x), "r"(y) : "memory"); }
__device__ __forceinline__ uint2 lds64(uint32_t a) { uint2 v; asm volatile("ld.shared.v2.b32 {%0,%1}, [%2];" : "=r"(v.x), "=r"(v.y) : "r"(a) : "memory"); return v; }
__device__ __forceinline__ void lds128r(uint32_t (&r)[4], uint32_t a) {
  asm volatile("ld.shared.v4.b32 {%0,%1,%2,%3}, [%4];" : "=r"(r[0]), "=r"(r[1]), "=r"(r[2]), "=r"(r[3]) : "r"(a) : "memory");
}
__device__ __forceinline__ uint32_t mapa(uint32_t addr, uint32_t rank) { uint32_t r; asm volatile("mapa.shared::cluster.u32 %0, %1, %2;" : "=r"(r) : "r"(addr), "r"(rank)); return r; }
__device__ __forceinline__ void st_async1(uint32_t dst, uint32_t a, uint32_t bar) {
  asm volatile("st.async.weak.shared::cluster.mbarrier::complete_tx::bytes.b32 [%0], %1, [%2];" ::"r"(dst), "r"(a), "r"(bar) : "memory");
}
__device__ __forceinline__ void st_async2(uint32_t dst, uint32_t a, uint32_t b, uint32_t bar) {
  asm volatile("st.async.weak.shared::cluster.mbarrier::complete_tx::bytes.v2.b32 [%0], {%1,%2}, [%3];" ::"r"(dst), "r"(a), "r"(b), "r"(bar) : "memory");
}
__device__ __forceinline__ void cluster_arrive() { asm volatile("barrier.cluster.arrive.relaxed.aligned;" ::: "memory"); }
__device__ __forceinline__ void cluster_wait() { asm volatile("barrier.cluster.wait.acquire.aligned;" ::: "memory"); }

__device__ __forceinline__ void wgmma_k3_ss_ta(float (&d)[80], uint64_t da, uint64_t db, int scale_d) {
  asm volatile("{.reg .pred p; setp.ne.b32 p, %82, 0;\n"
    "wgmma.mma_async.sync.aligned.m64n160k16.f32.bf16.bf16 {%0, %1, %2, %3, %4, %5, %6, %7, %8, %9, %10, %11, %12, %13, %14, %15, %16, %17, %18, %19, %20, %21, %22, %23, %24, %25, %26, %27, %28, %29, %30, %31, %32, %33, %34, %35, %36, %37, %38, %39, %40, %41, %42, %43, %44, %45, %46, %47, %48, %49, %50, %51, %52, %53, %54, %55, %56, %57, %58, %59, %60, %61, %62, %63, %64, %65, %66, %67, %68, %69, %70, %71, %72, %73, %74, %75, %76, %77, %78, %79}, %80, %81, p, 1, 1, 1, 0;}"
    : "+f"(d[0]), "+f"(d[1]), "+f"(d[2]), "+f"(d[3]), "+f"(d[4]), "+f"(d[5]), "+f"(d[6]), "+f"(d[7]), "+f"(d[8]), "+f"(d[9]), "+f"(d[10]), "+f"(d[11]), "+f"(d[12]), "+f"(d[13]), "+f"(d[14]), "+f"(d[15]), "+f"(d[16]), "+f"(d[17]), "+f"(d[18]), "+f"(d[19]), "+f"(d[20]), "+f"(d[21]), "+f"(d[22]), "+f"(d[23]), "+f"(d[24]), "+f"(d[25]), "+f"(d[26]), "+f"(d[27]), "+f"(d[28]), "+f"(d[29]), "+f"(d[30]), "+f"(d[31]), "+f"(d[32]), "+f"(d[33]), "+f"(d[34]), "+f"(d[35]), "+f"(d[36]), "+f"(d[37]), "+f"(d[38]), "+f"(d[39]), "+f"(d[40]), "+f"(d[41]), "+f"(d[42]), "+f"(d[43]), "+f"(d[44]), "+f"(d[45]), "+f"(d[46]), "+f"(d[47]), "+f"(d[48]), "+f"(d[49]), "+f"(d[50]), "+f"(d[51]), "+f"(d[52]), "+f"(d[53]), "+f"(d[54]), "+f"(d[55]), "+f"(d[56]), "+f"(d[57]), "+f"(d[58]), "+f"(d[59]), "+f"(d[60]), "+f"(d[61]), "+f"(d[62]), "+f"(d[63]), "+f"(d[64]), "+f"(d[65]), "+f"(d[66]), "+f"(d[67]), "+f"(d[68]), "+f"(d[69]), "+f"(d[70]), "+f"(d[71]), "+f"(d[72]), "+f"(d[73]), "+f"(d[74]), "+f"(d[75]), "+f"(d[76]), "+f"(d[77]), "+f"(d[78]), "+f"(d[79])
    : "l"(da), "l"(db), "r"(scale_d));
}
__device__ __forceinline__ void wgmma_m64n32_ss_ta(float (&d)[16], uint64_t da, uint64_t db, int scale_d) {
  asm volatile("{.reg .pred p; setp.ne.b32 p, %18, 0;\n"
    "wgmma.mma_async.sync.aligned.m64n32k16.f32.bf16.bf16 {%0, %1, %2, %3, %4, %5, %6, %7, %8, %9, %10, %11, %12, %13, %14, %15}, %16, %17, p, 1, 1, 1, 0;}"
    : "+f"(d[0]), "+f"(d[1]), "+f"(d[2]), "+f"(d[3]), "+f"(d[4]), "+f"(d[5]), "+f"(d[6]), "+f"(d[7]), "+f"(d[8]), "+f"(d[9]), "+f"(d[10]), "+f"(d[11]), "+f"(d[12]), "+f"(d[13]), "+f"(d[14]), "+f"(d[15])
    : "l"(da), "l"(db), "r"(scale_d));
}

__device__ __forceinline__ void wgmma_m64n32_rs(float (&d)[16], const uint32_t (&a)[4], uint64_t db, int scale_d) {
  asm volatile("{.reg .pred p; setp.ne.b32 p, %21, 0;\n"
    "wgmma.mma_async.sync.aligned.m64n32k16.f32.bf16.bf16 {%0, %1, %2, %3, %4, %5, %6, %7, %8, %9, %10, %11, %12, %13, %14, %15}, {%16, %17, %18, %19}, %20, p, 1, 1, 0;}"
    : "+f"(d[0]), "+f"(d[1]), "+f"(d[2]), "+f"(d[3]), "+f"(d[4]), "+f"(d[5]), "+f"(d[6]), "+f"(d[7]), "+f"(d[8]), "+f"(d[9]), "+f"(d[10]), "+f"(d[11]), "+f"(d[12]), "+f"(d[13]), "+f"(d[14]), "+f"(d[15])
    : "r"(a[0]), "r"(a[1]), "r"(a[2]), "r"(a[3]), "l"(db), "r"(scale_d));
}

#define X_POS 5
#define T_STEP 2784
#define T_PHASE 1760
#define RATE0 2295
#define T_LAG 32
#define T_TOL 192
#define T_SLIP 640
#define O_FIX 5
#define NTMP 4
#define V_PRE 6
#define SFENCE(i) asm volatile("{.reg .pred p; setp.eq.u32 p, %0, %1; @p trap;}" ::"r"(n), "r"(4096 + (i)) : "memory")
constexpr int RING = 4;
constexpr uint32_t EMPTY = 0xFFFFFFFFu;
namespace xo {
constexpr uint32_t SLOT = 1u << 20, HEAD = 16384;
constexpr uint32_t VM = 512;
constexpr uint32_t PT = 1024;
constexpr uint32_t PM = 1536;
constexpr uint32_t VT = 8192;
constexpr uint32_t MEM = NH * HEAD;
constexpr uint32_t OM = MEM + 16384;
constexpr uint32_t O = RING * SLOT;
constexpr uint32_t BYTES = O + S_LEN * HD * 2;
}
__device__ __align__(1024) uint4 g_scratch[2 * (xo::BYTES / 16)];
__device__ unsigned g_epoch;
__device__ __align__(16) unsigned g_rate[128];

struct ChainMaps {
  CUtensorMap wq, wk, wv;
  CUtensorMap wo;
  CUtensorMap x, xq;
  const char* xp;
  uint32_t t_step, t_phase;
};

namespace chain {
constexpr int OFF_X = 65536;
constexpr int OFF_MEM = 131072;
constexpr int OFF_WS = 0;
constexpr int OFF_FP = 147456;
constexpr int OFF_KT = 163840;
constexpr int OFF_QT = 180224;
constexpr int OFF_VT = 196608;
constexpr int OFF_PX = 204800;
constexpr int OFF_S4 = OFF_PX + 1536;
constexpr int OFF_QM = 212992;
constexpr int OFF_KM = 215040;
constexpr int OFF_S1 = 217088;
constexpr int OFF_WVR = 0;
constexpr int OFF_WOR = 147456;
constexpr int OFF_RED = 212992;
constexpr int OFF_VPX = 221184;
constexpr int OFF_RX = 223232;
constexpr int OFF_BAR = 229376;
constexpr int BAR_X = OFF_BAR, BAR_TOK = OFF_BAR + 16, BAR_EX = OFF_BAR + 32, BAR_P = OFF_BAR + 40, GRID_TGT = OFF_BAR + 128;
constexpr int CT_BASE = GRID_TGT + 4, CT_HEAD = GRID_TGT + 8, CT_OM = GRID_TGT + 12, CT_MP = GRID_TGT + 16, CT_O = GRID_TGT + 20, CT_PF = GRID_TGT + 24;
constexpr int CT_TT = GRID_TGT + 28, CT_T = GRID_TGT + 32;
constexpr uint32_t RANK_BIT = 1u << 24;
constexpr int OFF_RX1 = OFF_BAR + 256;
constexpr int SMEM = OFF_RX1 + 2048;
constexpr uint32_t SB_LO = 1024;
constexpr float SCALE = 0.08838834764831845f, L2E = 1.4426950408889634f;
}

__device__ __forceinline__ uint32_t umax4(uint32_t a, uint32_t b, uint32_t c, uint32_t d) { return max(max(a, b), max(c, d)); }
__device__ __forceinline__ bool warp_incomplete(uint32_t m) { return __any_sync(0xffffffffu, m == EMPTY); }
#define PIN(x) asm volatile("" : "+r"(x))
#define KEEPALIVE(a, z) do { float _d0, _d1, _d2, _d3; asm volatile("mma.sync.aligned.m16n8k16.row.col.f32.bf16.bf16.f32 {%0,%1,%2,%3}, {%4,%5,%6,%7}, {%4,%5}, {%8,%8,%8,%8};" \
    : "=f"(_d0), "=f"(_d1), "=f"(_d2), "=f"(_d3) : "r"(a[0]), "r"(a[1]), "r"(a[2]), "r"(a[3]), "f"(0.f)); \
      \
    asm volatile("{.reg .pred p; setp.ne.u32 p, %0, 0; @p st.shared.f32 [%0], %1;}" ::"r"(z), "f"(_d0 + _d3) : "memory"); } while (0)
constexpr int POLL_LIMIT = 1 << 15;

__device__ __forceinline__ uint32_t keep(uint32_t x) { return __shfl_sync(0xffffffffu, x, threadIdx.x & 31); }
__device__ __forceinline__ char* gptr(uint32_t hi, uint32_t lo) { return (char*)(((uint64_t)hi << 32) | lo); }
__device__ __forceinline__ uint32_t slot_off(int n) { return ((uint32_t)n & (RING - 1)) * xo::SLOT; }
__device__ __forceinline__ float quad_max(float x) {
  const float a = __shfl_xor_sync(~0u, x, 1), b = __shfl_xor_sync(~0u, x, 2), c = __shfl_xor_sync(~0u, x, 3);
  return fmaxf(fmaxf(x, a), fmaxf(b, c));
}
__device__ __forceinline__ void acc_fence(float (&a)[16]) {
#pragma unroll
  for (int i = 0; i < 16; i++) asm volatile("" : "+f"(a[i]) :: "memory");
}
template <int NB = 1, int STRIDE = 0>
__device__ __forceinline__ void gather_issue(uint32_t dst, const char* src) {
#pragma unroll
  for (int b = 0; b < NB; b++)
#pragma unroll
    for (int i = 0; i < 4; i++) cp_async16(dst + b * STRIDE + i * 512, src + b * STRIDE + i * 512);
  cp_async_commit();
}
template <int NB, int STRIDE>
__device__ __forceinline__ bool gather_incomplete(uint32_t chk) {
  uint32_t m = 0;
#pragma unroll
  for (int b = 0; b < NB; b++) m = max(m, umax4(lds32(chk + b * STRIDE), lds32(chk + b * STRIDE + 512), lds32(chk + b * STRIDE + 1024), lds32(chk + b * STRIDE + 1536)));
  return warp_incomplete(m);
}
__device__ __forceinline__ uint32_t ld_relaxed1(const void* p) {
  uint32_t v;
  asm volatile("ld.relaxed.gpu.global.u32 %0, [%1];" : "=r"(v) : "l"(p) : "memory");
  return v;
}
__device__ __forceinline__ uint32_t gtime() { uint64_t g; asm volatile("mov.u64 %0, %%globaltimer;" : "=l"(g) :: "memory"); return (uint32_t)g; }
#define WAIT_UNTIL(t, ka, alive, id) do { \
    int _d = gtime() - (t); \
    if (__builtin_expect(_d > T_TOL, 0)) do { t += T_SLIP; _d -= T_SLIP; } while (_d > T_TOL); \
    if (alive) for (int _k = 64; _d < -96 && --_k; _d = gtime() - (t)) KEEPALIVE(ka, zr); \
    for (uint32_t _g = 0xFFFFFF80u; (int)(_d & ++_g) < 0;) _d = gtime() - (t); } while (0)
__device__ __forceinline__ void issue_x(uint32_t sb, const CUtensorMap* map, int n, int part, int q = 0) {
  asm volatile("{.reg .pred p; elect.sync _|p, 0xffffffff;\n"
               "@p cp.async.bulk.tensor.3d.shared::cluster.global.mbarrier::complete_tx::bytes [%0], [%1, {%3, %4, %5}], [%2];}"
               ::"r"(sb + chain::OFF_X + part * 32768 + q * 16384), "l"(map), "r"(sb + chain::BAR_X + 8 * part), "r"(0), "r"(n * SEG), "r"(part * 8 + q * 4) : "memory");
}
__device__ __forceinline__ void issue_x_if(uint32_t sb, const CUtensorMap* map, int n, int part, uint32_t on) {
  asm volatile("{.reg .pred p, q; elect.sync _|p, 0xffffffff; setp.ne.and.u32 q, %6, 0, p;\n"
               "@q cp.async.bulk.tensor.3d.shared::cluster.global.mbarrier::complete_tx::bytes [%0], [%1, {%3, %4, %5}], [%2];}"
               ::"r"(sb + chain::OFF_X + part * 32768), "l"(map), "r"(sb + chain::BAR_X + 8 * part), "r"(0), "r"(n * SEG), "r"(part * 8), "r"(on) : "memory");
}
__device__ __forceinline__ void prefetch_l2(const char* p, uint32_t bytes) {
  asm volatile("{.reg .pred p; elect.sync _|p, 0xffffffff; @p cp.async.bulk.prefetch.L2.global [%0], %1;}" ::"l"(p), "r"(bytes) : "memory");
}
__device__ __forceinline__ void expect_elect(uint32_t bar, uint32_t bytes) {
  asm volatile("{.reg .pred p; elect.sync _|p, 0xffffffff; @p mbarrier.arrive.expect_tx.shared::cta.b64 _, [%0], %1;}" ::"r"(bar), "r"(bytes) : "memory");
}
template <int WG> __device__ __forceinline__ constexpr uint64_t xdesc(int ks) {
  return (uint64_t)(((chain::SB_LO + chain::OFF_X + WG * 32768 + (ks >> 2) * 4096 + (ks & 3) * 32) >> 4) + (1u << 16)) |
         ((uint64_t)(64u | (1u << 30)) << 32);
}
template <int WG> __device__ __forceinline__ constexpr uint64_t wdesc(int o, int ks) {
  return (uint64_t)(((chain::SB_LO + chain::OFF_WS + WG * 32768 + o * 16384 + ks * 2048) >> 4) + (1u << 16)) | ((uint64_t)(64u | (1u << 30)) << 32);
}
__device__ __forceinline__ void load_mem0(uint2 (&m)[8], const bf16* __restrict__ mem0) {
#pragma unroll
  for (int r = 0; r < 8; r++) m[r] = ld_relaxed2((const uint2*)(mem0 + r * DM) + threadIdx.x);
}
__device__ __forceinline__ void store_mem0(uint32_t sb, const uint2 (&m)[8]) {
  const uint32_t d = sb + chain::OFF_MEM + threadIdx.x * 64;
  sts128(d, make_uint4(__byte_perm(m[0].x, m[1].x, 0x5410), __byte_perm(m[2].x, m[3].x, 0x5410), __byte_perm(m[4].x, m[5].x, 0x5410), __byte_perm(m[6].x, m[7].x, 0x5410)));
  sts128(d + 16, make_uint4(__byte_perm(m[0].x, m[1].x, 0x7632), __byte_perm(m[2].x, m[3].x, 0x7632), __byte_perm(m[4].x, m[5].x, 0x7632), __byte_perm(m[6].x, m[7].x, 0x7632)));
  sts128(d + 32, make_uint4(__byte_perm(m[0].y, m[1].y, 0x5410), __byte_perm(m[2].y, m[3].y, 0x5410), __byte_perm(m[4].y, m[5].y, 0x5410), __byte_perm(m[6].y, m[7].y, 0x5410)));
  sts128(d + 48, make_uint4(__byte_perm(m[0].y, m[1].y, 0x7632), __byte_perm(m[2].y, m[3].y, 0x7632), __byte_perm(m[4].y, m[5].y, 0x7632), __byte_perm(m[6].y, m[7].y, 0x7632)));
}
template <int K> __device__ __forceinline__ uint32_t loop_zero(int n) { uint32_t z; asm volatile("shr.u32 %0, %1, %2;" : "=r"(z) : "r"(n), "n"(16 + K)); return z; }
#define NEWZ(k) zr = loop_zero<k>(n)

template <int WG>
__device__ __forceinline__ void role_a(const ChainMaps& maps, const bf16* __restrict__ mem0, const uint32_t sb, const uint32_t xbase_hi) {
  using namespace chain;
  const int h = blockIdx.x >> 2;
  const bool J = sb >= RANK_BIT;
  const uint32_t u16 = (threadIdx.x & 96) * 64 + (threadIdx.x & 31) * 16;
  const uint32_t t16 = keep(u16), l16 = keep((threadIdx.x & 31) * 16);
  const uint32_t a_wl = keep((((threadIdx.x >> 4) & 1) * 8 + (threadIdx.x & 7)) * 128 + (((((threadIdx.x >> 4) & 6) + ((threadIdx.x >> 3) & 1)) ^ (threadIdx.x & 7)) << 4));
  const uint32_t xhi = keep(xbase_hi + (t16 >> 16));
#define xh (lds32(sb + CT_HEAD) + t16)
#define xm (lds32(sb + CT_BASE) + t16 + xo::MEM)
#define last_warp __any_sync(0xffffffffu, tv >= 6144)
#define tv (t16 ^ zr)
  const CUtensorMap* wm = J ? &maps.wk : &maps.wq;

  uint32_t aW[2][24][4];
  uint2 m0[8];
  load_mem0(m0, mem0);
  mbar_wait(sb + BAR_P, 0);
#pragma unroll
  for (int ks = 0; ks < 24; ks++) ldsm_x4_t(aW[0][ks], sb + a_wl + OFF_X + WG * 49152 + ks * 2048);
  named_bar(0, 256);
  if (WG == 1 && __any_sync(0xffffffffu, t16 >= 6144)) {
    fence_async_smem();
    if (l16 == 0) {
      mbar_expect_tx(sb + BAR_P + 16, 2 * 16384);
      for (int q = 0; q < 2; q++) tma_load_2d(sb + OFF_X + (4 + q) * 16384, wm, h * DH + (q ^ 1) * 64, q * 512 + 256, sb + BAR_P + 16);
    }
    __syncwarp();
    expect_elect(sb + BAR_X, 32768); expect_elect(sb + BAR_X + 8, 32768); expect_elect(sb + BAR_TOK, 8192);
    issue_x(sb, &maps.x, 0, 0); issue_x(sb, &maps.x, 0, 1);
  }
  mbar_wait(sb + BAR_P + 8, 0);
#pragma unroll
  for (int ks = 0; ks < 16; ks++) ldsm_x4_t(aW[1][ks], sb + a_wl + OFF_X + 6 * 16384 + WG * 32768 + ks * 2048);
  mbar_wait(sb + BAR_P + 16, 0);
#pragma unroll
  for (int ks = 0; ks < 8; ks++) ldsm_x4_t(aW[1][16 + ks], sb + a_wl + OFF_X + (4 + WG) * 16384 + ks * 2048);
  named_bar(0, 256);
  cluster_arrive();
  store_mem0(sb, m0);
  mbar_wait(sb + BAR_P + 24, 0);
  cluster_wait();
  const uint32_t rsb = sb ^ RANK_BIT;
  const uint32_t a_ws = sb + a_wl + OFF_WS + WG * 32768;

  uint32_t ws[2][4][4];
  auto load_ws = [&]() {
#pragma unroll
    for (int q = 0; q < 2; q++) {
      const uint32_t a = a_ws + q * 4096;
      ldsm_x4_t(ws[q][0], a); ldsm_x4_t(ws[q][1], a + 16384); ldsm_x4_t(ws[q][2], a + 2048); ldsm_x4_t(ws[q][3], a + 16384 + 2048);
    }
  };
  uint32_t tref = 0;
#pragma unroll 1
  for (int n = 0; n <= (J ? NSEG : NSEG - 1); n++) {
#define s (n - 1)
#define sv ((int)(n ^ zr) - 1)
    const bool more = __builtin_expect(s + 1 < NSEG, 1);
    uint32_t zr = loop_zero<0>(n);
#define wq ((int)(tv >> 11))
#define lv (l16 ^ zr)
#define gh (xh + slot_off(sv))
    uint32_t tmp[NTMP][4];
    auto load_tmp = [&](int o) {
#pragma unroll
      for (int ks = 0; ks < NTMP; ks++) ldsm_x4_t(tmp[ks], a_ws + o * 16384 + ks * 2048);
    };
    float y[10];
    auto no_p = [&]() {
#pragma unroll
      for (int i = 0; i < 10; i++) asm volatile("mov.b32 %0, %1;" : "=f"(y[i]) : "r"(zr));
    };
    auto finish_p = [&]() {
      const uint32_t gp = gh;
      float sy = ((y[0] + y[1]) + (y[2] + y[3])) + ((y[4] + y[5]) + (y[6] + y[7])) + (y[8] + y[9]);
      const float ry = rcp((sy + __shfl_xor_sync(~0u, sy, 1)) + (__shfl_xor_sync(~0u, sy, 2) + __shfl_xor_sync(~0u, sy, 3)));
      st_relaxed4(gptr(xhi, gp) + xo::PT, pack_bf16(y[2] * ry, y[3] * ry), pack_bf16(y[4] * ry, y[5] * ry), pack_bf16(y[6] * ry, y[7] * ry), pack_bf16(y[8] * ry, y[9] * ry));
      const uint32_t l12 = lv - (lv >> 2);
      st_relaxed1(gptr(xhi, gp - l12) + xo::PM, pack_bf16(y[0] * ry, y[1] * ry));
    };
    auto wait_x = [&]() { mbar_wait<0>(sb + BAR_X + 8 * WG, n & 1); };
    if (__builtin_expect(s < 0, 0)) { load_tmp(1); wait_x(); if (WG == 0) no_p(); }
    else {
      {
        if (WG == 1) { if (__builtin_expect(s > 0, 1)) {
          const uint32_t dst = sb + OFF_MEM + tv + t16 - l16, chk = dst + ((lv >> 5) & 12);
          uint32_t tries = zr;
#pragma unroll 1
          do {
            if (tries) {
              const char* src = gptr(xhi, xm + t16 - l16 + slot_off(sv));
              tref += T_SLIP;
              WAIT_UNTIL(tref, aW[0][0], 1, -1);
              gather_issue<2, 2048>(dst, src);
            }
            KEEPALIVE(aW[0][0], zr);
            cp_async_wait_group<0>();
          } while (gather_incomplete<2, 2048>(chk) && ++tries < POLL_LIMIT);
        } } else if (J == 0) {
          uint32_t tries = s == 0;
#pragma unroll 1
          do {
            if (tries) gather_issue(sb + OFF_VT + tv, gptr(xhi, gh) + xo::VT);
            cp_async_wait_group<0>();
          } while (gather_incomplete<1, 0>(sb + OFF_VT + t16 + ((lv >> 5) & 12)) && ++tries < POLL_LIMIT);
        }
        named_bar(1, 256);
      }
      float c[2][2][4];
#pragma unroll
      for (int i = 0; i < 4; i++) c[i >> 1][i & 1][0] = c[i >> 1][i & 1][1] = c[i >> 1][i & 1][2] = c[i >> 1][i & 1][3] = 0.f;
      {
        const uint32_t a_mem = sb + OFF_MEM + WG * 8192 + l16;
        uint32_t b[4][4];
        bool tok;
        constexpr int PR[16] = {12, 13, 0, 1, 2, 3, 4, 14, 5, 6, 7, 8, 9, 15, 10, 11};
        ldsm_x4_t(b[0], a_mem + PR[0] * 512); ldsm_x4_t(b[1], a_mem + PR[1] * 512);
#pragma unroll
        for (int i = 0; i < 16; i++) {
          if ((i & 1) == 0 && i < 14) {
            ldsm_x4_t(b[(i + 2) & 3], a_mem + PR[i + 2] * 512); ldsm_x4_t(b[(i + 3) & 3], a_mem + PR[i + 3] * 512);
            if (i == 2 || i == 8) { ldsm_x4_t(ws[1][0], a_ws + (i == 2 ? 2 : 3) * 4096); ldsm_x4_t(ws[1][1], a_ws + (i == 2 ? 2 : 3) * 4096 + 16384); }
            if (i == 4 || i == 10) { ldsm_x4_t(ws[1][2], a_ws + (i == 4 ? 2 : 3) * 4096 + 2048); ldsm_x4_t(ws[1][3], a_ws + (i == 4 ? 2 : 3) * 4096 + 16384 + 2048); }
          }
          const int p = PR[i];
          if (p >= 12) {
            const int z = i != 0;
            mma16816(c[0][0], ws[z][0], b[i & 3][0], b[i & 3][1]); mma16816(c[1][0], ws[z][1], b[i & 3][0], b[i & 3][1]);
            mma16816(c[0][1], ws[z][2], b[i & 3][2], b[i & 3][3]); mma16816(c[1][1], ws[z][3], b[i & 3][2], b[i & 3][3]);
          } else {
            mma16816(c[1][0], aW[1][2 * p], b[i & 3][0], b[i & 3][1]); mma16816(c[1][1], aW[1][2 * p + 1], b[i & 3][2], b[i & 3][3]);
            mma16816(c[0][0], aW[0][2 * p], b[i & 3][0], b[i & 3][1]); mma16816(c[0][1], aW[0][2 * p + 1], b[i & 3][2], b[i & 3][3]);
          }
          if (i == 12) tok = mbar_test(sb + BAR_TOK + 8 * (s & 1), (s >> 1) & 1);
          if (i == 15 && __builtin_expect(!tok, 0)) mbar_wait(sb + BAR_TOK + 8 * (s & 1), (s >> 1) & 1);
          if (i == X_POS + 4 * (1 - WG)) { issue_x_if(sb, &maps.x, s + 1, WG, t16 >= 6144 && more); if (WG) __syncwarp(); }
        }
      }
      sts128f(sb + OFF_PX + WG * 512 + t16, make_float4(c[1][0][0] + c[1][1][0], c[1][0][1] + c[1][1][1], c[1][0][2] + c[1][1][2], c[1][0][3] + c[1][1][3]));
      const float4 own = make_float4(c[0][0][0] + c[0][1][0], c[0][0][1] + c[0][1][1], c[0][0][2] + c[0][1][2], c[0][0][3] + c[0][1][3]);
      NEWZ(1);
      uint32_t a = (J ? OFF_KM : OFF_QM) + WG * 1024 + wq * 256 + (lv >> 2);
      uint32_t ra = rsb + a, ra2 = ra + 128, rx = rsb + BAR_EX + zr;
      PIN(a); PIN(ra); PIN(ra2); PIN(rx);
      const uint32_t kt = sb + OFF_KT + (s & 1) * 8192;
#define k_lane ((lv & 240) + ((lv & 256) << 2))
#define a_lane (((lv & 128) << 1) + ((lv & 256) >> 1) + (lv & 112))
      uint32_t kb[4][4], aq = sb + OFF_QM + a_lane, ak = kt + wq * 256 + k_lane;
      PIN(aq);
      if (WG == 0) PIN(ak);
      SFENCE(16);
      named_bar(3, 256);
      {
        const float4 o = lds128f(sb + OFF_PX + (WG ^ 1) * 512 + t16);
        const uint32_t lo = pack_bf16(own.x + o.x, own.y + o.y), hi = pack_bf16(own.z + o.z, own.w + o.w);
        if (J == 1 && more) { st_async1(ra, lo, rx); st_async1(ra2, hi, rx); }
        sts32(sb + a, lo); sts32(sb + a + 128, hi);
      }
      if (J == 0) {
        uint32_t am[4][4];
        auto load_q = [&]() {
#pragma unroll
          for (int p = 0; p < 4; p++) ldsm_x4_t(am[p], aq + p * 512);
        };
        auto scores = [&]() {
          float c0[2][4], c1[2][4];
#pragma unroll
          for (int i = 0; i < 2; i++) { c0[i][0] = c0[i][1] = c0[i][2] = c0[i][3] = 0.f; c1[i][0] = c1[i][1] = c1[i][2] = c1[i][3] = 0.f; }
#pragma unroll
          for (int p = 0; p < 4; p++) { mma16816(c0[p & 1], am[p], kb[p][0], kb[p][1]); mma16816(c1[p & 1], am[p], kb[p][2], kb[p][3]); }
          const uint32_t r1 = pack_bf16((c0[0][0] + c0[1][0]) + (c1[0][2] + c1[1][2]), (c0[0][1] + c0[1][1]) + (c1[0][3] + c1[1][3]));
          return pack_bf16(bf_lo(r1) * SCALE, bf_hi(r1) * SCALE);
        };
        if (WG == 1) {
          if (last_warp) {
            named_bar(7, 256);
            load_q();
            const uint32_t sa = sb + OFF_S1 + (lv >> 1);
            mbar_wait<0>(sb + BAR_EX, s & 1);
#pragma unroll
            for (int p = 0; p < 4; p++) ldsm_x4_t(kb[p], sb + OFF_KM + p * 512 + l16);
            const uint32_t sm = scores();
            sts64(sa, sm, __float_as_uint(quad_max(fmaxf(bf_lo(sm), bf_hi(sm)))));
            named_bar_arrive(9, 160);
          } else {
            named_bar_arrive(7, 256);
          }
          wait_x();
          load_tmp(1);
        } else {
#pragma unroll
          for (int p = 0; p < 4; p++) ldsm_x4(kb[p], ak + p * 2048);
          named_bar(7, 256);
          load_q();
          const uint32_t hb = lds32(sb + CT_HEAD), omb = lds32(sb + CT_OM);
          const char* pvm = gptr(xhi, hb + t16 + slot_off(sv) - (lv >> 1) + (am[3][0] & zr)) + xo::VM;
          uint2 vm0 = ld_relaxed2(pvm), vm1 = ld_relaxed2(pvm + 256);
          sts32(sb + OFF_S4 + l16 + wq * 4, scores());
          named_bar(8, 128);
          const uint4 sc = lds128(sb + OFF_S4 + l16);
          uint32_t vb[4][4];
          {
            const uint32_t va = sb + OFF_VT + t16 + (sc.x & zr);
#pragma unroll
            for (int e = 0; e < 4; e++) lds128r(vb[e], va + e * 512);
          }
          float x[8] = {bf_lo(sc.x), bf_hi(sc.x), bf_lo(sc.y), bf_hi(sc.y), bf_lo(sc.z), bf_hi(sc.z), bf_lo(sc.w), bf_hi(sc.w)};
          const float mt = quad_max(fmaxf(fmaxf(fmaxf(x[0], x[1]), fmaxf(x[2], x[3])), fmaxf(fmaxf(x[4], x[5]), fmaxf(x[6], x[7]))));
          const float mtb = mt * L2E;
#pragma unroll
          for (int i = 0; i < 8; i++) x[i] = ex2(fmaf(x[i], L2E, -mtb));
          uint32_t pa[4], pb[4], p5;
          asm volatile("" : "=r"(pa[1]), "=r"(pa[3]), "=r"(pb[1]), "=r"(pb[3]), "=r"(p5));
          pa[0] = pack_bf16(x[0], x[1]); pa[2] = pack_bf16(x[2], x[3]);
          pb[0] = pack_bf16(x[4], x[5]); pb[2] = pack_bf16(x[6], x[7]);
          float st = ((x[0] + x[1]) + (x[2] + x[3])) + ((x[4] + x[5]) + (x[6] + x[7]));
          asm volatile("" : "+r"(pb[0]), "+r"(pb[2]), "+f"(st));
          float oa[4][4];
#pragma unroll
          for (int e = 0; e < 4; e++) { oa[e][0] = oa[e][1] = oa[e][2] = oa[e][3] = 0.f; mma16816(oa[e], pa, vb[e][0], vb[e][1]); }
          SFENCE(25);
          named_bar(9, 160);
          const uint2 sm2 = lds64(sb + OFF_S1 + (lv >> 1));
          const uint32_t sm = sm2.x;
          const float mx = fmaxf(mt, __uint_as_float(sm2.y));
#pragma unroll
          for (int e = 0; e < 4; e++) mma16816(oa[e], pb, vb[e][2], vb[e][3]);
          const float mb = mx * L2E;
          const float e0 = ex2(fmaf(bf_lo(sm), L2E, -mb)), e1 = ex2(fmaf(bf_hi(sm), L2E, -mb)), ct = ex2(mtb - mb);
          const uint32_t xo0 = omb + wq * 512 + l16;
          if (__builtin_expect(warp_incomplete(max(max(vm0.x, vm1.x), __float_as_uint(mx) & zr)), 0)) {
            uint32_t tries = zr;
#pragma unroll 1
            do { vm0 = ld_relaxed2(pvm); vm1 = ld_relaxed2(pvm + 256); } while (warp_incomplete(max(vm0.x, vm1.x)) && ++tries < POLL_LIMIT);
          }
          const float sx = fmaf(ct, st, e0 + e1);
          const float s1 = __shfl_xor_sync(~0u, sx, 1), s2 = __shfl_xor_sync(~0u, sx, 2), s3 = __shfl_xor_sync(~0u, sx, 3);
          const uint32_t p4 = pack_bf16(e0, e1);
#pragma unroll
          for (int e = 0; e < 4; e++) { oa[e][0] *= ct; oa[e][1] *= ct; }
          mma1688(oa[0], p4, p5, vm0.x); mma1688(oa[1], p4, p5, vm0.y); mma1688(oa[2], p4, p5, vm1.x); mma1688(oa[3], p4, p5, vm1.y);
          const float rx = rcp((sx + s1) + (s2 + s3));
          st_relaxed4(gptr(xhi, xo0 + slot_off(sv)), pack_bf16(oa[0][0] * rx, oa[0][1] * rx), pack_bf16(oa[1][0] * rx, oa[1][1] * rx),
                      pack_bf16(oa[2][0] * rx, oa[2][1] * rx), pack_bf16(oa[3][0] * rx, oa[3][1] * rx));
          SFENCE(24);
          named_bar_arrive(10, 256);
          st_relaxed4(gptr(xhi, xo0 + slot_off(sv + 3)), EMPTY, EMPTY, EMPTY, EMPTY);
          load_tmp(1);
          wait_x();
          no_p();
        }
      } else {
        bool xok;
        {
          const int mt = WG | (wq == 3), ktile = wq == 3 ? 2 + WG : wq - 1;
          const uint32_t qt = sb + OFF_QT + (s & 1) * 8192 + mt * 512 + a_lane;
          uint32_t q[8][4];
          if (__any_sync(0xffffffffu, tv < 2048)) {
            named_bar(7, 256);
#pragma unroll
            for (int p = 0; p < 4; p++) ldsm_x4_t(kb[p], sb + OFF_KM + p * 512 + l16);
          } else {
            named_bar_arrive(7, 256);
#pragma unroll
            for (int p = 0; p < 4; p++) ldsm_x4(kb[p], kt + ktile * 256 + k_lane + p * 2048);
          }
#pragma unroll
          for (int i = 0; i < 8; i++) ldsm_x4(q[i], qt + i * 1024);
          __syncwarp();
          float c0[4][4];
#pragma unroll
          for (int i = 0; i < 4; i++) { c0[i][0] = c0[i][1] = c0[i][2] = c0[i][3] = 0.f; mma16816(c0[i], q[i], kb[i >> 1][(i & 1) * 2], kb[i >> 1][(i & 1) * 2 + 1]); }
#pragma unroll
          for (int i = 0; i < 4; i++) mma16816(c0[i], q[4 + i], kb[2 + (i >> 1)][(i & 1) * 2], kb[2 + (i >> 1)][(i & 1) * 2 + 1]);
          load_tmp(1);
          xok = mbar_test(sb + BAR_X + 8 * WG, n & 1);
          NEWZ(3);
          const uint32_t r0 = pack_bf16((c0[0][0] + c0[1][0]) + (c0[2][0] + c0[3][0]), (c0[0][1] + c0[1][1]) + (c0[2][1] + c0[3][1]));
          const uint32_t r1 = pack_bf16((c0[0][2] + c0[1][2]) + (c0[2][2] + c0[3][2]), (c0[0][3] + c0[1][3]) + (c0[2][3] + c0[3][3]));
          const uint32_t sa = wq == 0 ? sb + OFF_S1 + (lv >> 2) + mt * 256 : sb + OFF_S4 + l16 + mt * 4096 + ktile * 4;
          sts32(sa, pack_bf16(bf_lo(r0) * SCALE, bf_hi(r0) * SCALE));
          sts32(sa + (wq == 0 ? 128 : 2048), pack_bf16(bf_lo(r1) * SCALE, bf_hi(r1) * SCALE));
        }
        if (WG == 1) named_bar_arrive(8, 256);
        else {
          if (more) named_bar_arrive(10, 256);
          named_bar(8, 256);
          const uint4 sc = lds128(sb + OFF_S4 + t16); const uint32_t s1 = lds32(sb + OFF_S1 + wq * 128 + (lv >> 2));
          y[0] = bf_lo(s1); y[1] = bf_hi(s1); y[2] = bf_lo(sc.x); y[3] = bf_hi(sc.x); y[4] = bf_lo(sc.y); y[5] = bf_hi(sc.y);
          y[6] = bf_lo(sc.z); y[7] = bf_hi(sc.z); y[8] = bf_lo(sc.w); y[9] = bf_hi(sc.w);
          const int rel = wq * 8 + (int)(lv >> 6) - (int)((lv >> 3) & 6);
          const float NEG = -999292928.f;
#pragma unroll
          for (int e = 0; e < 4; e++) {
            if (e * 8 > rel) y[2 * e + 2] = NEG;
            if (e * 8 + 1 > rel) y[2 * e + 3] = NEG;
          }
          float my = fmaxf(fmaxf(fmaxf(y[0], y[1]), fmaxf(y[2], y[3])), fmaxf(fmaxf(y[4], y[5]), fmaxf(y[6], y[7])));
          my = quad_max(fmaxf(my, fmaxf(y[8], y[9])));
#pragma unroll
          for (int i = 0; i < 10; i++) y[i] = ex2((y[i] - my) * L2E);
          if (!more) finish_p();
        }
        if (!xok && more) wait_x();
      }
    }
    if (more) {
      float acc[16];
      const uint32_t xph = (s + 1) & 1;
      auto batch = [&](const uint32_t (&a)[24][4], int o) {
        wg_fence();
#pragma unroll
        for (int ks = NTMP; ks < 8; ks++) wgmma_m64n32_ss_ta(acc, wdesc<WG>(o, ks), xdesc<WG>(24 + ks), ks != NTMP);
#pragma unroll
        for (int ks = 0; ks < NTMP; ks++) wgmma_m64n32_rs(acc, tmp[ks], xdesc<WG>(24 + ks), 1);
#pragma unroll
        for (int ks = 0; ks < 24; ks++) wgmma_m64n32_rs(acc, a[ks], xdesc<WG>(ks), 1);
        wg_commit();
        SFENCE(50 + o);
      };
      if (WG == 0) named_bar(12, 256);
      else if (__builtin_expect(s >= 0, 1)) named_bar(10, 256);
      batch(aW[1], 1);
      named_bar_arrive(WG ? 12 : 13, 256);
      if (WG == 0 && J == 1 && s >= 0) { NEWZ(7); finish_p(); }
      wg_wait<0>();
      acc_fence(acc);
      load_tmp(0);
#pragma unroll
      for (int i = 0; i < 4; i++) sts128f(sb + OFF_FP + WG * 8192 + t16 + i * 512, make_float4(acc[4 * i], acc[4 * i + 1], acc[4 * i + 2], acc[4 * i + 3]));
      NEWZ(4);
      if (WG == 0 && s >= 0) {
        const uint32_t g1 = xh + slot_off(sv + 1);
        if (J == 0) gather_issue(sb + OFF_VT + tv, gptr(xhi, g1) + xo::VT);
        else {
          st_relaxed4(gptr(xhi, g1) + xo::PT, EMPTY, EMPTY, EMPTY, EMPTY);
          st_relaxed1(gptr(xhi, g1 - lv + (lv >> 2)) + xo::PM, EMPTY);
        }
      }
      uint32_t esrc = 0;
      if (WG == 1) { esrc = xm + t16 - l16 + 2048 + slot_off(sv + 1); tref += lds32(sb + CT_T); }
      named_bar(WG ? 13 : 14, 256);
      batch(aW[0], 0);
      NEWZ(5);
      if (WG == 1) {
        named_bar(14, 256);
        if (last_warp && s + 2 < NSEG) {
          expect_elect(sb + BAR_TOK + 8 * (xph ^ 1), 8192); expect_elect(sb + BAR_X, 32768); expect_elect(sb + BAR_X + 8, 32768);
          if (J == 0) expect_elect(sb + BAR_EX, 2048);
          if (s == NSEG - 3) asm volatile("griddepcontrol.launch_dependents;");
        }
      }
      const uint32_t tb = lds32(sb + CT_TT) + xph * 8192 + WG * 4096 + ((tv + l16) >> 1);
      float4 oth[4];
#pragma unroll
      for (int i = 0; i < 4; i++) oth[i] = lds128f(sb + OFF_FP + (WG ^ 1) * 8192 + t16 + i * 512);
      if (WG == 1 && __builtin_expect(s >= 0, 1)) {
        const uint32_t edst = sb + OFF_MEM + tv + t16 - l16;
        WAIT_UNTIL(tref, aW[0][0], 0, J ? 7 : 0);
        gather_issue<2, 2048>(edst, gptr(xhi, esrc) - 2048);
      }
      wg_wait<0>();
      acc_fence(acc);
      uint32_t lt[4], ht[4];
#pragma unroll
      for (int i = 0; i < 4; i++) {
        const float4 o = oth[i];
        lt[i] = pack_bf16(acc[4 * i] + o.x, acc[4 * i + 1] + o.y); ht[i] = pack_bf16(acc[4 * i + 2] + o.z, acc[4 * i + 3] + o.w);
      }
      stsm_x4_t(tb, lt[0], ht[0], lt[1], ht[1]); stsm_x4_t(tb + 512, lt[2], ht[2], lt[3], ht[3]);
      NEWZ(6);
      if (WG == 0 && last_warp) {
        load_ws();
        named_bar(11, 256);
        fence_async_smem();
        const uint32_t tt = (J ? OFF_KT : OFF_QT) + xph * 8192;
        asm volatile("{.reg .pred p; elect.sync _|p, 0xffffffff;\n"
                     "@p cp.async.bulk.shared::cluster.shared::cta.mbarrier::complete_tx::bytes [%0], [%1], 8192, [%2];}"
                     ::"r"(rsb + tt), "r"(sb + tt), "r"(rsb + BAR_TOK + 8 * xph) : "memory");
      } else {
        named_bar_arrive(11, 256);
        load_ws();
      }
    }
    if (!more) break;
    if (__builtin_expect(s < 0, 0)) {
      tref = gtime() / T_SLIP * T_SLIP - T_SLIP;
    }
  }
  cp_async_wait_group<0>();
  if (J == 0) mbar_wait(sb + BAR_TOK + 8, 1);
}

template <int WG>
__device__ __forceinline__ void role_v(const ChainMaps& maps, const bf16* __restrict__ mem0, const uint32_t sb, const uint32_t xbase_hi) {
  using namespace chain;
  const int h = blockIdx.x >> 2;
  const uint32_t u16 = (threadIdx.x & 96) * 64 + (threadIdx.x & 31) * 16;
  const uint32_t t16 = keep(u16), l16 = keep((threadIdx.x & 31) * 16);
  const uint32_t xhi = keep(xbase_hi + (t16 >> 16));
#define j (sb >> 24)
  auto wv_addr = [&](uint32_t t) { return WG * 32768 + ((t & 256) << 2) + ((t & 112) << 3) + ((((t >> 6) & 96) + ((t >> 3) & 16)) ^ (t & 112)); };
  auto wo_addr = [&](uint32_t t) { return OFF_WOR + WG * 32768 + ((t & 6144) << 2) + ((t & 256) << 1) + ((t & 112) << 2) + ((((j ^ 1) << 5) + ((t >> 3) & 16)) ^ ((t >> 1) & 48)); };
#define ovt (((tv + l16) >> 1) + (xo::VT + WG * 512 + j * 4096))
#define ovm (((tv & 4096) >> 1) + ((tv & 2048) >> 3) + (lv >> 1) + (xo::VM + j * 4096))
#define xvt (lds32(sb + CT_HEAD) + ovt)
#define xvm (lds32(sb + CT_HEAD) + ovm)
#define xom (lds32(sb + CT_OM) + t16 + WG * 8192)
#define warp_is(q) __any_sync(0xffffffffu, (tv >> 11) == (q))
#define upper_warps (WG == 1 || __any_sync(0xffffffffu, tv >= 4096))

  uint32_t aV[16][4];
  uint32_t aO[16][4];
  uint32_t bO[16][4];
  uint32_t rot[16][4];
  if (WG == 1 && __any_sync(0xffffffffu, t16 >= 6144)) {
    expect_elect(sb + BAR_X, 32768); expect_elect(sb + BAR_X + 8, 32768);
    issue_x(sb, &maps.x, 0, 0); issue_x(sb, &maps.x, 0, 1);
    prefetch_l2(maps.xp + 65536 + (h * 2 + j) * 3072, 3072);
  }
  cluster_arrive();
  { uint2 m0[8]; load_mem0(m0, mem0); store_mem0(sb, m0); }
  mbar_wait(sb + BAR_P, 0);
#pragma unroll
  for (int ks = 0; ks < 16; ks++) ldsm_x4_t(aV[ks], sb + wv_addr(t16) + OFF_WOR + ks * 2048);
  auto load_v = [&](uint32_t t) {
#pragma unroll
    for (int ks = 0; ks < 16; ks++) ldsm_x4_t(rot[ks], sb + wv_addr(t) + OFF_WVR + ks * 2048);
  };
  load_v(t16);
  named_bar(0, 256);
  if (threadIdx.x == 0) {
    fence_async_smem();
    mbar_expect_tx(sb + BAR_P + 8, 4 * 16384);
    for (int q = 0; q < 4; q++) tma_load_2d(sb + OFF_WOR + q * 16384, &maps.wo, h * 32, j * 2048 + q * 256, sb + BAR_P + 8);
    for (int q = 0; q < 4; q++) tma_prefetch_2d(&maps.wo, h * 32, j * 2048 + 1024 + q * 256);
  }
  __syncwarp();
  cluster_wait();
  const uint32_t rsb = sb ^ RANK_BIT;

  uint32_t tref = 0;
#pragma unroll 1
  for (int n = 0; n <= NSEG; n++) {
    const bool more = __builtin_expect(s + 1 < NSEG, 1);
    uint32_t zr = loop_zero<0>(n);
    bool xok = false;
    if (__builtin_expect(s >= 0, 1)) {
      if (__builtin_expect(s > 0, 1)) {
        const uint32_t dst = sb + OFF_MEM + WG * 8192 + t16 + ((lv >> 5) & 12);
        uint32_t tries = zr;
#pragma unroll 1
        do {
          if (tries) { const char* src = gptr(xhi, xm + WG * 8192 + slot_off(sv)); tref += T_SLIP; WAIT_UNTIL(tref, aV[0], 1, -1); gather_issue(sb + OFF_MEM + WG * 8192 + tv, src); }
          KEEPALIVE(aV[0], zr);
          cp_async_wait_group<0>();
        } while (gather_incomplete<1, 0>(dst) && ++tries < POLL_LIMIT);
        named_bar(1 + WG, 128);
      }
      const uint32_t a_mem = sb + OFF_MEM + WG * 8192 + l16;
      float c[2][4];
      c[0][0] = c[0][1] = c[0][2] = c[0][3] = c[1][0] = c[1][1] = c[1][2] = c[1][3] = 0.f;
      constexpr int NBUF = (48 - 8 - 4 * O_FIX) / 4;
      uint32_t b[NBUF][4];
#pragma unroll
      for (int p = 0; p < NBUF - 1; p++) ldsm_x4_t(b[p], a_mem + p * 512);
#pragma unroll
      for (int p = 0; p < 16; p++) {
        if (p + NBUF - 1 < 16) ldsm_x4_t(b[(p + NBUF - 1) % NBUF], a_mem + (p + NBUF - 1) * 512);
        if (p < 8) { mma16816(c[0], aV[2 * p], b[p % NBUF][0], b[p % NBUF][1]); mma16816(c[1], aV[2 * p + 1], b[p % NBUF][2], b[p % NBUF][3]); }
        else { mma16816(c[0], rot[2 * p - 16], b[p % NBUF][0], b[p % NBUF][1]); mma16816(c[1], rot[2 * p - 15], b[p % NBUF][2], b[p % NBUF][3]); }
      }
      xok = mbar_test(sb + BAR_X + 8 * WG, n & 1);
      SFENCE(15);
      const float4 own = make_float4(c[0][0] + c[1][0], c[0][1] + c[1][1], c[0][2] + c[1][2], c[0][3] + c[1][3]);
      NEWZ(1);
      const uint32_t pvm = WG == 0 ? xvm + slot_off(sv) : 0;
      if (WG == 1) sts128f(sb + OFF_VPX + wq * 512 + l16, own);
      named_bar(3, 256);
      if (WG == 0) {
        const float4 o = lds128f(sb + OFF_VPX + wq * 512 + l16);
        st_relaxed2(gptr(xhi, pvm), pack_bf16(own.x + o.x, own.y + o.y), pack_bf16(own.z + o.z, own.w + o.w));
      }
    }
    auto token_pv = [&](int seg, bool staged) {
      constexpr int NU = 2 - WG;
      uint4 pt0, pt1, v0[NU], v1[NU]; uint32_t pm0, pm1; uint2 vm[NU];
      const uint32_t ap = l16 + WG * 4096 + xo::PT, am = (lv >> 2) + WG * 4096 + xo::PM;
      const uint32_t at = ovt - WG * 512;
      if (staged) {
        const uint32_t b = sb + OFF_MEM;
        pt0 = lds128(b + ap); pt1 = lds128(b + ap + 2048); pm0 = lds32(b + am); pm1 = lds32(b + am + 2048);
#pragma unroll
        for (int u = 0; u < NU; u++) { v0[u] = lds128(b + at - u * 2048); v1[u] = lds128(b + at + 512 - u * 2048); vm[u] = lds64(b + ovm - u * 2048); }
      } else {
        const uint32_t b = lds32(sb + CT_HEAD) + slot_off(seg);
        pt0.x = EMPTY;
#pragma unroll
        for (int u = 0; u < NU; u++) {
          v0[u] = ld_relaxed4(gptr(xhi, b + at) - u * 2048); v1[u] = ld_relaxed4(gptr(xhi, b + at) + 512 - u * 2048);
          vm[u] = ld_relaxed2(gptr(xhi, b + ovm) - u * 2048);
        }
      }
      const bool odd = lv & 16;
      char* op = gptr(xhi, lds32(sb + CT_O) + (seg * SEG + WG * 16 + (lv >> 6)) * (HD * 2) + wq * 32 + (lv & 16) + ((lv >> 2) & 8));
      if (!staged || __builtin_expect(warp_incomplete(umax4(pt0.x, pt1.x, pm0, pm1)), 0)) {
        const uint32_t b = lds32(sb + CT_HEAD) + slot_off(seg);
        uint32_t tries = zr;
#pragma unroll 1
        do {
          pt0 = ld_relaxed4(gptr(xhi, b + ap)); pt1 = ld_relaxed4(gptr(xhi, b + ap) + 2048);
          pm0 = ld_relaxed1(gptr(xhi, b + am)); pm1 = ld_relaxed1(gptr(xhi, b + am) + 2048);
        } while (warp_incomplete(umax4(pt0.x, pt1.x, pm0, pm1)) && ++tries < POLL_LIMIT);
      }
      const uint32_t pa[4] = {pt0.x, pt1.x, pt0.y, pt1.y}, pb[4] = {pt0.z, pt1.z, pt0.w, pt1.w};
#pragma unroll
      for (int u = 0; u < NU; u++) {
        float o0[4] = {0.f, 0.f, 0.f, 0.f}, o1[4] = {0.f, 0.f, 0.f, 0.f};
        mma1688(o0, pm0, pm1, vm[u].x); mma1688(o1, pm0, pm1, vm[u].y);
        mma16816(o0, pa, v0[u].x, v0[u].y); mma16816(o1, pa, v1[u].x, v1[u].y);
        if (WG) { mma16816(o0, pb, v0[u].z, v0[u].w); mma16816(o1, pb, v1[u].z, v1[u].w); }
#pragma unroll
        for (int r = 0; r < 2; r++) {
          const uint32_t w0 = pack_bf16(o0[2 * r], o0[2 * r + 1]), w1 = pack_bf16(o1[2 * r], o1[2 * r + 1]);
          const uint32_t rv = __shfl_xor_sync(~0u, odd ? w0 : w1, 1);
          asm volatile("st.global.v2.u32 [%0], {%1, %2};" ::"l"(op + r * 8 * HD * 2 - u * 64), "r"(odd ? rv : w0), "r"(odd ? w1 : rv) : "memory");
        }
      }
    };
    if (!more) {
      named_bar(3, 256);
      if (upper_warps) {
#pragma unroll 1
        for (int seg = NSEG - 2; seg < NSEG; seg++) token_pv(seg, false);
      }
      break;
    }
    {
      if (__builtin_expect(s > 0, 1)) {
        const uint32_t o = WG ? ovt - 512 : tv + 512;
        const char* src = gptr(xhi, lds32(sb + CT_HEAD) + slot_off(sv - 1) + o);
#pragma unroll
        for (int i = 0; i < 3 - WG; i++) cp_async16(sb + OFF_MEM + o + i * 512, src + i * 512);
        cp_async_commit();
      }
      bool xw;
      {
        float acc[16];
        if (__builtin_expect(!xok, 0)) mbar_wait<0>(sb + BAR_X + 8 * WG, (s + 1) & 1);
        wg_fence();
#pragma unroll
        for (int ks = 0; ks < 16; ks++) wgmma_m64n32_rs(acc, rot[ks], xdesc<WG>(16 + ks), ks != 0);
        wg_commit();
#pragma unroll
        for (int ks = 0; ks < 16; ks++) wgmma_m64n32_rs(acc, aV[ks], xdesc<WG>(ks), 1);
        wg_commit();
        SFENCE(50);
        NEWZ(2);
        xw = warp_is(3) && s + 2 < NSEG;
        tref += lds32(sb + CT_T + 4) + WG * T_LAG - T_SLIP;
        const uint32_t pvt = xvt + slot_off(sv + 1), awo = sb + wo_addr(tv);
        if (WG == 0 && warp_is(1) && s >= 0) expect_elect(sb + BAR_EX, 4096);
        if (xw) {
          expect_elect(sb + BAR_X + 8 * WG, 32768);
          if (WG == 1 && s == NSEG - 3) asm volatile("griddepcontrol.launch_dependents;");
          if (WG == 1 && s + 5 < NSEG) prefetch_l2(maps.xp + (s + 5) * 65536 + lds32(sb + CT_PF), 1024);
        }
        wg_wait<1>();
        if (xw) { named_bar(4 + WG, 128); issue_x(sb, &maps.xq, s + 2, WG, 1); }
        else if (s + 2 < NSEG) named_bar_arrive(4 + WG, 128);
        if (__builtin_expect(s == 0, 0)) {
          mbar_wait(sb + BAR_P + 16, 0);
#pragma unroll
          for (int ks = 16 - O_FIX; ks < 16; ks++) ldsm_x4_t(bO[ks], (awo ^ 32) + (ks & 7) * 1024);
        }
#pragma unroll
        for (int ks = 0; ks < 16 - O_FIX; ks++) ldsm_x4_t(bO[ks], (ks < 8 ? awo : awo ^ 32) + (ks & 7) * 1024);
        wg_wait<0>();
        acc_fence(acc);
        constexpr int K = WG * 2, G = 2 - K;
        sts128f(sb + OFF_RED + WG * 1024 + t16, make_float4(acc[G], acc[G + 1], acc[4 + G], acc[5 + G]));
        sts128f(sb + OFF_RED + WG * 1024 + 512 + t16, make_float4(acc[8 + G], acc[9 + G], acc[12 + G], acc[13 + G]));
        cp_async_wait_group<0>();
        named_bar(3, 256);
        const float4 o0 = lds128f(sb + OFF_RED + (WG ^ 1) * 1024 + t16), o1 = lds128f(sb + OFF_RED + (WG ^ 1) * 1024 + 512 + t16);
        st_relaxed4(gptr(xhi, pvt),
                    pack_bf16(acc[K] + o0.x, acc[K + 1] + o0.y), pack_bf16(acc[4 + K] + o0.z, acc[5 + K] + o0.w),
                    pack_bf16(acc[8 + K] + o1.x, acc[9 + K] + o1.y), pack_bf16(acc[12 + K] + o1.z, acc[13 + K] + o1.w));
      }
      if (__builtin_expect(s >= 0, 1)) {
        uint32_t tries = 0;
#pragma unroll
        for (int ks = 0; ks < 16 - O_FIX; ks++) tries |= bO[ks][0];
        const char* po = gptr(xhi, xom + slot_off(sv) + (tries & zr));
        tries = zr;
        float d[2][2][4];
        uint32_t mx;
#pragma unroll 1
        do {
          tref += T_SLIP;
          WAIT_UNTIL(tref, aV[0], 1, 1);
          uint4 o[8];
#pragma unroll
          for (int i = 0; i < 4; i++) o[i] = ld_relaxed4(po + i * 512);
#pragma unroll
          for (int i = 0; i < 4; i++) o[4 + i] = ld_relaxed4(po + 16384 + i * 512);
          __syncwarp();
#pragma unroll
          for (int i = 0; i < 2; i++)
#pragma unroll
            for (int q = 0; q < 2; q++) { d[i][q][0] = d[i][q][1] = d[i][q][2] = d[i][q][3] = 0.f; }
#pragma unroll
          for (int i = 0; i < 4; i++) {
            mma16816(d[0][0], aO[2 * i], o[i].x, o[i].y); mma16816(d[1][0], aO[8 + 2 * i], o[i].x, o[i].y);
            mma16816(d[0][1], aO[2 * i + 1], o[i].z, o[i].w); mma16816(d[1][1], aO[9 + 2 * i], o[i].z, o[i].w);
          }
          mx = umax4(o[0].w, o[1].w, o[2].w, o[3].w);
          SFENCE(33 + tries);
#pragma unroll
          for (int i = 0; i < 4; i++) {
            mma16816(d[0][0], bO[2 * i], o[4 + i].x, o[4 + i].y); mma16816(d[1][0], bO[8 + 2 * i], o[4 + i].x, o[4 + i].y);
            mma16816(d[0][1], bO[2 * i + 1], o[4 + i].z, o[4 + i].w); mma16816(d[1][1], bO[9 + 2 * i], o[4 + i].z, o[4 + i].w);
          }
          mx = max(mx, umax4(o[4].w, o[5].w, o[6].w, o[7].w));
        } while (warp_incomplete(mx) && ++tries < POLL_LIMIT);
        NEWZ(3);
        {
          const uint32_t rr = rsb + (WG ? OFF_RX1 : OFF_RX) + wq * 512 + (lv >> 1);
          st_async2(rr, __float_as_uint(d[0][0][0] + d[0][1][0]), __float_as_uint(d[0][0][1] + d[0][1][1]), rsb + BAR_EX);
          st_async2(rr + 256, __float_as_uint(d[0][0][2] + d[0][1][2]), __float_as_uint(d[0][0][3] + d[0][1][3]), rsb + BAR_EX);
          const uint32_t rd = sb + OFF_RED + (WG ^ 1) * 1024 + t16 - (lv >> 1);
          sts64(rd, __float_as_uint(d[1][0][0] + d[1][1][0]), __float_as_uint(d[1][0][1] + d[1][1][1]));
          sts64(rd + 256, __float_as_uint(d[1][0][2] + d[1][1][2]), __float_as_uint(d[1][0][3] + d[1][1][3]));
        }
        if (upper_warps) {
          named_bar_arrive(7, 256);
          if (xw) issue_x(sb, &maps.xq, s + 2, WG, 0);
          if (__builtin_expect(s > 0, 1)) token_pv(sv - 1, true);
        } else {
          const uint32_t mp = lds32(sb + CT_MP) + (lv >> 2) + wq * 128, ra = sb + wq * 256 + (lv >> 1);
          char* pp = gptr(xhi, mp + slot_off(sv + 1));
          named_bar(7, 256);
          uint2 p[8];
#pragma unroll
          for (int i = 0; i < 8; i++) p[i] = lds64(ra + OFF_RED + i * 1024);
#define SUM8(c) (((__uint_as_float(p[0].c) + __uint_as_float(p[1].c)) + (__uint_as_float(p[2].c) + __uint_as_float(p[3].c))) + \
                 ((__uint_as_float(p[4].c) + __uint_as_float(p[5].c)) + (__uint_as_float(p[6].c) + __uint_as_float(p[7].c))))
          const float r0 = SUM8(x), r1 = SUM8(y);
          mbar_wait(sb + BAR_EX, s & 1);
#pragma unroll
          for (int i = 0; i < 8; i++) p[i] = lds64(ra + (i < 4 ? OFF_RX : OFF_RX1) + (i & 3) * 512);
          st_relaxed1(pp, pack_bf16(r0 + SUM8(x), r1 + SUM8(y)));
          st_relaxed1(gptr(xhi, mp + slot_off(sv + 3)), EMPTY);
        }
        NEWZ(4);
        const char* src = gptr(xhi, xm + WG * 8192 + slot_off(sv + 1));
        const uint32_t awv = sb + wv_addr(tv) + OFF_WVR;
        tref += lds32(sb + CT_T + 8) - WG * T_LAG;
        named_bar(8, 256);
#pragma unroll
        for (int ks = 0; ks < V_PRE; ks++) ldsm_x4_t(rot[ks], awv + ks * 2048);
        WAIT_UNTIL(tref, aV[0], 1, 2);
        gather_issue(sb + OFF_MEM + WG * 8192 + tv, src);
#pragma unroll
        for (int ks = V_PRE; ks < 16; ks++) ldsm_x4_t(rot[ks], awv + ks * 2048);
        NEWZ(6);
        st_relaxed4(gptr(xhi, xvt + slot_off(sv + 2)), EMPTY, EMPTY, EMPTY, EMPTY);
        if (WG == 0) st_relaxed2(gptr(xhi, xvm + slot_off(sv + 2)), EMPTY, EMPTY);
      } else {
        load_v(tv);
        if (xw) issue_x(sb, &maps.xq, s + 2, WG, 0);
        mbar_wait(sb + BAR_P + 8, 0);
#pragma unroll
        for (int ks = 0; ks < 8; ks++) { ldsm_x4_t(aO[ks], sb + wo_addr(tv) + ks * 1024); ldsm_x4_t(aO[8 + ks], sb + (wo_addr(tv) ^ 32) + ks * 1024); }
        named_bar(0, 256);
        if (threadIdx.x == 0) {
          fence_async_smem();
          mbar_expect_tx(sb + BAR_P + 16, 4 * 16384);
          for (int q = 0; q < 4; q++) tma_load_2d(sb + OFF_WOR + q * 16384, &maps.wo, h * 32, j * 2048 + 1024 + q * 256, sb + BAR_P + 16);
        }
        __syncwarp();
        tref = gtime() / T_SLIP * T_SLIP - T_SLIP;
      }
    }
  }
}

#undef j
#undef s
#undef sv
#undef xm
#undef wq

__global__ void __launch_bounds__(256, 1) __cluster_dims__(2, 1, 1)
chain_kernel(const __grid_constant__ ChainMaps maps, const bf16* __restrict__ mem0, const uint64_t xbase) {
  using namespace chain;
  extern __shared__ uint8_t smem_raw[];
  uint32_t sb = smem_u32(smem_raw);
  PIN(sb);
  if (sb != SB_LO + (blockIdx.x & 1) * RANK_BIT || mapa(sb, (blockIdx.x & 1) ^ 1) != (sb ^ RANK_BIT)) __trap();
  const int tid = threadIdx.x;
  const int h = blockIdx.x >> 2, role = (blockIdx.x >> 1) & 1, j = blockIdx.x & 1;
  if (tid == 0) {
    for (int i = 0; i < 9; i++) mbar_init(sb + OFF_BAR + 8 * i, 1);
    asm volatile("fence.mbarrier_init.release.cluster;" ::: "memory");
    const uint32_t xl = (uint32_t)xbase;
    sts32(sb + CT_BASE, xl); sts32(sb + CT_HEAD, xl + h * xo::HEAD); sts32(sb + CT_OM, xl + xo::OM + (role ? j * 32768 : h * 2048));
    sts32(sb + CT_MP, xl + xo::MEM + (h * 2 + j) * 256); sts32(sb + CT_O, xl + xo::O + (h * 2 + j) * 128); sts32(sb + CT_PF, (h * 2 + j) * 1024);
    sts32(sb + CT_TT, sb + (j ? OFF_KT : OFF_QT));
    if (role == 0) {
      const CUtensorMap* wm = j ? &maps.wk : &maps.wq;
      mbar_expect_tx(sb + BAR_P, 6 * 16384);
      for (int c = 0; c < 3; c++)
        for (int q = 0; q < 2; q++) tma_load_2d(sb + OFF_X + (q * 3 + c) * 16384, wm, h * DH + q * 64, q * 512 + c * 128, sb + BAR_P);
      mbar_expect_tx(sb + BAR_P + 8, 4 * 16384);
      for (int c = 0; c < 2; c++)
        for (int q = 0; q < 2; q++) tma_load_2d(sb + OFF_X + (6 + q * 2 + c) * 16384, wm, h * DH + (q ^ 1) * 64, q * 512 + c * 128, sb + BAR_P + 8);
      mbar_expect_tx(sb + BAR_P + 24, 4 * 16384);
      for (int q = 0; q < 2; q++)
        for (int o = 0; o < 2; o++) tma_load_2d(sb + OFF_WS + (q * 2 + o) * 16384, wm, h * DH + (q ^ o) * 64, q * 512 + 384, sb + BAR_P + 24);
      for (int q = 0; q < 2; q++) tma_prefetch_2d(wm, h * DH + (q ^ 1) * 64, q * 512 + 256);
    } else {
      mbar_expect_tx(sb + BAR_P, 8 * 16384);
      for (int q = 0; q < 4; q++) tma_load_2d(sb + OFF_WOR + q * 16384, &maps.wv, h * DH + j * 64, (q >> 1) * 512 + (q & 1) * 128, sb + BAR_P);
      for (int q = 0; q < 4; q++) tma_load_2d(sb + OFF_WVR + q * 16384, &maps.wv, h * DH + j * 64, (q >> 1) * 512 + 256 + (q & 1) * 128, sb + BAR_P);
    }
  }
  for (int r = 0; r < RING; r++) {
    char* p = (char*)xbase + r * xo::SLOT;
    const int wq = (tid >> 5) & 3;
    if (role == 1) st_relaxed4(p + h * xo::HEAD + xo::VT + (8 * j + 2 * wq + (tid >> 7)) * 512 + (tid & 31) * 16, EMPTY, EMPTY, EMPTY, EMPTY);
    else if (j == 0) st_relaxed4(p + (tid < 128 ? xo::OM + h * 2048 + tid * 16 : h * xo::HEAD + wq * 2048 + xo::VM + (tid & 31) * 16), EMPTY, EMPTY, EMPTY, EMPTY);
    else {
      st_relaxed4(p + h * xo::HEAD + (tid >> 6) * 2048 + 1024 + (tid & 63) * 16, EMPTY, EMPTY, EMPTY, EMPTY);
      if (tid < 32) st_relaxed4(p + xo::MEM + h * 512 + tid * 16, EMPTY, EMPTY, EMPTY, EMPTY);
    }
  }
  __syncthreads();
  if (__shfl_sync(0xffffffffu, tid >> 5, 0) == 0) {
    uint32_t t[2], c[2], ka[4] = {0, 0, 0, 0};
    const uint32_t z = maps.t_step >> 24;
#pragma unroll
    for (int i = 0; i < 2; i++) {
      const uint32_t end = (gtime() & ~31u) + (i ? 2048 : 1024);
      for (int g = z; g < 256 && (int)(gtime() - (end - 96)) < 0; g++) KEEPALIVE(ka, z);
      for (int g = z; g < 256 && (int)((t[i] = gtime()) - end) < 0; g++) {}
      c[i] = (uint32_t)clock64();
    }
    uint32_t v = 0, target = 0;
    if (tid == 0) {
      st_relaxed1(&g_rate[blockIdx.x], (t[1] - t[0]) * 4096u / (c[1] - c[0]));
      __threadfence();
      target = (atomicAdd(&g_epoch, 1u) & ~127u) + 128u;
    }
    target = __shfl_sync(0xffffffffu, target, 0);
    int guard = 0;
    do { asm volatile("ld.acquire.gpu.global.u32 %0, [%1];" : "=r"(v) : "l"(&g_epoch) : "memory"); }
    while (__any_sync(0xffffffffu, (int)(v - target) < 0) && ++guard < (1 << 20));
    const uint4 r4 = ld_relaxed4(&g_rate[tid * 4]);
    uint32_t r = min(__reduce_max_sync(0xffffffffu, umax4(r4.x, r4.y, r4.z, r4.w)), 4 * RATE0);
    if (r < RATE0 + 28) r = RATE0;
    const uint32_t a = (maps.t_step * r / RATE0 + 31) & ~31u, b = (maps.t_phase * r / RATE0 + 31) & ~31u;
    sts128(sb + CT_T, make_uint4(a, b, a - b, r));
  }
  const uint32_t xhi = (uint32_t)(xbase >> 32);
  const int wg = __shfl_sync(0xffffffffu, tid >> 7, 0);
  if (role == 0) {
    if (wg == 0) role_a<0>(maps, mem0, sb, xhi); else role_a<1>(maps, mem0, sb, xhi);
  } else {
    if (wg == 0) role_v<0>(maps, mem0, sb, xhi); else role_v<1>(maps, mem0, sb, xhi);
  }
  __syncwarp();
  cluster_arrive();
  cluster_wait();
}

struct BMaps {
  CUtensorMap q, k, v, out, k8;
  const bf16 *shift_k, *ssm_k, *ssm_D;
};

#define B_SLEEP 200
namespace bp {
constexpr int U_PITCH = (2048 + 128) * 2 + 16;
constexpr int KR_WORDS = 1048;
constexpr int KR_PITCH = 8704;
constexpr int OFF_U = 0;
constexpr int OFF_KR = (8 * U_PITCH + 127) / 128 * 128;
constexpr int Q_OFF = 4352;
constexpr int OFF_BAR = OFF_KR + 8 * KR_PITCH;
constexpr int GROUP_BYTES = OFF_BAR + 128;
constexpr int SMEM = 2 * GROUP_BYTES + 128;
constexpr int NTASK = DM / 8;
static_assert(Q_OFF >= 4224 && Q_OFF + 4096 <= KR_PITCH, "staging does not fit");
}

__device__ __forceinline__ uint32_t bmul2(uint32_t a, uint32_t b) { uint32_t r; asm("mul.rn.bf16x2 %0, %1, %2;" : "=r"(r) : "r"(a), "r"(b)); return r; }
__device__ __forceinline__ uint32_t badd2(uint32_t a, uint32_t b) { uint32_t r; asm("add.rn.bf16x2 %0, %1, %2;" : "=r"(r) : "r"(a), "r"(b)); return r; }

__device__ __forceinline__ void mbar_wait_sleep(uint32_t bar, uint32_t parity) {
  int guard = 0;
  while (!mbar_try(bar, parity)) { __nanosleep(B_SLEEP); if (++guard > (1 << 22)) __trap(); }
}

__device__ __forceinline__ void bpart_body(const BMaps& maps, int first, int stride, int end) {
  using namespace bp;
  extern __shared__ uint8_t smem_all[];
  const int grp = __shfl_sync(0xffffffffu, threadIdx.x >> 8, 0);
  const int lane = keep(threadIdx.x & 31), g = lane >> 2, t = lane & 3;
  const int w = __shfl_sync(0xffffffffu, (threadIdx.x >> 5) & 7, 0);
  const uint32_t sb = ((smem_u32(smem_all) + 127) & ~127u) + grp * GROUP_BYTES;
  const uint32_t kr = sb + OFF_KR + w * KR_PITCH, bar_k = sb + OFF_BAR + 8 * w, bar_q = bar_k + 64;
  if (lane == 0) { mbar_init(bar_k, 1); mbar_init(bar_q, 1); asm volatile("fence.mbarrier_init.release.cluster;" ::: "memory"); }
  if (lane < 16) sts128(sb + OFF_U + w * U_PITCH + lane * 16, make_uint4(0, 0, 0, 0));
  __syncwarp();
  if (grp == 1) { named_bar_arrive(3, 512); named_bar(5, 512); }
  const int lm = lane >> 3, lr = lane & 7;
  uint32_t ph = 0;
  for (int task = first + grp; task < end; task += stride, ph ^= 1) {
    const int d0 = task * 8;
    uint4 x[8];
    {
      const uint4* kf = (const uint4*)(maps.ssm_k + (size_t)(d0 + w) * S_LEN);
#pragma unroll
      for (int it = 0; it < 8; it++) x[it] = __ldg(kf + it * 32 + lane);
    }
    const uint4 ska = __ldg((const uint4*)(maps.shift_k + (d0 + 2 * t) * 4));
    __syncwarp();
    if (lane == 0) {
      mbar_expect_tx(bar_k, 2 * 4096 + 128);
      tma_load_2d(kr + 4096, &maps.k8, d0, w * 256 + 248, bar_k);
      tma_load_2d(kr, &maps.k, d0, w * 256 - 8, bar_k);
      bulk_wait_read<0>();
      tma_load_2d(kr + Q_OFF, &maps.v, d0, w * 256, bar_k);
    }
    __syncwarp();
    if (task == first) named_bar_arrive(5, 512);
    const uint32_t sk[4] = {__byte_perm(ska.x, ska.z, 0x5410), __byte_perm(ska.x, ska.z, 0x7632), __byte_perm(ska.y, ska.w, 0x5410), __byte_perm(ska.y, ska.w, 0x7632)};
    mbar_wait_sleep(bar_k, ph);
    {
      const uint32_t ka = kr + (lane + 8) * 16;
#pragma unroll
      for (int i = 0; i < 8; i++) {
        uint32_t k0[4], k1[4], k2[4], k3[4], v[4], r[4];
        ldsm_x4(k3, ka + i * 512 - 48); ldsm_x4(k2, ka + i * 512 - 32); ldsm_x4(k1, ka + i * 512 - 16); ldsm_x4(k0, ka + i * 512);
        ldsm_x4(v, ka + (Q_OFF - 128) + i * 512);
#pragma unroll
        for (int b = 0; b < 4; b++) {
          uint32_t acc = bmul2(k3[b], sk[3]);
          acc = badd2(acc, bmul2(k2[b], sk[2]));
          acc = badd2(acc, bmul2(k1[b], sk[1]));
          acc = badd2(acc, bmul2(k0[b], sk[0]));
          r[b] = bmul2(acc, v[b]);
        }
        const int ch = 16 + w * 32 + i * 4 + lm;
        stsm_x4_t(sb + OFF_U + lr * U_PITCH + ((ch ^ ((ch >> 3) & 1)) << 4), r[0], r[1], r[2], r[3]);
      }
    }
    __syncwarp();
    {
      const uint32_t c0 = kr, c1 = c0 + (KR_WORDS + 16) * 4;
      uint32_t carry = 0;
#pragma unroll
      for (int it = 0; it < 8; it++) {
        const int blk = it * 32 + lane;
        uint32_t prev = __shfl_up_sync(0xffffffffu, x[it].w, 1);
        if (lane == 0) prev = carry;
        carry = __shfl_sync(0xffffffffu, x[it].w, 31);
        sts128(c0 + (1028 - 4 * blk) * 4, make_uint4(__byte_perm(x[it].w, 0, 0x1032), __byte_perm(x[it].z, 0, 0x1032),
                                                     __byte_perm(x[it].y, 0, 0x1032), __byte_perm(x[it].x, 0, 0x1032)));
        sts128(c1 + (1028 - 4 * blk) * 4, make_uint4(__byte_perm(x[it].w, x[it].z, 0x7610), __byte_perm(x[it].z, x[it].y, 0x7610),
                                                     __byte_perm(x[it].y, x[it].x, 0x7610), __byte_perm(x[it].x, prev, 0x7610)));
      }
      if (lane < 4) { sts128(c0 + (1032 + 4 * lane) * 4, make_uint4(0, 0, 0, 0)); sts128(c1 + (1032 + 4 * lane) * 4, make_uint4(0, 0, 0, 0)); }
      __syncwarp();
    }
    named_bar(3 + grp, 512);
    float acc[16][4];
#pragma unroll
    for (int jn = 0; jn < 16; jn++) { acc[jn][0] = acc[jn][1] = acc[jn][2] = acc[jn][3] = 0.f; }
    {
      const uint32_t ub = sb + OFF_U + w * U_PITCH;
      uint32_t kd = kr + (((g & 1) ? 0 : KR_WORDS + 16) + ((((g & 1) ? 2063 : 2062) - (g - 2 * t)) >> 1)) * 4;
      uint32_t uc = 2 * (8 + lr + (lm >> 1) * 8) + (lm & 1);
#pragma unroll 1
      for (int d0s = 0; d0s < 8; d0s++, kd -= 32, uc -= 2) {
        const uint32_t uf = ub + ((uc ^ ((uc >> 3) & 1)) << 4);
        uint32_t A[3][4];
        A[0][0] = lds32v(kd); A[0][1] = lds32v(kd - 16); A[0][2] = lds32v(kd + 16); A[0][3] = lds32v(kd);
        uint32_t F[8][4];
#pragma unroll
        for (int m = 7; m >= 0; m--) ldsm_x4(F[m], uf + m * 512);
#pragma unroll
        for (int i = 0; i < 16; i++) {
          if (i + 1 < 16) {
            A[(i + 1) % 3][0] = lds32v(kd - 256 * (i + 1)); A[(i + 1) % 3][1] = lds32v(kd - 256 * (i + 1) - 16);
            A[(i + 1) % 3][2] = lds32v(kd - 256 * (i + 1) + 16); A[(i + 1) % 3][3] = lds32v(kd - 256 * (i + 1));
          }
#pragma unroll
          for (int jn = 15; jn >= i; jn--) mma16816(acc[jn], A[i % 3], F[(jn - i) >> 1][((jn - i) & 1) * 2], F[(jn - i) >> 1][((jn - i) & 1) * 2 + 1]);
        }
      }
    }
    named_bar_arrive(3 + (grp ^ 1), 512);
    __syncwarp();
    fence_async_smem();
    __syncwarp();
    if (lane == 0) { mbar_expect_tx(bar_q, 4096); tma_load_2d(kr + Q_OFF, &maps.q, d0, w * 256, bar_q); }
    const uint32_t dpair = __ldg((const uint32_t*)(maps.ssm_D + d0) + t);
    {
      const uint32_t ya = kr + w * 16 + (((lm >> 1) * 8 + lr) * 32) + (lm & 1) * 16;
#pragma unroll
      for (int jn = 0; jn < 16; jn += 2)
        stsm_x4_t(ya + jn * 256, pack_bf16(acc[jn][0], acc[jn][1]), pack_bf16(acc[jn][2], acc[jn][3]),
                  pack_bf16(acc[jn + 1][0], acc[jn + 1][1]), pack_bf16(acc[jn + 1][2], acc[jn + 1][3]));
    }
    named_bar(1 + grp, 256);
    mbar_wait_sleep(bar_q, ph);
    {
      const uint32_t ya = sb + OFF_KR + lr * (KR_PITCH + 16) + (w * 256 + lm * 8) * 2;
#pragma unroll
      for (int i = 0; i < 8; i++) {
        uint32_t y[4], u[4], q[4], r[4];
        ldsm_x4(q, kr + Q_OFF + lane * 16 + i * 512);
        ldsm_x4_t(y, ya + i * 64);
        const int ch = 16 + w * 32 + i * 4 + lm;
        ldsm_x4_t(u, sb + OFF_U + lr * U_PITCH + ((ch ^ ((ch >> 3) & 1)) << 4));
#pragma unroll
        for (int b = 0; b < 4; b++) r[b] = bmul2(q[b], badd2(y[b], bmul2(u[b], dpair)));
        stsm_x4(kr + Q_OFF + lane * 16 + i * 512, r[0], r[1], r[2], r[3]);
      }
      fence_async_smem();
      __syncwarp();
      if (lane == 0) { tma_store_2d(&maps.out, kr + Q_OFF, DM + d0, w * 256); bulk_commit(); }
    }
    named_bar(1 + grp, 256);
  }
  if (lane == 0) bulk_wait<0>();
}

__global__ void __launch_bounds__(512, 1) __cluster_dims__(2, 1, 1) bpart_kernel(const __grid_constant__ BMaps maps, int end) {
  bpart_body(maps, blockIdx.x * 2, gridDim.x * 2, end);
}

struct GemmMaps {
  CUtensorMap o;
  CUtensorMap w;
  CUtensorMap c;
};
namespace k3 {
constexpr int STAGES = 6;
constexpr int W_BYTES = 2 * 8192, O_BYTES = K3_N * 128, STAGE_BYTES = W_BYTES + O_BYTES;
constexpr int TT = (S_LEN + K3_N - 1) / K3_N, NGEMM = TT * (DM / 128), NB = 128 - NGEMM, KSTEPS = HD / 64;
constexpr int SMEM_G = STAGES * STAGE_BYTES + 1024 + 256;
constexpr int SMEM = SMEM_G > bp::SMEM ? SMEM_G : bp::SMEM;
static_assert(STAGE_BYTES % 1024 == 0, "swizzle atoms");
}

__global__ void __launch_bounds__(512, 1)
tail_kernel(const __grid_constant__ GemmMaps maps, const __grid_constant__ BMaps bmaps) {
  using namespace k3;
  if (blockIdx.x < NB) {
    bpart_body(bmaps, bp::NTASK - 2 * NB + 2 * blockIdx.x, bp::NTASK, bp::NTASK);
    return;
  }
  extern __shared__ uint8_t smem_raw[];
  const uint32_t sbase = (smem_u32(smem_raw) + 1023) & ~1023u;
  const uint32_t bars = sbase + STAGES * STAGE_BYTES;
  const int tid = threadIdx.x, warp = tid >> 5;
  const int tt = (blockIdx.x - NB) / 8, ct = (blockIdx.x - NB) % 8;

  if (tid == 0) {
    for (int s = 0; s < STAGES; s++) { mbar_init(bars + 8 * s, 1); mbar_init(bars + 8 * (STAGES + s), 2); }
    asm volatile("fence.mbarrier_init.release.cluster;" ::: "memory");
  }
  __syncthreads();

  if (warp >= 8) {
    if (tid == 256) {
      tma_prefetch_desc(&maps.o);
      for (int k = 0; k < STAGES; k++) {
        const uint32_t full = bars + 8 * k, sa = sbase + k * STAGE_BYTES;
        mbar_expect_tx(full, STAGE_BYTES);
#pragma unroll
        for (int j = 0; j < 2; j++) tma_load_2d(sa + j * 8192, &maps.w, ct * 128 + j * 64, k * 64, full);
      }
      asm volatile("griddepcontrol.wait;" ::: "memory");
      int stage = 0; uint32_t ph = 1;
      for (int k = 0; k < KSTEPS; k++) {
        mbar_wait(bars + 8 * (STAGES + stage), ph);
        const uint32_t full = bars + 8 * stage, sa = sbase + stage * STAGE_BYTES;
        const bool pre = k < STAGES;
        if (!pre) mbar_expect_tx(full, STAGE_BYTES);
        tma_load_2d(sa + W_BYTES, &maps.o, k * 64, tt * K3_N, full);
        if (!pre) {
#pragma unroll
          for (int j = 0; j < 2; j++) tma_load_2d(sa + j * 8192, &maps.w, ct * 128 + j * 64, k * 64, full);
        }
        if (++stage == STAGES) { stage = 0; ph ^= 1; }
      }
    }
  } else {
    const int wg = warp >> 2, lane = tid & 31, wq = warp & 3;
    int stage = 0; uint32_t ph = 0;
    float acc[K3_N / 2];
    int prev = -1;
    for (int k = 0; k < KSTEPS; k++) {
      mbar_wait(bars + 8 * stage, ph);
      const uint32_t sa = sbase + stage * STAGE_BYTES;
      wg_fence();
#pragma unroll
      for (int kk = 0; kk < 4; kk++) {
        const uint64_t da = make_desc(sa + wg * 8192 + kk * 2048, 16, 1024, 1);
        const uint64_t db = make_desc(sa + W_BYTES + kk * 32, 16, 1024, 1);
        wgmma_k3_ss_ta(acc, da, db, (k | kk) != 0);
      }
      wg_commit();
      if (prev >= 0) { wg_wait<1>(); if ((tid & 127) == 0) mbar_arrive(bars + 8 * (STAGES + prev)); }
      prev = stage;
      if (++stage == STAGES) { stage = 0; ph ^= 1; }
    }
    wg_wait<0>();
#pragma unroll
    for (int i = 0; i < K3_N / 2; i++) asm volatile("" : "+f"(acc[i]) :: "memory");
    named_bar(1, 256);
    const uint32_t ebuf = sbase + wg * STAGE_BYTES;
    const uint32_t ea = ebuf + ((lane >> 4) * 8 + (lane & 7)) * 128 + (((2 * wq + ((lane >> 3) & 1)) ^ (lane & 7)) << 4);
#pragma unroll
    for (int i = 0; i < K3_N / 8; i += 2) {
      const int i1 = i + 1 < K3_N / 8 ? i + 1 : i;
      stsm_x4_t(ea + i * 1024, pack_bf16(acc[4 * i], acc[4 * i + 1]), pack_bf16(acc[4 * i + 2], acc[4 * i + 3]),
                pack_bf16(acc[4 * i1], acc[4 * i1 + 1]), pack_bf16(acc[4 * i1 + 2], acc[4 * i1 + 3]));
    }
    fence_async_smem();
    named_bar(2 + wg, 128);
    if ((tid & 127) == 0) {
      tma_store_2d(&maps.c, ebuf, ct * 128 + wg * 64, tt * K3_N);
      bulk_commit();
      bulk_wait<0>();
    }
  }
}

typedef CUresult (*EncodeFn)(CUtensorMap*, CUtensorMapDataType, cuuint32_t, void*, const cuuint64_t*, const cuuint64_t*,
                             const cuuint32_t*, const cuuint32_t*, CUtensorMapInterleave, CUtensorMapSwizzle,
                             CUtensorMapL2promotion, CUtensorMapFloatOOBfill);

void make_map(EncodeFn enc, CUtensorMap* m, const void* ptr, uint64_t cols, uint64_t rows, uint64_t pitch_elems,
              uint32_t box_cols, uint32_t box_rows, CUtensorMapSwizzle swz,
              CUtensorMapL2promotion promo = CU_TENSOR_MAP_L2_PROMOTION_L2_128B) {
  cuuint64_t dims[2] = {cols, rows};
  cuuint64_t strides[1] = {pitch_elems * 2};
  cuuint32_t box[2] = {box_cols, box_rows};
  cuuint32_t es[2] = {1, 1};
  enc(m, CU_TENSOR_MAP_DATA_TYPE_BFLOAT16, 2, const_cast<void*>(ptr), dims, strides, box, es, CU_TENSOR_MAP_INTERLEAVE_NONE, swz,
      promo, CU_TENSOR_MAP_FLOAT_OOB_FILL_NONE);
}

void make_map_nd(EncodeFn enc, CUtensorMap* m, const void* ptr, int rank, const uint64_t* dims, const uint64_t* strides_elems,
                 const uint32_t* box, CUtensorMapSwizzle swz) {
  cuuint64_t d[5], st[4]; cuuint32_t b[5], es[5];
  for (int i = 0; i < rank; i++) { d[i] = dims[i]; b[i] = box[i]; es[i] = 1; if (i) st[i - 1] = strides_elems[i] * 2; }
  enc(m, CU_TENSOR_MAP_DATA_TYPE_BFLOAT16, rank, const_cast<void*>(ptr), d, st, b, es, CU_TENSOR_MAP_INTERLEAVE_NONE, swz,
      CU_TENSOR_MAP_L2_PROMOTION_L2_128B, CU_TENSOR_MAP_FLOAT_OOB_FILL_NONE);
}

}

extern "C" void kernel_launch(void* const* d_in, const int* in_sizes, int n_in, void* d_out, int out_size) {
  (void)in_sizes; (void)n_in; (void)out_size;
  const bf16* x = (const bf16*)d_in[0];
  const bf16* mem0 = (const bf16*)d_in[1];
  const bf16* Wq = (const bf16*)d_in[2];
  const bf16* Wk = (const bf16*)d_in[3];
  const bf16* Wv = (const bf16*)d_in[4];
  const bf16* Wo = (const bf16*)d_in[5];
  const bf16* Bq = (const bf16*)d_in[7];
  const bf16* Bk = (const bf16*)d_in[8];
  const bf16* Bv = (const bf16*)d_in[9];
  const bf16* shift_k = (const bf16*)d_in[10];
  const bf16* ssm_k = (const bf16*)d_in[11];
  const bf16* ssm_D = (const bf16*)d_in[12];
  bf16* out = (bf16*)d_out;

  static EncodeFn enc = nullptr;
  static uint64_t xbase0;
  static int nsm = 132;
  static cudaStream_t s1;
  static cudaEvent_t ev_fork, ev_join;
  if (!enc) {
    cudaDriverEntryPointQueryResult qr;
    void* fn = nullptr;
    cudaGetDriverEntryPoint("cuTensorMapEncodeTiled", &fn, cudaEnableDefault, &qr);
    enc = (EncodeFn)fn;
    void* ps = nullptr;
    cudaGetSymbolAddress(&ps, g_scratch);
    xbase0 = (uint64_t)ps;
    if ((xbase0 >> 32) != ((xbase0 + xo::BYTES - 1) >> 32)) xbase0 += xo::BYTES;
    cudaFuncSetAttribute(tail_kernel, cudaFuncAttributeMaxDynamicSharedMemorySize, k3::SMEM);
    cudaFuncSetAttribute(chain_kernel, cudaFuncAttributeMaxDynamicSharedMemorySize, chain::SMEM);
    cudaFuncSetAttribute(bpart_kernel, cudaFuncAttributeMaxDynamicSharedMemorySize, bp::SMEM);
    cudaStreamCreateWithFlags(&s1, cudaStreamNonBlocking);
    cudaEventCreateWithFlags(&ev_fork, cudaEventDisableTiming);
    cudaEventCreateWithFlags(&ev_join, cudaEventDisableTiming);
    int dev = 0; cudaGetDevice(&dev);
    cudaDeviceGetAttribute(&nsm, cudaDevAttrMultiProcessorCount, dev);
  }
  uint64_t xbase = xbase0;
  const CUtensorMapSwizzle SW128 = CU_TENSOR_MAP_SWIZZLE_128B, SW64 = CU_TENSOR_MAP_SWIZZLE_64B;
  GemmMaps m3; ChainMaps mc;
  make_map(enc, &m3.o, (void*)(xbase + xo::O), HD, S_LEN, HD, 64, K3_N, SW128);
  make_map(enc, &m3.w, Wo, DM, HD, DM, 64, 64, SW128);
  make_map(enc, &m3.c, out, DM, S_LEN, OUT_LD, 64, K3_N, SW128);
  const CUtensorMapL2promotion P256 = CU_TENSOR_MAP_L2_PROMOTION_L2_256B;
  make_map(enc, &mc.wq, Wq, HD, DM, HD, 64, 128, SW128, P256);
  make_map(enc, &mc.wk, Wk, HD, DM, HD, 64, 128, SW128, P256);
  make_map(enc, &mc.wv, Wv, HD, DM, HD, 64, 128, SW128, P256);
  make_map(enc, &mc.wo, Wo, DM, HD, DM, 32, 256, SW64, P256);
  {
    const uint64_t dx[3] = {64, S_LEN, DM / 64}, sx[3] = {1, DM, 64};
    const uint32_t bx[3] = {64, SEG, 8};
    make_map_nd(enc, &mc.x, x, 3, dx, sx, bx, SW128);
    const uint32_t bq[3] = {64, SEG, 4};
    make_map_nd(enc, &mc.xq, x, 3, dx, sx, bq, SW128);
    mc.xp = (const char*)x;
  }

  const int skip = 0;
  mc.t_step = T_STEP; mc.t_phase = T_PHASE;
  BMaps mb;
  const CUtensorMapSwizzle SWN = CU_TENSOR_MAP_SWIZZLE_NONE;
  make_map(enc, &mb.k, Bk, DM, S_LEN, DM, 8, 256, SWN);
  make_map(enc, &mb.q, Bq, DM, S_LEN, DM, 8, 256, SWN);
  make_map(enc, &mb.v, Bv, DM, S_LEN, DM, 8, 256, SWN);
  mb.shift_k = shift_k; mb.ssm_k = ssm_k; mb.ssm_D = ssm_D;
  make_map(enc, &mb.out, out, OUT_LD, S_LEN, OUT_LD, 8, 256, SWN);
  make_map(enc, &mb.k8, Bk, DM, S_LEN, DM, 8, 8, SWN);
  cudaStream_t s0 = cudaStreamPerThread;
  const int nb = nsm >= 132 ? 4 : 2, ntask1 = bp::NTASK - 2 * k3::NB;
  const bool fork = nsm >= 130 && !(skip & 16);
  if (fork) {
    cudaEventRecord(ev_fork, s0);
    cudaStreamWaitEvent(s1, ev_fork, 0);
    if (!(skip & 1)) bpart_kernel<<<nb, 512, bp::SMEM, s1>>>(mb, ntask1);
    cudaEventRecord(ev_join, s1);
  } else if (!(skip & 1)) {
    bpart_kernel<<<ntask1 / 2, 512, bp::SMEM, s0>>>(mb, ntask1);
  }
  if (!(skip & 4)) chain_kernel<<<128, 256, chain::SMEM, s0>>>(mc, mem0, xbase);
  if (!(skip & 8)) {
    cudaLaunchAttribute pdl[1];
    pdl[0].id = cudaLaunchAttributeProgrammaticStreamSerialization;
    pdl[0].val.programmaticStreamSerializationAllowed = 1;
    cudaLaunchConfig_t cfg = {};
    cfg.gridDim = dim3(128); cfg.blockDim = dim3(512); cfg.dynamicSmemBytes = k3::SMEM; cfg.stream = s0;
    cfg.attrs = pdl; cfg.numAttrs = 1;
    cudaLaunchKernelEx(&cfg, tail_kernel, m3, mb);
  }
  if (fork) cudaStreamWaitEvent(s0, ev_join, 0);
}
```

```cpp
#include <cuda_runtime.h>
#include <cuda_bf16.h>
#include <cuda.h>
#include <stdint.h>

namespace {

constexpr int S_LEN = 2048;
constexpr int DM = 1024;
constexpr int NH = 32;
constexpr int DH = 128;
constexpr int HD = NH * DH;
constexpr int SEG = 32;
constexpr int NSEG = S_LEN / SEG;
constexpr int OUT_LD = 2048;

typedef __nv_bfloat16 bf16;
#define K3_N 160

__device__ __forceinline__ uint32_t smem_u32(const void* p) { return (uint32_t)__cvta_generic_to_shared(p); }

__device__ __forceinline__ void mbar_init(uint32_t bar, uint32_t count) {
  asm volatile("mbarrier.init.shared::cta.b64 [%0], %1;" ::"r"(bar), "r"(count) : "memory");
}
__device__ __forceinline__ void mbar_expect_tx(uint32_t bar, uint32_t bytes) {
  asm volatile("mbarrier.arrive.expect_tx.shared::cta.b64 _, [%0], %1;" ::"r"(bar), "r"(bytes) : "memory");
}
__device__ __forceinline__ void mbar_arrive(uint32_t bar) {
  asm volatile("mbarrier.arrive.shared::cta.b64 _, [%0];" ::"r"(bar) : "memory");
}
__device__ __forceinline__ bool mbar_try(uint32_t bar, uint32_t parity) {
  uint32_t ok;
  asm volatile("{.reg .pred p; mbarrier.try_wait.parity.shared::cta.b64 p, [%1], %2; selp.u32 %0, 1, 0, p;}"
               : "=r"(ok) : "r"(bar), "r"(parity) : "memory");
  return ok;
}
__device__ __forceinline__ bool mbar_test(uint32_t bar, uint32_t parity) {
  uint32_t ok;
  asm volatile("{.reg .pred p; mbarrier.test_wait.parity.shared::cta.b64 p, [%1], %2; selp.u32 %0, 1, 0, p;}"
               : "=r"(ok) : "r"(bar), "r"(parity) : "memory");
  return ok;
}
template <int HINT = 1>
__device__ __forceinline__ void mbar_wait(uint32_t bar, uint32_t parity) {
  int guard = 0;
  while (__builtin_expect(!mbar_try(bar, parity), HINT)) { if (++guard > (1 << 22)) __trap(); }
}
__device__ __forceinline__ void tma_load_2d(uint32_t dst, const CUtensorMap* map, int c0, int c1, uint32_t bar) {
  asm volatile("cp.async.bulk.tensor.2d.shared::cluster.global.mbarrier::complete_tx::bytes [%0], [%1, {%3, %4}], [%2];"
               ::"r"(dst), "l"(map), "r"(bar), "r"(c0), "r"(c1) : "memory");
}
__device__ __forceinline__ void tma_store_2d(const CUtensorMap* map, uint32_t src, int c0, int c1) {
  asm volatile("cp.async.bulk.tensor.2d.global.shared::cta.bulk_group [%0, {%2, %3}], [%1];"
               ::"l"(map), "r"(src), "r"(c0), "r"(c1) : "memory");
}
__device__ __forceinline__ void tma_prefetch_2d(const CUtensorMap* map, int c0, int c1) {
  asm volatile("cp.async.bulk.prefetch.tensor.2d.L2.global [%0, {%1, %2}];" ::"l"(map), "r"(c0), "r"(c1) : "memory");
}
__device__ __forceinline__ void tma_prefetch_desc(const CUtensorMap* map) {
  asm volatile("prefetch.tensormap [%0];" ::"l"(map) : "memory");
}
__device__ __forceinline__ void fence_async_smem() { asm volatile("fence.proxy.async.shared::cta;" ::: "memory"); }
__device__ __forceinline__ void bulk_commit() { asm volatile("cp.async.bulk.commit_group;" ::: "memory"); }
template <int N> __device__ __forceinline__ void bulk_wait_read() { asm volatile("cp.async.bulk.wait_group.read %0;" ::"n"(N) : "memory"); }
template <int N> __device__ __forceinline__ void bulk_wait() { asm volatile("cp.async.bulk.wait_group %0;" ::"n"(N) : "memory"); }
__device__ __forceinline__ void named_bar(int id, int n) { asm volatile("bar.sync %0, %1;" ::"r"(id), "r"(n) : "memory"); }

__device__ __forceinline__ void named_bar_arrive(int id, int n) { asm volatile("bar.arrive %0, %1;" ::"r"(id), "r"(n) : "memory"); }
__device__ __forceinline__ float ex2(float x) { float y; asm("ex2.approx.ftz.f32 %0, %1;" : "=f"(y) : "f"(x)); return y; }
__device__ __forceinline__ float rcp(float x) { float y; asm("rcp.approx.ftz.f32 %0, %1;" : "=f"(y) : "f"(x)); return y; }

__device__ __forceinline__ void sts32(uint32_t a, uint32_t x) { asm volatile("st.shared.b32 [%0], %1;" ::"r"(a), "r"(x) : "memory"); }
__device__ __forceinline__ uint32_t lds32(uint32_t a) { uint32_t x; asm volatile("ld.shared.b32 %0, [%1];" : "=r"(x) : "r"(a) : "memory"); return x; }
__device__ __forceinline__ uint32_t lds32v(uint32_t a) { uint32_t x; asm volatile("ld.volatile.shared.b32 %0, [%1];" : "=r"(x) : "r"(a) : "memory"); return x; }
__device__ __forceinline__ void sts128(uint32_t a, const uint4& v) { asm volatile("st.shared.v4.b32 [%0], {%1,%2,%3,%4};" ::"r"(a), "r"(v.x), "r"(v.y), "r"(v.z), "r"(v.w) : "memory"); }
__device__ __forceinline__ void sts128f(uint32_t a, const float4& v) { asm volatile("st.shared.v4.f32 [%0], {%1,%2,%3,%4};" ::"r"(a), "f"(v.x), "f"(v.y), "f"(v.z), "f"(v.w) : "memory"); }
__device__ __forceinline__ uint4 lds128(uint32_t a) { uint4 v; asm volatile("ld.shared.v4.b32 {%0,%1,%2,%3}, [%4];" : "=r"(v.x), "=r"(v.y), "=r"(v.z), "=r"(v.w) : "r"(a) : "memory"); return v; }
__device__ __forceinline__ float4 lds128f(uint32_t a) { float4 v; asm volatile("ld.shared.v4.f32 {%0,%1,%2,%3}, [%4];" : "=f"(v.x), "=f"(v.y), "=f"(v.z), "=f"(v.w) : "r"(a) : "memory"); return v; }

__device__ __forceinline__ void cp_async16(uint32_t dst, const void* src) { asm volatile("cp.async.cg.shared.global [%0], [%1], 16;" ::"r"(dst), "l"(src) : "memory"); }
__device__ __forceinline__ void cp_async_commit() { asm volatile("cp.async.commit_group;" ::: "memory"); }
template <int N> __device__ __forceinline__ void cp_async_wait_group() { asm volatile("cp.async.wait_group %0;" ::"n"(N) : "memory"); }

__device__ __forceinline__ void wg_fence() { asm volatile("wgmma.fence.sync.aligned;" ::: "memory"); }
__device__ __forceinline__ void wg_commit() { asm volatile("wgmma.commit_group.sync.aligned;" ::: "memory"); }
template <int N> __device__ __forceinline__ void wg_wait() { asm volatile("wgmma.wait_group.sync.aligned %0;" ::"n"(N) : "memory"); }
__device__ __forceinline__ uint64_t make_desc(uint32_t addr, uint32_t lbo, uint32_t sbo, uint32_t swz) {
  return (uint64_t)((addr & 0x3FFFF) >> 4) | ((uint64_t)(lbo >> 4) << 16) | ((uint64_t)(sbo >> 4) << 32) | ((uint64_t)swz << 62);
}

__device__ __forceinline__ void ldsm_x4(uint32_t (&r)[4], uint32_t addr) {
  asm volatile("ldmatrix.sync.aligned.m8n8.x4.shared.b16 {%0,%1,%2,%3}, [%4];"
               : "=r"(r[0]), "=r"(r[1]), "=r"(r[2]), "=r"(r[3]) : "r"(addr) : "memory");
}
__device__ __forceinline__ void ldsm_x4_t(uint32_t (&r)[4], uint32_t addr) {
  asm volatile("ldmatrix.sync.aligned.m8n8.x4.trans.shared.b16 {%0,%1,%2,%3}, [%4];"
               : "=r"(r[0]), "=r"(r[1]), "=r"(r[2]), "=r"(r[3]) : "r"(addr) : "memory");
}
__device__ __forceinline__ void stsm_x4(uint32_t addr, uint32_t r0, uint32_t r1, uint32_t r2, uint32_t r3) {
  asm volatile("stmatrix.sync.aligned.m8n8.x4.shared.b16 [%0], {%1,%2,%3,%4};"
               ::"r"(addr), "r"(r0), "r"(r1), "r"(r2), "r"(r3) : "memory");
}
__device__ __forceinline__ void stsm_x4_t(uint32_t addr, uint32_t r0, uint32_t r1, uint32_t r2, uint32_t r3) {
  asm volatile("stmatrix.sync.aligned.m8n8.x4.trans.shared.b16 [%0], {%1,%2,%3,%4};" ::"r"(addr), "r"(r0), "r"(r1), "r"(r2), "r"(r3) : "memory");
}
__device__ __forceinline__ void mma16816(float (&c)[4], const uint32_t (&a)[4], uint32_t b0, uint32_t b1) {
  asm volatile("mma.sync.aligned.m16n8k16.row.col.f32.bf16.bf16.f32 {%0,%1,%2,%3}, {%4,%5,%6,%7}, {%8,%9}, {%0,%1,%2,%3};"
               : "+f"(c[0]), "+f"(c[1]), "+f"(c[2]), "+f"(c[3])
               : "r"(a[0]), "r"(a[1]), "r"(a[2]), "r"(a[3]), "r"(b0), "r"(b1));
}
__device__ __forceinline__ void mma1688(float (&c)[4], uint32_t a0, uint32_t a1, uint32_t b0) {
  asm volatile("mma.sync.aligned.m16n8k8.row.col.f32.bf16.bf16.f32 {%0,%1,%2,%3}, {%4,%5}, {%6}, {%0,%1,%2,%3};"
               : "+f"(c[0]), "+f"(c[1]), "+f"(c[2]), "+f"(c[3]) : "r"(a0), "r"(a1), "r"(b0));
}
__device__ __forceinline__ uint32_t pack_bf16(float lo, float hi) {
  uint32_t r;
  asm("cvt.rn.bf16x2.f32 %0, %1, %2;" : "=r"(r) : "f"(hi), "f"(lo));
  return r;
}
__device__ __forceinline__ float bf_lo(uint32_t w) { return __uint_as_float(w << 16); }
__device__ __forceinline__ float bf_hi(uint32_t w) { return __uint_as_float(w & 0xFFFF0000u); }

__device__ __forceinline__ uint4 ld_relaxed4(const void* p) {
  uint4 v;
  asm volatile("ld.relaxed.gpu.global.v4.u32 {%0,%1,%2,%3}, [%4];" : "=r"(v.x), "=r"(v.y), "=r"(v.z), "=r"(v.w) : "l"(p) : "memory");
  return v;
}
__device__ __forceinline__ void st_relaxed4(void* p, uint32_t a, uint32_t b, uint32_t c, uint32_t d) {
  asm volatile("st.relaxed.gpu.global.v4.u32 [%0], {%1,%2,%3,%4};" ::"l"(p), "r"(a), "r"(b), "r"(c), "r"(d) : "memory");
}
__device__ __forceinline__ void st_relaxed2(void* p, uint32_t a, uint32_t b) {
  asm volatile("st.relaxed.gpu.global.v2.u32 [%0], {%1,%2};" ::"l"(p), "r"(a), "r"(b) : "memory");
}
__device__ __forceinline__ void st_relaxed1(void* p, uint32_t a) {
  asm volatile("st.relaxed.gpu.global.u32 [%0], %1;" ::"l"(p), "r"(a) : "memory");
}

__device__ __forceinline__ uint2 ld_relaxed2(const void* p) {
  uint2 v;
  asm volatile("ld.relaxed.gpu.global.v2.u32 {%0,%1}, [%2];" : "=r"(v.x), "=r"(v.y) : "l"(p) : "memory");
  return v;
}
__device__ __forceinline__ void sts64(uint32_t a, uint32_t x, uint32_t y) { asm volatile("st.shared.v2.b32 [%0], {%1,%2};" ::"r"(a), "r"(x), "r"(y) : "memory"); }
__device__ __forceinline__ uint2 lds64(uint32_t a) { uint2 v; asm volatile("ld.shared.v2.b32 {%0,%1}, [%2];" : "=r"(v.x), "=r"(v.y) : "r"(a) : "memory"); return v; }
__device__ __forceinline__ void lds128r(uint32_t (&r)[4], uint32_t a) {
  asm volatile("ld.shared.v4.b32 {%0,%1,%2,%3}, [%4];" : "=r"(r[0]), "=r"(r[1]), "=r"(r[2]), "=r"(r[3]) : "r"(a) : "memory");
}
__device__ __forceinline__ uint32_t mapa(uint32_t addr, uint32_t rank) { uint32_t r; asm volatile("mapa.shared::cluster.u32 %0, %1, %2;" : "=r"(r) : "r"(addr), "r"(rank)); return r; }
__device__ __forceinline__ void st_async1(uint32_t dst, uint32_t a, uint32_t bar) {
  asm volatile("st.async.weak.shared::cluster.mbarrier::complete_tx::bytes.b32 [%0], %1, [%2];" ::"r"(dst), "r"(a), "r"(bar) : "memory");
}
__device__ __forceinline__ void st_async2(uint32_t dst, uint32_t a, uint32_t b, uint32_t bar) {
  asm volatile("st.async.weak.shared::cluster.mbarrier::complete_tx::bytes.v2.b32 [%0], {%1,%2}, [%3];" ::"r"(dst), "r"(a), "r"(b), "r"(bar) : "memory");
}
__device__ __forceinline__ void cluster_arrive() { asm volatile("barrier.cluster.arrive.relaxed.aligned;" ::: "memory"); }
__device__ __forceinline__ void cluster_wait() { asm volatile("barrier.cluster.wait.acquire.aligned;" ::: "memory"); }

__device__ __forceinline__ void wgmma_k3_ss_ta(float (&d)[80], uint64_t da, uint64_t db, int scale_d) {
  asm volatile("{.reg .pred p; setp.ne.b32 p, %82, 0;\n"
    "wgmma.mma_async.sync.aligned.m64n160k16.f32.bf16.bf16 {%0, %1, %2, %3, %4, %5, %6, %7, %8, %9, %10, %11, %12, %13, %14, %15, %16, %17, %18, %19, %20, %21, %22, %23, %24, %25, %26, %27, %28, %29, %30, %31, %32, %33, %34, %35, %36, %37, %38, %39, %40, %41, %42, %43, %44, %45, %46, %47, %48, %49, %50, %51, %52, %53, %54, %55, %56, %57, %58, %59, %60, %61, %62, %63, %64, %65, %66, %67, %68, %69, %70, %71, %72, %73, %74, %75, %76, %77, %78, %79}, %80, %81, p, 1, 1, 1, 0;}"
    : "+f"(d[0]), "+f"(d[1]), "+f"(d[2]), "+f"(d[3]), "+f"(d[4]), "+f"(d[5]), "+f"(d[6]), "+f"(d[7]), "+f"(d[8]), "+f"(d[9]), "+f"(d[10]), "+f"(d[11]), "+f"(d[12]), "+f"(d[13]), "+f"(d[14]), "+f"(d[15]), "+f"(d[16]), "+f"(d[17]), "+f"(d[18]), "+f"(d[19]), "+f"(d[20]), "+f"(d[21]), "+f"(d[22]), "+f"(d[23]), "+f"(d[24]), "+f"(d[25]), "+f"(d[26]), "+f"(d[27]), "+f"(d[28]), "+f"(d[29]), "+f"(d[30]), "+f"(d[31]), "+f"(d[32]), "+f"(d[33]), "+f"(d[34]), "+f"(d[35]), "+f"(d[36]), "+f"(d[37]), "+f"(d[38]), "+f"(d[39]), "+f"(d[40]), "+f"(d[41]), "+f"(d[42]), "+f"(d[43]), "+f"(d[44]), "+f"(d[45]), "+f"(d[46]), "+f"(d[47]), "+f"(d[48]), "+f"(d[49]), "+f"(d[50]), "+f"(d[51]), "+f"(d[52]), "+f"(d[53]), "+f"(d[54]), "+f"(d[55]), "+f"(d[56]), "+f"(d[57]), "+f"(d[58]), "+f"(d[59]), "+f"(d[60]), "+f"(d[61]), "+f"(d[62]), "+f"(d[63]), "+f"(d[64]), "+f"(d[65]), "+f"(d[66]), "+f"(d[67]), "+f"(d[68]), "+f"(d[69]), "+f"(d[70]), "+f"(d[71]), "+f"(d[72]), "+f"(d[73]), "+f"(d[74]), "+f"(d[75]), "+f"(d[76]), "+f"(d[77]), "+f"(d[78]), "+f"(d[79])
    : "l"(da), "l"(db), "r"(scale_d));
}
__device__ __forceinline__ void wgmma_m64n32_ss_ta(float (&d)[16], uint64_t da, uint64_t db, int scale_d) {
  asm volatile("{.reg .pred p; setp.ne.b32 p, %18, 0;\n"
    "wgmma.mma_async.sync.aligned.m64n32k16.f32.bf16.bf16 {%0, %1, %2, %3, %4, %5, %6, %7, %8, %9, %10, %11, %12, %13, %14, %15}, %16, %17, p, 1, 1, 1, 0;}"
    : "+f"(d[0]), "+f"(d[1]), "+f"(d[2]), "+f"(d[3]), "+f"(d[4]), "+f"(d[5]), "+f"(d[6]), "+f"(d[7]), "+f"(d[8]), "+f"(d[9]), "+f"(d[10]), "+f"(d[11]), "+f"(d[12]), "+f"(d[13]), "+f"(d[14]), "+f"(d[15])
    : "l"(da), "l"(db), "r"(scale_d));
}

__device__ __forceinline__ void wgmma_m64n32_rs(float (&d)[16], const uint32_t (&a)[4], uint64_t db, int scale_d) {
  asm volatile("{.reg .pred p; setp.ne.b32 p, %21, 0;\n"
    "wgmma.mma_async.sync.aligned.m64n32k16.f32.bf16.bf16 {%0, %1, %2, %3, %4, %5, %6, %7, %8, %9, %10, %11, %12, %13, %14, %15}, {%16, %17, %18, %19}, %20, p, 1, 1, 0;}"
    : "+f"(d[0]), "+f"(d[1]), "+f"(d[2]), "+f"(d[3]), "+f"(d[4]), "+f"(d[5]), "+f"(d[6]), "+f"(d[7]), "+f"(d[8]), "+f"(d[9]), "+f"(d[10]), "+f"(d[11]), "+f"(d[12]), "+f"(d[13]), "+f"(d[14]), "+f"(d[15])
    : "r"(a[0]), "r"(a[1]), "r"(a[2]), "r"(a[3]), "l"(db), "r"(scale_d));
}

#define X_POS 7
#define T_STEP 2752
#define T_PHASE 1760
#define RATE0 2295
#define T_LAG 32
#define T_TOL 192
#define T_SLIP 640
#define O_FIX 5
#define NTMP 4
#define V_PRE 6
#define SFENCE(i) asm volatile("{.reg .pred p; setp.eq.u32 p, %0, %1; @p trap;}" ::"r"(n), "r"(4096 + (i)) : "memory")
constexpr int RING = 4;
constexpr uint32_t EMPTY = 0xFFFFFFFFu;
namespace xo {
constexpr uint32_t SLOT = 1u << 20, HEAD = 16384;
constexpr uint32_t VM = 512;
constexpr uint32_t PT = 1024;
constexpr uint32_t PM = 1536;
constexpr uint32_t VT = 8192;
constexpr uint32_t MEM = NH * HEAD;
constexpr uint32_t OM = MEM + 16384;
constexpr uint32_t O = RING * SLOT;
constexpr uint32_t BYTES = O + S_LEN * HD * 2;
}
__device__ __align__(1024) uint4 g_scratch[2 * (xo::BYTES / 16)];
__device__ unsigned g_epoch;
__device__ __align__(16) unsigned g_rate[128];

struct ChainMaps {
  CUtensorMap wq, wk, wv;
  CUtensorMap wo;
  CUtensorMap x, xq;
  const char* xp;
  uint32_t t_step, t_phase;
};

namespace chain {
constexpr int OFF_X = 65536;
constexpr int OFF_MEM = 131072;
constexpr int OFF_WS = 0;
constexpr int OFF_FP = 147456;
constexpr int OFF_KT = 163840;
constexpr int OFF_QT = 180224;
constexpr int OFF_VT = 196608;
constexpr int OFF_PX = 204800;
constexpr int OFF_S4 = OFF_PX + 1536;
constexpr int OFF_QM = 212992;
constexpr int OFF_KM = 215040;
constexpr int OFF_S1 = 217088;
constexpr int OFF_WVR = 0;
constexpr int OFF_WOR = 147456;
constexpr int OFF_RED = 212992;
constexpr int OFF_VPX = 221184;
constexpr int OFF_RX = 223232;
constexpr int OFF_BAR = 229376;
constexpr int BAR_X = OFF_BAR, BAR_TOK = OFF_BAR + 16, BAR_EX = OFF_BAR + 32, BAR_P = OFF_BAR + 40, GRID_TGT = OFF_BAR + 128;
constexpr int CT_BASE = GRID_TGT + 4, CT_HEAD = GRID_TGT + 8, CT_OM = GRID_TGT + 12, CT_MP = GRID_TGT + 16, CT_O = GRID_TGT + 20, CT_PF = GRID_TGT + 24;
constexpr int CT_TT = GRID_TGT + 28, CT_T = GRID_TGT + 32;
constexpr uint32_t RANK_BIT = 1u << 24;
constexpr int OFF_RX1 = OFF_BAR + 256;
constexpr int SMEM = OFF_RX1 + 2048;
constexpr uint32_t SB_LO = 1024;
constexpr float SCALE = 0.08838834764831845f, L2E = 1.4426950408889634f;
}

__device__ __forceinline__ uint32_t umax4(uint32_t a, uint32_t b, uint32_t c, uint32_t d) { return max(max(a, b), max(c, d)); }
__device__ __forceinline__ bool warp_incomplete(uint32_t m) { return __any_sync(0xffffffffu, m == EMPTY); }
#define PIN(x) asm volatile("" : "+r"(x))
#define KEEPALIVE(a, z) do { float _d0, _d1, _d2, _d3; asm volatile("mma.sync.aligned.m16n8k16.row.col.f32.bf16.bf16.f32 {%0,%1,%2,%3}, {%4,%5,%6,%7}, {%4,%5}, {%8,%8,%8,%8};" \
    : "=f"(_d0), "=f"(_d1), "=f"(_d2), "=f"(_d3) : "r"(a[0]), "r"(a[1]), "r"(a[2]), "r"(a[3]), "f"(0.f)); \
      \
    asm volatile("{.reg .pred p; setp.ne.u32 p, %0, 0; @p st.shared.f32 [%0], %1;}" ::"r"(z), "f"(_d0 + _d3) : "memory"); } while (0)
constexpr int POLL_LIMIT = 1 << 15;

__device__ __forceinline__ uint32_t keep(uint32_t x) { return __shfl_sync(0xffffffffu, x, threadIdx.x & 31); }
__device__ __forceinline__ char* gptr(uint32_t hi, uint32_t lo) { return (char*)(((uint64_t)hi << 32) | lo); }
__device__ __forceinline__ uint32_t slot_off(int n) { return ((uint32_t)n & (RING - 1)) * xo::SLOT; }
__device__ __forceinline__ float quad_max(float x) {
  const float a = __shfl_xor_sync(~0u, x, 1), b = __shfl_xor_sync(~0u, x, 2), c = __shfl_xor_sync(~0u, x, 3);
  return fmaxf(fmaxf(x, a), fmaxf(b, c));
}
__device__ __forceinline__ void acc_fence(float (&a)[16]) {
#pragma unroll
  for (int i = 0; i < 16; i++) asm volatile("" : "+f"(a[i]) :: "memory");
}
template <int NB = 1, int STRIDE = 0>
__device__ __forceinline__ void gather_issue(uint32_t dst, const char* src) {
#pragma unroll
  for (int b = 0; b < NB; b++)
#pragma unroll
    for (int i = 0; i < 4; i++) cp_async16(dst + b * STRIDE + i * 512, src + b * STRIDE + i * 512);
  cp_async_commit();
}
template <int NB, int STRIDE>
__device__ __forceinline__ bool gather_incomplete(uint32_t chk) {
  uint32_t m = 0;
#pragma unroll
  for (int b = 0; b < NB; b++) m = max(m, umax4(lds32(chk + b * STRIDE), lds32(chk + b * STRIDE + 512), lds32(chk + b * STRIDE + 1024), lds32(chk + b * STRIDE + 1536)));
  return warp_incomplete(m);
}
__device__ __forceinline__ uint32_t ld_relaxed1(const void* p) {
  uint32_t v;
  asm volatile("ld.relaxed.gpu.global.u32 %0, [%1];" : "=r"(v) : "l"(p) : "memory");
  return v;
}
__device__ __forceinline__ uint32_t gtime() { uint64_t g; asm volatile("mov.u64 %0, %%globaltimer;" : "=l"(g) :: "memory"); return (uint32_t)g; }
#define WAIT_UNTIL(t, ka, alive, id) do { \
    int _d = gtime() - (t); \
    if (__builtin_expect(_d > T_TOL, 0)) do { t += T_SLIP; _d -= T_SLIP; } while (_d > T_TOL); \
    if (alive) for (int _k = 64; _d < -96 && --_k; _d = gtime() - (t)) KEEPALIVE(ka, zr); \
    for (uint32_t _g = 0xFFFFFF80u; (int)(_d & ++_g) < 0;) _d = gtime() - (t); } while (0)
__device__ __forceinline__ void issue_x(uint32_t sb, const CUtensorMap* map, int n, int part, int q = 0) {
  asm volatile("{.reg .pred p; elect.sync _|p, 0xffffffff;\n"
               "@p cp.async.bulk.tensor.3d.shared::cluster.global.mbarrier::complete_tx::bytes [%0], [%1, {%3, %4, %5}], [%2];}"
               ::"r"(sb + chain::OFF_X + part * 32768 + q * 16384), "l"(map), "r"(sb + chain::BAR_X + 8 * part), "r"(0), "r"(n * SEG), "r"(part * 8 + q * 4) : "memory");
}
__device__ __forceinline__ void issue_x_if(uint32_t sb, const CUtensorMap* map, int n, int part, uint32_t on) {
  asm volatile("{.reg .pred p, q; elect.sync _|p, 0xffffffff; setp.ne.and.u32 q, %6, 0, p;\n"
               "@q cp.async.bulk.tensor.3d.shared::cluster.global.mbarrier::complete_tx::bytes [%0], [%1, {%3, %4, %5}], [%2];}"
               ::"r"(sb + chain::OFF_X + part * 32768), "l"(map), "r"(sb + chain::BAR_X + 8 * part), "r"(0), "r"(n * SEG), "r"(part * 8), "r"(on) : "memory");
}
__device__ __forceinline__ void prefetch_l2(const char* p, uint32_t bytes) {
  asm volatile("{.reg .pred p; elect.sync _|p, 0xffffffff; @p cp.async.bulk.prefetch.L2.global [%0], %1;}" ::"l"(p), "r"(bytes) : "memory");
}
__device__ __forceinline__ void expect_elect(uint32_t bar, uint32_t bytes) {
  asm volatile("{.reg .pred p; elect.sync _|p, 0xffffffff; @p mbarrier.arrive.expect_tx.shared::cta.b64 _, [%0], %1;}" ::"r"(bar), "r"(bytes) : "memory");
}
template <int WG> __device__ __forceinline__ constexpr uint64_t xdesc(int ks) {
  return (uint64_t)(((chain::SB_LO + chain::OFF_X + WG * 32768 + (ks >> 2) * 4096 + (ks & 3) * 32) >> 4) + (1u << 16)) |
         ((uint64_t)(64u | (1u << 30)) << 32);
}
template <int WG> __device__ __forceinline__ constexpr uint64_t wdesc(int o, int ks) {
  return (uint64_t)(((chain::SB_LO + chain::OFF_WS + WG * 32768 + o * 16384 + ks * 2048) >> 4) + (1u << 16)) | ((uint64_t)(64u | (1u << 30)) << 32);
}
__device__ __forceinline__ void load_mem0(uint2 (&m)[8], const bf16* __restrict__ mem0) {
#pragma unroll
  for (int r = 0; r < 8; r++) m[r] = ld_relaxed2((const uint2*)(mem0 + r * DM) + threadIdx.x);
}
__device__ __forceinline__ void store_mem0(uint32_t sb, const uint2 (&m)[8]) {
  const uint32_t d = sb + chain::OFF_MEM + threadIdx.x * 64;
  sts128(d, make_uint4(__byte_perm(m[0].x, m[1].x, 0x5410), __byte_perm(m[2].x, m[3].x, 0x5410), __byte_perm(m[4].x, m[5].x, 0x5410), __byte_perm(m[6].x, m[7].x, 0x5410)));
  sts128(d + 16, make_uint4(__byte_perm(m[0].x, m[1].x, 0x7632), __byte_perm(m[2].x, m[3].x, 0x7632), __byte_perm(m[4].x, m[5].x, 0x7632), __byte_perm(m[6].x, m[7].x, 0x7632)));
  sts128(d + 32, make_uint4(__byte_perm(m[0].y, m[1].y, 0x5410), __byte_perm(m[2].y, m[3].y, 0x5410), __byte_perm(m[4].y, m[5].y, 0x5410), __byte_perm(m[6].y, m[7].y, 0x5410)));
  sts128(d + 48, make_uint4(__byte_perm(m[0].y, m[1].y, 0x7632), __byte_perm(m[2].y, m[3].y, 0x7632), __byte_perm(m[4].y, m[5].y, 0x7632), __byte_perm(m[6].y, m[7].y, 0x7632)));
}
template <int K> __device__ __forceinline__ uint32_t loop_zero(int n) { uint32_t z; asm volatile("shr.u32 %0, %1, %2;" : "=r"(z) : "r"(n), "n"(16 + K)); return z; }
#define NEWZ(k) zr = loop_zero<k>(n)

template <int WG>
__device__ __forceinline__ void role_a(const ChainMaps& maps, const bf16* __restrict__ mem0, const uint32_t sb, const uint32_t xbase_hi) {
  using namespace chain;
  const int h = blockIdx.x >> 2;
  const bool J = sb >= RANK_BIT;
  const uint32_t u16 = (threadIdx.x & 96) * 64 + (threadIdx.x & 31) * 16;
  const uint32_t t16 = keep(u16), l16 = keep((threadIdx.x & 31) * 16);
  const uint32_t a_wl = keep((((threadIdx.x >> 4) & 1) * 8 + (threadIdx.x & 7)) * 128 + (((((threadIdx.x >> 4) & 6) + ((threadIdx.x >> 3) & 1)) ^ (threadIdx.x & 7)) << 4));
  const uint32_t xhi = keep(xbase_hi + (t16 >> 16));
#define xh (lds32(sb + CT_HEAD) + t16)
#define xm (lds32(sb + CT_BASE) + t16 + xo::MEM)
#define last_warp __any_sync(0xffffffffu, tv >= 6144)
#define tv (t16 ^ zr)
  const CUtensorMap* wm = J ? &maps.wk : &maps.wq;

  uint32_t aW[2][24][4];
  uint2 m0[8];
  load_mem0(m0, mem0);
  mbar_wait(sb + BAR_P, 0);
#pragma unroll
  for (int ks = 0; ks < 24; ks++) ldsm_x4_t(aW[0][ks], sb + a_wl + OFF_X + WG * 49152 + ks * 2048);
  named_bar(0, 256);
  if (WG == 1 && __any_sync(0xffffffffu, t16 >= 6144)) {
    fence_async_smem();
    if (l16 == 0) {
      mbar_expect_tx(sb + BAR_P + 16, 2 * 16384);
      for (int q = 0; q < 2; q++) tma_load_2d(sb + OFF_X + (4 + q) * 16384, wm, h * DH + (q ^ 1) * 64, q * 512 + 256, sb + BAR_P + 16);
    }
    __syncwarp();
    expect_elect(sb + BAR_X, 32768); expect_elect(sb + BAR_X + 8, 32768); expect_elect(sb + BAR_TOK, 8192);
    issue_x(sb, &maps.x, 0, 0); issue_x(sb, &maps.x, 0, 1);
  }
  mbar_wait(sb + BAR_P + 8, 0);
#pragma unroll
  for (int ks = 0; ks < 16; ks++) ldsm_x4_t(aW[1][ks], sb + a_wl + OFF_X + 6 * 16384 + WG * 32768 + ks * 2048);
  mbar_wait(sb + BAR_P + 16, 0);
#pragma unroll
  for (int ks = 0; ks < 8; ks++) ldsm_x4_t(aW[1][16 + ks], sb + a_wl + OFF_X + (4 + WG) * 16384 + ks * 2048);
  named_bar(0, 256);
  cluster_arrive();
  store_mem0(sb, m0);
  mbar_wait(sb + BAR_P + 24, 0);
  cluster_wait();
  const uint32_t rsb = sb ^ RANK_BIT;
  const uint32_t a_ws = sb + a_wl + OFF_WS + WG * 32768;

  uint32_t ws[2][4][4];
  auto load_ws = [&]() {
#pragma unroll
    for (int q = 0; q < 2; q++) {
      const uint32_t a = a_ws + q * 4096;
      ldsm_x4_t(ws[q][0], a); ldsm_x4_t(ws[q][1], a + 16384); ldsm_x4_t(ws[q][2], a + 2048); ldsm_x4_t(ws[q][3], a + 16384 + 2048);
    }
  };
  uint32_t tref = 0;
#pragma unroll 1
  for (int n = 0; n <= (J ? NSEG : NSEG - 1); n++) {
#define s (n - 1)
#define sv ((int)(n ^ zr) - 1)
    const bool more = __builtin_expect(s + 1 < NSEG, 1);
    uint32_t zr = loop_zero<0>(n);
#define wq ((int)(tv >> 11))
#define lv (l16 ^ zr)
#define gh (xh + slot_off(sv))
    uint32_t tmp[NTMP][4];
    auto load_tmp = [&](int o) {
#pragma unroll
      for (int ks = 0; ks < NTMP; ks++) ldsm_x4_t(tmp[ks], a_ws + o * 16384 + ks * 2048);
    };
    float y[10];
    auto no_p = [&]() {
#pragma unroll
      for (int i = 0; i < 10; i++) asm volatile("mov.b32 %0, %1;" : "=f"(y[i]) : "r"(zr));
    };
    auto finish_p = [&]() {
      const uint32_t gp = gh;
      float sy = ((y[0] + y[1]) + (y[2] + y[3])) + ((y[4] + y[5]) + (y[6] + y[7])) + (y[8] + y[9]);
      const float ry = rcp((sy + __shfl_xor_sync(~0u, sy, 1)) + (__shfl_xor_sync(~0u, sy, 2) + __shfl_xor_sync(~0u, sy, 3)));
      st_relaxed4(gptr(xhi, gp) + xo::PT, pack_bf16(y[2] * ry, y[3] * ry), pack_bf16(y[4] * ry, y[5] * ry), pack_bf16(y[6] * ry, y[7] * ry), pack_bf16(y[8] * ry, y[9] * ry));
      const uint32_t l12 = lv - (lv >> 2);
      st_relaxed1(gptr(xhi, gp - l12) + xo::PM, pack_bf16(y[0] * ry, y[1] * ry));
    };
    auto wait_x = [&]() { mbar_wait<0>(sb + BAR_X + 8 * WG, n & 1); };
    if (__builtin_expect(s < 0, 0)) { load_tmp(1); wait_x(); if (WG == 0) no_p(); }
    else {
      {
        if (WG == 1) { if (__builtin_expect(s > 0, 1)) {
          const uint32_t dst = sb + OFF_MEM + tv + t16 - l16, chk = dst + ((lv >> 5) & 12);
          uint32_t tries = zr;
#pragma unroll 1
          do {
            if (tries) {
              const char* src = gptr(xhi, xm + t16 - l16 + slot_off(sv));
              tref += T_SLIP;
              WAIT_UNTIL(tref, aW[0][0], 1, -1);
              gather_issue<2, 2048>(dst, src);
            }
            KEEPALIVE(aW[0][0], zr);
            cp_async_wait_group<0>();
          } while (gather_incomplete<2, 2048>(chk) && ++tries < POLL_LIMIT);
        } } else if (J == 0) {
          uint32_t tries = s == 0;
#pragma unroll 1
          do {
            if (tries) gather_issue(sb + OFF_VT + tv, gptr(xhi, gh) + xo::VT);
            cp_async_wait_group<0>();
          } while (gather_incomplete<1, 0>(sb + OFF_VT + t16 + ((lv >> 5) & 12)) && ++tries < POLL_LIMIT);
        }
        named_bar(1, 256);
      }
      float c[2][2][4];
#pragma unroll
      for (int i = 0; i < 4; i++) c[i >> 1][i & 1][0] = c[i >> 1][i & 1][1] = c[i >> 1][i & 1][2] = c[i >> 1][i & 1][3] = 0.f;
      {
        const uint32_t a_mem = sb + OFF_MEM + WG * 8192 + l16;
        uint32_t b[4][4];
        bool tok;
        constexpr int PR[16] = {12, 13, 0, 1, 2, 3, 4, 14, 5, 6, 7, 8, 9, 15, 10, 11};
        ldsm_x4_t(b[0], a_mem + PR[0] * 512); ldsm_x4_t(b[1], a_mem + PR[1] * 512);
#pragma unroll
        for (int i = 0; i < 16; i++) {
          if ((i & 1) == 0 && i < 14) {
            ldsm_x4_t(b[(i + 2) & 3], a_mem + PR[i + 2] * 512); ldsm_x4_t(b[(i + 3) & 3], a_mem + PR[i + 3] * 512);
            if (i == 2 || i == 8) { ldsm_x4_t(ws[1][0], a_ws + (i == 2 ? 2 : 3) * 4096); ldsm_x4_t(ws[1][1], a_ws + (i == 2 ? 2 : 3) * 4096 + 16384); }
            if (i == 4 || i == 10) { ldsm_x4_t(ws[1][2], a_ws + (i == 4 ? 2 : 3) * 4096 + 2048); ldsm_x4_t(ws[1][3], a_ws + (i == 4 ? 2 : 3) * 4096 + 16384 + 2048); }
          }
          const int p = PR[i];
          if (p >= 12) {
            const int z = i != 0;
            mma16816(c[0][0], ws[z][0], b[i & 3][0], b[i & 3][1]); mma16816(c[1][0], ws[z][1], b[i & 3][0], b[i & 3][1]);
            mma16816(c[0][1], ws[z][2], b[i & 3][2], b[i & 3][3]); mma16816(c[1][1], ws[z][3], b[i & 3][2], b[i & 3][3]);
          } else {
            mma16816(c[1][0], aW[1][2 * p], b[i & 3][0], b[i & 3][1]); mma16816(c[1][1], aW[1][2 * p + 1], b[i & 3][2], b[i & 3][3]);
            mma16816(c[0][0], aW[0][2 * p], b[i & 3][0], b[i & 3][1]); mma16816(c[0][1], aW[0][2 * p + 1], b[i & 3][2], b[i & 3][3]);
          }
          if (i == 12) tok = mbar_test(sb + BAR_TOK + 8 * (s & 1), (s >> 1) & 1);
          if (i == 15 && __builtin_expect(!tok, 0)) mbar_wait(sb + BAR_TOK + 8 * (s & 1), (s >> 1) & 1);
          if (i == X_POS + 4 * (1 - WG)) { issue_x_if(sb, &maps.x, s + 1, WG, t16 >= 6144 && more); if (WG) __syncwarp(); }
        }
      }
      sts128f(sb + OFF_PX + WG * 512 + t16, make_float4(c[1][0][0] + c[1][1][0], c[1][0][1] + c[1][1][1], c[1][0][2] + c[1][1][2], c[1][0][3] + c[1][1][3]));
      const float4 own = make_float4(c[0][0][0] + c[0][1][0], c[0][0][1] + c[0][1][1], c[0][0][2] + c[0][1][2], c[0][0][3] + c[0][1][3]);
      NEWZ(1);
      uint32_t a = (J ? OFF_KM : OFF_QM) + WG * 1024 + wq * 256 + (lv >> 2);
      uint32_t ra = rsb + a, ra2 = ra + 128, rx = rsb + BAR_EX + zr;
      PIN(a); PIN(ra); PIN(ra2); PIN(rx);
      const uint32_t kt = sb + OFF_KT + (s & 1) * 8192;
#define k_lane ((lv & 240) + ((lv & 256) << 2))
#define a_lane (((lv & 128) << 1) + ((lv & 256) >> 1) + (lv & 112))
      uint32_t kb[4][4], aq = sb + OFF_QM + a_lane, ak = kt + wq * 256 + k_lane;
      PIN(aq);
      if (WG == 0) PIN(ak);
      SFENCE(16);
      named_bar(3, 256);
      {
        const float4 o = lds128f(sb + OFF_PX + (WG ^ 1) * 512 + t16);
        const uint32_t lo = pack_bf16(own.x + o.x, own.y + o.y), hi = pack_bf16(own.z + o.z, own.w + o.w);
        if (J == 1 && more) { st_async1(ra, lo, rx); st_async1(ra2, hi, rx); }
        sts32(sb + a, lo); sts32(sb + a + 128, hi);
      }
      if (J == 0) {
        uint32_t am[4][4];
        auto load_q = [&]() {
#pragma unroll
          for (int p = 0; p < 4; p++) ldsm_x4_t(am[p], aq + p * 512);
        };
        auto scores = [&]() {
          float c0[2][4], c1[2][4];
#pragma unroll
          for (int i = 0; i < 2; i++) { c0[i][0] = c0[i][1] = c0[i][2] = c0[i][3] = 0.f; c1[i][0] = c1[i][1] = c1[i][2] = c1[i][3] = 0.f; }
#pragma unroll
          for (int p = 0; p < 4; p++) { mma16816(c0[p & 1], am[p], kb[p][0], kb[p][1]); mma16816(c1[p & 1], am[p], kb[p][2], kb[p][3]); }
          const uint32_t r1 = pack_bf16((c0[0][0] + c0[1][0]) + (c1[0][2] + c1[1][2]), (c0[0][1] + c0[1][1]) + (c1[0][3] + c1[1][3]));
          return pack_bf16(bf_lo(r1) * SCALE, bf_hi(r1) * SCALE);
        };
        if (WG == 1) {
          if (last_warp) {
            named_bar(7, 256);
            load_q();
            const uint32_t sa = sb + OFF_S1 + (lv >> 1);
            mbar_wait<0>(sb + BAR_EX, s & 1);
#pragma unroll
            for (int p = 0; p < 4; p++) ldsm_x4_t(kb[p], sb + OFF_KM + p * 512 + l16);
            const uint32_t sm = scores();
            sts64(sa, sm, __float_as_uint(quad_max(fmaxf(bf_lo(sm), bf_hi(sm)))));
            named_bar_arrive(9, 160);
          } else {
            named_bar_arrive(7, 256);
          }
          wait_x();
          load_tmp(1);
        } else {
#pragma unroll
          for (int p = 0; p < 4; p++) ldsm_x4(kb[p], ak + p * 2048);
          named_bar(7, 256);
          load_q();
          const uint32_t hb = lds32(sb + CT_HEAD), omb = lds32(sb + CT_OM);
          const char* pvm = gptr(xhi, hb + t16 + slot_off(sv) - (lv >> 1) + (am[3][0] & zr)) + xo::VM;
          uint2 vm0 = ld_relaxed2(pvm), vm1 = ld_relaxed2(pvm + 256);
          sts32(sb + OFF_S4 + l16 + wq * 4, scores());
          named_bar(8, 128);
          const uint4 sc = lds128(sb + OFF_S4 + l16);
          uint32_t vb[4][4];
          {
            const uint32_t va = sb + OFF_VT + t16 + (sc.x & zr);
#pragma unroll
            for (int e = 0; e < 4; e++) lds128r(vb[e], va + e * 512);
          }
          float x[8] = {bf_lo(sc.x), bf_hi(sc.x), bf_lo(sc.y), bf_hi(sc.y), bf_lo(sc.z), bf_hi(sc.z), bf_lo(sc.w), bf_hi(sc.w)};
          const float mt = quad_max(fmaxf(fmaxf(fmaxf(x[0], x[1]), fmaxf(x[2], x[3])), fmaxf(fmaxf(x[4], x[5]), fmaxf(x[6], x[7]))));
          const float mtb = mt * L2E;
#pragma unroll
          for (int i = 0; i < 8; i++) x[i] = ex2(fmaf(x[i], L2E, -mtb));
          uint32_t pa[4], pb[4], p5;
          asm volatile("" : "=r"(pa[1]), "=r"(pa[3]), "=r"(pb[1]), "=r"(pb[3]), "=r"(p5));
          pa[0] = pack_bf16(x[0], x[1]); pa[2] = pack_bf16(x[2], x[3]);
          pb[0] = pack_bf16(x[4], x[5]); pb[2] = pack_bf16(x[6], x[7]);
          float st = ((x[0] + x[1]) + (x[2] + x[3])) + ((x[4] + x[5]) + (x[6] + x[7]));
          asm volatile("" : "+r"(pb[0]), "+r"(pb[2]), "+f"(st));
          float oa[4][4];
#pragma unroll
          for (int e = 0; e < 4; e++) { oa[e][0] = oa[e][1] = oa[e][2] = oa[e][3] = 0.f; mma16816(oa[e], pa, vb[e][0], vb[e][1]); }
          SFENCE(25);
          named_bar(9, 160);
          const uint2 sm2 = lds64(sb + OFF_S1 + (lv >> 1));
          const uint32_t sm = sm2.x;
          const float mx = fmaxf(mt, __uint_as_float(sm2.y));
#pragma unroll
          for (int e = 0; e < 4; e++) mma16816(oa[e], pb, vb[e][2], vb[e][3]);
          const float mb = mx * L2E;
          const float e0 = ex2(fmaf(bf_lo(sm), L2E, -mb)), e1 = ex2(fmaf(bf_hi(sm), L2E, -mb)), ct = ex2(mtb - mb);
          const uint32_t xo0 = omb + wq * 512 + l16;
          if (__builtin_expect(warp_incomplete(max(max(vm0.x, vm1.x), __float_as_uint(mx) & zr)), 0)) {
            uint32_t tries = zr;
#pragma unroll 1
            do { vm0 = ld_relaxed2(pvm); vm1 = ld_relaxed2(pvm + 256); } while (warp_incomplete(max(vm0.x, vm1.x)) && ++tries < POLL_LIMIT);
          }
          named_bar_arrive(10, 256);
          const float sx = fmaf(ct, st, e0 + e1);
          const float s1 = __shfl_xor_sync(~0u, sx, 1), s2 = __shfl_xor_sync(~0u, sx, 2), s3 = __shfl_xor_sync(~0u, sx, 3);
          const uint32_t p4 = pack_bf16(e0, e1);
#pragma unroll
          for (int e = 0; e < 4; e++) { oa[e][0] *= ct; oa[e][1] *= ct; }
          mma1688(oa[0], p4, p5, vm0.x); mma1688(oa[1], p4, p5, vm0.y); mma1688(oa[2], p4, p5, vm1.x); mma1688(oa[3], p4, p5, vm1.y);
          const float rx = rcp((sx + s1) + (s2 + s3));
          st_relaxed4(gptr(xhi, xo0 + slot_off(sv)), pack_bf16(oa[0][0] * rx, oa[0][1] * rx), pack_bf16(oa[1][0] * rx, oa[1][1] * rx),
                      pack_bf16(oa[2][0] * rx, oa[2][1] * rx), pack_bf16(oa[3][0] * rx, oa[3][1] * rx));
          st_relaxed4(gptr(xhi, xo0 + slot_off(sv + 3)), EMPTY, EMPTY, EMPTY, EMPTY);
          load_tmp(1);
          wait_x();
          no_p();
        }
      } else {
        bool xok;
        {
          const int mt = WG | (wq == 3), ktile = wq == 3 ? 2 + WG : wq - 1;
          const uint32_t qt = sb + OFF_QT + (s & 1) * 8192 + mt * 512 + a_lane;
          uint32_t q[8][4];
          if (__any_sync(0xffffffffu, tv < 2048)) {
            named_bar(7, 256);
#pragma unroll
            for (int p = 0; p < 4; p++) ldsm_x4_t(kb[p], sb + OFF_KM + p * 512 + l16);
          } else {
            named_bar_arrive(7, 256);
#pragma unroll
            for (int p = 0; p < 4; p++) ldsm_x4(kb[p], kt + ktile * 256 + k_lane + p * 2048);
          }
#pragma unroll
          for (int i = 0; i < 8; i++) ldsm_x4(q[i], qt + i * 1024);
          __syncwarp();
          float c0[4][4];
#pragma unroll
          for (int i = 0; i < 4; i++) { c0[i][0] = c0[i][1] = c0[i][2] = c0[i][3] = 0.f; mma16816(c0[i], q[i], kb[i >> 1][(i & 1) * 2], kb[i >> 1][(i & 1) * 2 + 1]); }
#pragma unroll
          for (int i = 0; i < 4; i++) mma16816(c0[i], q[4 + i], kb[2 + (i >> 1)][(i & 1) * 2], kb[2 + (i >> 1)][(i & 1) * 2 + 1]);
          load_tmp(1);
          xok = mbar_test(sb + BAR_X + 8 * WG, n & 1);
          NEWZ(3);
          const uint32_t r0 = pack_bf16((c0[0][0] + c0[1][0]) + (c0[2][0] + c0[3][0]), (c0[0][1] + c0[1][1]) + (c0[2][1] + c0[3][1]));
          const uint32_t r1 = pack_bf16((c0[0][2] + c0[1][2]) + (c0[2][2] + c0[3][2]), (c0[0][3] + c0[1][3]) + (c0[2][3] + c0[3][3]));
          const uint32_t sa = wq == 0 ? sb + OFF_S1 + (lv >> 2) + mt * 256 : sb + OFF_S4 + l16 + mt * 4096 + ktile * 4;
          sts32(sa, pack_bf16(bf_lo(r0) * SCALE, bf_hi(r0) * SCALE));
          sts32(sa + (wq == 0 ? 128 : 2048), pack_bf16(bf_lo(r1) * SCALE, bf_hi(r1) * SCALE));
        }
        if (WG == 1) named_bar_arrive(8, 256);
        else {
          if (more) named_bar_arrive(10, 256);
          named_bar(8, 256);
          const uint4 sc = lds128(sb + OFF_S4 + t16); const uint32_t s1 = lds32(sb + OFF_S1 + wq * 128 + (lv >> 2));
          y[0] = bf_lo(s1); y[1] = bf_hi(s1); y[2] = bf_lo(sc.x); y[3] = bf_hi(sc.x); y[4] = bf_lo(sc.y); y[5] = bf_hi(sc.y);
          y[6] = bf_lo(sc.z); y[7] = bf_hi(sc.z); y[8] = bf_lo(sc.w); y[9] = bf_hi(sc.w);
          const int rel = wq * 8 + (int)(lv >> 6) - (int)((lv >> 3) & 6);
          const float NEG = -999292928.f;
#pragma unroll
          for (int e = 0; e < 4; e++) {
            if (e * 8 > rel) y[2 * e + 2] = NEG;
            if (e * 8 + 1 > rel) y[2 * e + 3] = NEG;
          }
          float my = fmaxf(fmaxf(fmaxf(y[0], y[1]), fmaxf(y[2], y[3])), fmaxf(fmaxf(y[4], y[5]), fmaxf(y[6], y[7])));
          my = quad_max(fmaxf(my, fmaxf(y[8], y[9])));
#pragma unroll
          for (int i = 0; i < 10; i++) y[i] = ex2((y[i] - my) * L2E);
          if (!more) finish_p();
        }
        if (!xok && more) wait_x();
      }
    }
    if (more) {
      float acc[16];
      const uint32_t xph = (s + 1) & 1;
      auto batch = [&](const uint32_t (&a)[24][4], int o) {
        wg_fence();
#pragma unroll
        for (int ks = NTMP; ks < 8; ks++) wgmma_m64n32_ss_ta(acc, wdesc<WG>(o, ks), xdesc<WG>(24 + ks), ks != NTMP);
#pragma unroll
        for (int ks = 0; ks < NTMP; ks++) wgmma_m64n32_rs(acc, tmp[ks], xdesc<WG>(24 + ks), 1);
#pragma unroll
        for (int ks = 0; ks < 24; ks++) wgmma_m64n32_rs(acc, a[ks], xdesc<WG>(ks), 1);
        wg_commit();
        SFENCE(50 + o);
      };
      if (WG == 0) named_bar(12, 256);
      else if (__builtin_expect(s >= 0, 1)) named_bar(10, 256);
      batch(aW[1], 1);
      named_bar_arrive(WG ? 12 : 13, 256);
      if (WG == 0 && s >= 0) {
        NEWZ(7);
        const uint32_t g1 = xh + slot_off(sv + 1);
        if (J == 0) gather_issue(sb + OFF_VT + tv, gptr(xhi, g1) + xo::VT);
        else {
          finish_p();
          st_relaxed4(gptr(xhi, g1) + xo::PT, EMPTY, EMPTY, EMPTY, EMPTY);
          st_relaxed1(gptr(xhi, g1 - lv + (lv >> 2)) + xo::PM, EMPTY);
        }
      }
      wg_wait<0>();
      acc_fence(acc);
      load_tmp(0);
#pragma unroll
      for (int i = 0; i < 4; i++) sts128f(sb + OFF_FP + WG * 8192 + t16 + i * 512, make_float4(acc[4 * i], acc[4 * i + 1], acc[4 * i + 2], acc[4 * i + 3]));
      NEWZ(4);
      uint32_t esrc = 0;
      if (WG == 1) { esrc = xm + t16 - l16 + 2048 + slot_off(sv + 1); tref += lds32(sb + CT_T); }
      named_bar(WG ? 13 : 14, 256);
      batch(aW[0], 0);
      NEWZ(5);
      if (WG == 1) {
        named_bar(14, 256);
        if (last_warp && s + 2 < NSEG) {
          expect_elect(sb + BAR_TOK + 8 * (xph ^ 1), 8192); expect_elect(sb + BAR_X, 32768); expect_elect(sb + BAR_X + 8, 32768);
          if (J == 0) expect_elect(sb + BAR_EX, 2048);
          if (s == NSEG - 3) asm volatile("griddepcontrol.launch_dependents;");
        }
      }
      const uint32_t tb = lds32(sb + CT_TT) + xph * 8192 + WG * 4096 + ((tv + l16) >> 1);
      float4 oth[4];
#pragma unroll
      for (int i = 0; i < 4; i++) oth[i] = lds128f(sb + OFF_FP + (WG ^ 1) * 8192 + t16 + i * 512);
      if (WG == 1 && __builtin_expect(s >= 0, 1)) {
        const uint32_t edst = sb + OFF_MEM + tv + t16 - l16;
        WAIT_UNTIL(tref, aW[0][0], 0, J ? 7 : 0);
        gather_issue<2, 2048>(edst, gptr(xhi, esrc) - 2048);
      }
      wg_wait<0>();
      acc_fence(acc);
      uint32_t lt[4], ht[4];
#pragma unroll
      for (int i = 0; i < 4; i++) {
        const float4 o = oth[i];
        lt[i] = pack_bf16(acc[4 * i] + o.x, acc[4 * i + 1] + o.y); ht[i] = pack_bf16(acc[4 * i + 2] + o.z, acc[4 * i + 3] + o.w);
      }
      stsm_x4_t(tb, lt[0], ht[0], lt[1], ht[1]); stsm_x4_t(tb + 512, lt[2], ht[2], lt[3], ht[3]);
      NEWZ(6);
      if (WG == 0 && last_warp) {
        load_ws();
        named_bar(11, 256);
        fence_async_smem();
        const uint32_t tt = (J ? OFF_KT : OFF_QT) + xph * 8192;
        asm volatile("{.reg .pred p; elect.sync _|p, 0xffffffff;\n"
                     "@p cp.async.bulk.shared::cluster.shared::cta.mbarrier::complete_tx::bytes [%0], [%1], 8192, [%2];}"
                     ::"r"(rsb + tt), "r"(sb + tt), "r"(rsb + BAR_TOK + 8 * xph) : "memory");
      } else {
        named_bar_arrive(11, 256);
        load_ws();
      }
    }
    if (!more) break;
    if (__builtin_expect(s < 0, 0)) {
      tref = gtime() / T_SLIP * T_SLIP - T_SLIP;
    }
  }
  cp_async_wait_group<0>();
  if (J == 0) mbar_wait(sb + BAR_TOK + 8, 1);
}

template <int WG>
__device__ __forceinline__ void role_v(const ChainMaps& maps, const bf16* __restrict__ mem0, const uint32_t sb, const uint32_t xbase_hi) {
  using namespace chain;
  const int h = blockIdx.x >> 2;
  const uint32_t u16 = (threadIdx.x & 96) * 64 + (threadIdx.x & 31) * 16;
  const uint32_t t16 = keep(u16), l16 = keep((threadIdx.x & 31) * 16);
  const uint32_t xhi = keep(xbase_hi + (t16 >> 16));
#define j (sb >> 24)
  auto wv_addr = [&](uint32_t t) { return WG * 32768 + ((t & 256) << 2) + ((t & 112) << 3) + ((((t >> 6) & 96) + ((t >> 3) & 16)) ^ (t & 112)); };
  auto wo_addr = [&](uint32_t t) { return OFF_WOR + WG * 32768 + ((t & 6144) << 2) + ((t & 256) << 1) + ((t & 112) << 2) + ((((j ^ 1) << 5) + ((t >> 3) & 16)) ^ ((t >> 1) & 48)); };
#define ovt (((tv + l16) >> 1) + (xo::VT + WG * 512 + j * 4096))
#define ovm (((tv & 4096) >> 1) + ((tv & 2048) >> 3) + (lv >> 1) + (xo::VM + j * 4096))
#define xvt (lds32(sb + CT_HEAD) + ovt)
#define xvm (lds32(sb + CT_HEAD) + ovm)
#define xom (lds32(sb + CT_OM) + t16 + WG * 8192)
#define warp_is(q) __any_sync(0xffffffffu, (tv >> 11) == (q))
#define upper_warps (WG == 1 || __any_sync(0xffffffffu, tv >= 4096))

  uint32_t aV[16][4];
  uint32_t aO[16][4];
  uint32_t bO[16][4];
  uint32_t rot[16][4];
  if (WG == 1 && __any_sync(0xffffffffu, t16 >= 6144)) {
    expect_elect(sb + BAR_X, 32768); expect_elect(sb + BAR_X + 8, 32768);
    issue_x(sb, &maps.x, 0, 0); issue_x(sb, &maps.x, 0, 1);
    prefetch_l2(maps.xp + 65536 + (h * 2 + j) * 3072, 3072);
  }
  cluster_arrive();
  { uint2 m0[8]; load_mem0(m0, mem0); store_mem0(sb, m0); }
  mbar_wait(sb + BAR_P, 0);
#pragma unroll
  for (int ks = 0; ks < 16; ks++) ldsm_x4_t(aV[ks], sb + wv_addr(t16) + OFF_WOR + ks * 2048);
  auto load_v = [&](uint32_t t) {
#pragma unroll
    for (int ks = 0; ks < 16; ks++) ldsm_x4_t(rot[ks], sb + wv_addr(t) + OFF_WVR + ks * 2048);
  };
  load_v(t16);
  named_bar(0, 256);
  if (threadIdx.x == 0) {
    fence_async_smem();
    mbar_expect_tx(sb + BAR_P + 8, 4 * 16384);
    for (int q = 0; q < 4; q++) tma_load_2d(sb + OFF_WOR + q * 16384, &maps.wo, h * 32, j * 2048 + q * 256, sb + BAR_P + 8);
    for (int q = 0; q < 4; q++) tma_prefetch_2d(&maps.wo, h * 32, j * 2048 + 1024 + q * 256);
  }
  __syncwarp();
  cluster_wait();
  const uint32_t rsb = sb ^ RANK_BIT;

  uint32_t tref = 0;
#pragma unroll 1
  for (int n = 0; n <= NSEG; n++) {
    const bool more = __builtin_expect(s + 1 < NSEG, 1);
    uint32_t zr = loop_zero<0>(n);
    bool xok = false;
    if (__builtin_expect(s >= 0, 1)) {
      if (__builtin_expect(s > 0, 1)) {
        const uint32_t dst = sb + OFF_MEM + WG * 8192 + t16 + ((lv >> 5) & 12);
        uint32_t tries = zr;
#pragma unroll 1
        do {
          if (tries) { const char* src = gptr(xhi, xm + WG * 8192 + slot_off(sv)); tref += T_SLIP; WAIT_UNTIL(tref, aV[0], 1, -1); gather_issue(sb + OFF_MEM + WG * 8192 + tv, src); }
          KEEPALIVE(aV[0], zr);
          cp_async_wait_group<0>();
        } while (gather_incomplete<1, 0>(dst) && ++tries < POLL_LIMIT);
        named_bar(1 + WG, 128);
      }
      const uint32_t a_mem = sb + OFF_MEM + WG * 8192 + l16;
      float c[2][4];
      c[0][0] = c[0][1] = c[0][2] = c[0][3] = c[1][0] = c[1][1] = c[1][2] = c[1][3] = 0.f;
      constexpr int NBUF = (48 - 8 - 4 * O_FIX) / 4;
      uint32_t b[NBUF][4];
#pragma unroll
      for (int p = 0; p < NBUF - 1; p++) ldsm_x4_t(b[p], a_mem + p * 512);
#pragma unroll
      for (int p = 0; p < 16; p++) {
        if (p + NBUF - 1 < 16) ldsm_x4_t(b[(p + NBUF - 1) % NBUF], a_mem + (p + NBUF - 1) * 512);
        if (p < 8) { mma16816(c[0], aV[2 * p], b[p % NBUF][0], b[p % NBUF][1]); mma16816(c[1], aV[2 * p + 1], b[p % NBUF][2], b[p % NBUF][3]); }
        else { mma16816(c[0], rot[2 * p - 16], b[p % NBUF][0], b[p % NBUF][1]); mma16816(c[1], rot[2 * p - 15], b[p % NBUF][2], b[p % NBUF][3]); }
      }
      xok = mbar_test(sb + BAR_X + 8 * WG, n & 1);
      SFENCE(15);
      const float4 own = make_float4(c[0][0] + c[1][0], c[0][1] + c[1][1], c[0][2] + c[1][2], c[0][3] + c[1][3]);
      NEWZ(1);
      const uint32_t pvm = WG == 0 ? xvm + slot_off(sv) : 0;
      if (WG == 1) sts128f(sb + OFF_VPX + wq * 512 + l16, own);
      named_bar(3, 256);
      if (WG == 0) {
        const float4 o = lds128f(sb + OFF_VPX + wq * 512 + l16);
        st_relaxed2(gptr(xhi, pvm), pack_bf16(own.x + o.x, own.y + o.y), pack_bf16(own.z + o.z, own.w + o.w));
      }
    }
    auto token_pv = [&](int seg, bool staged) {
      constexpr int NU = 2 - WG;
      uint4 pt0, pt1, v0[NU], v1[NU]; uint32_t pm0, pm1; uint2 vm[NU];
      const uint32_t ap = l16 + WG * 4096 + xo::PT, am = (lv >> 2) + WG * 4096 + xo::PM;
      const uint32_t at = ovt - WG * 512;
      if (staged) {
        const uint32_t b = sb + OFF_MEM;
        pt0 = lds128(b + ap); pt1 = lds128(b + ap + 2048); pm0 = lds32(b + am); pm1 = lds32(b + am + 2048);
#pragma unroll
        for (int u = 0; u < NU; u++) { v0[u] = lds128(b + at - u * 2048); v1[u] = lds128(b + at + 512 - u * 2048); vm[u] = lds64(b + ovm - u * 2048); }
      } else {
        const uint32_t b = lds32(sb + CT_HEAD) + slot_off(seg);
        pt0.x = EMPTY;
#pragma unroll
        for (int u = 0; u < NU; u++) {
          v0[u] = ld_relaxed4(gptr(xhi, b + at) - u * 2048); v1[u] = ld_relaxed4(gptr(xhi, b + at) + 512 - u * 2048);
          vm[u] = ld_relaxed2(gptr(xhi, b + ovm) - u * 2048);
        }
      }
      const bool odd = lv & 16;
      char* op = gptr(xhi, lds32(sb + CT_O) + (seg * SEG + WG * 16 + (lv >> 6)) * (HD * 2) + wq * 32 + (lv & 16) + ((lv >> 2) & 8));
      if (!staged || __builtin_expect(warp_incomplete(umax4(pt0.x, pt1.x, pm0, pm1)), 0)) {
        const uint32_t b = lds32(sb + CT_HEAD) + slot_off(seg);
        uint32_t tries = zr;
#pragma unroll 1
        do {
          pt0 = ld_relaxed4(gptr(xhi, b + ap)); pt1 = ld_relaxed4(gptr(xhi, b + ap) + 2048);
          pm0 = ld_relaxed1(gptr(xhi, b + am)); pm1 = ld_relaxed1(gptr(xhi, b + am) + 2048);
        } while (warp_incomplete(umax4(pt0.x, pt1.x, pm0, pm1)) && ++tries < POLL_LIMIT);
      }
      const uint32_t pa[4] = {pt0.x, pt1.x, pt0.y, pt1.y}, pb[4] = {pt0.z, pt1.z, pt0.w, pt1.w};
#pragma unroll
      for (int u = 0; u < NU; u++) {
        float o0[4] = {0.f, 0.f, 0.f, 0.f}, o1[4] = {0.f, 0.f, 0.f, 0.f};
        mma1688(o0, pm0, pm1, vm[u].x); mma1688(o1, pm0, pm1, vm[u].y);
        mma16816(o0, pa, v0[u].x, v0[u].y); mma16816(o1, pa, v1[u].x, v1[u].y);
        if (WG) { mma16816(o0, pb, v0[u].z, v0[u].w); mma16816(o1, pb, v1[u].z, v1[u].w); }
#pragma unroll
        for (int r = 0; r < 2; r++) {
          const uint32_t w0 = pack_bf16(o0[2 * r], o0[2 * r + 1]), w1 = pack_bf16(o1[2 * r], o1[2 * r + 1]);
          const uint32_t rv = __shfl_xor_sync(~0u, odd ? w0 : w1, 1);
          asm volatile("st.global.v2.u32 [%0], {%1, %2};" ::"l"(op + r * 8 * HD * 2 - u * 64), "r"(odd ? rv : w0), "r"(odd ? w1 : rv) : "memory");
        }
      }
    };
    if (!more) {
      named_bar(3, 256);
      if (upper_warps) {
#pragma unroll 1
        for (int seg = NSEG - 2; seg < NSEG; seg++) token_pv(seg, false);
      }
      break;
    }
    {
      if (__builtin_expect(s > 0, 1)) {
        const uint32_t o = WG ? ovt - 512 : tv + 512;
        const char* src = gptr(xhi, lds32(sb + CT_HEAD) + slot_off(sv - 1) + o);
#pragma unroll
        for (int i = 0; i < 3 - WG; i++) cp_async16(sb + OFF_MEM + o + i * 512, src + i * 512);
        cp_async_commit();
      }
      bool xw;
      {
        float acc[16];
        if (__builtin_expect(!xok, 0)) mbar_wait<0>(sb + BAR_X + 8 * WG, (s + 1) & 1);
        wg_fence();
#pragma unroll
        for (int ks = 0; ks < 16; ks++) wgmma_m64n32_rs(acc, rot[ks], xdesc<WG>(16 + ks), ks != 0);
        wg_commit();
#pragma unroll
        for (int ks = 0; ks < 16; ks++) wgmma_m64n32_rs(acc, aV[ks], xdesc<WG>(ks), 1);
        wg_commit();
        SFENCE(50);
        NEWZ(2);
        xw = warp_is(3) && s + 2 < NSEG;
        tref += lds32(sb + CT_T + 4) + WG * T_LAG - T_SLIP;
        const uint32_t pvt = xvt + slot_off(sv + 1), awo = sb + wo_addr(tv);
        if (WG == 0 && warp_is(1) && s >= 0) expect_elect(sb + BAR_EX, 4096);
        if (xw) {
          expect_elect(sb + BAR_X + 8 * WG, 32768);
          if (WG == 1 && s == NSEG - 3) asm volatile("griddepcontrol.launch_dependents;");
          if (WG == 1 && s + 5 < NSEG) prefetch_l2(maps.xp + (s + 5) * 65536 + lds32(sb + CT_PF), 1024);
        }
        wg_wait<1>();
        if (xw) issue_x(sb, &maps.xq, s + 2, WG, 1);
        if (__builtin_expect(s == 0, 0)) {
          mbar_wait(sb + BAR_P + 16, 0);
#pragma unroll
          for (int ks = 16 - O_FIX; ks < 16; ks++) ldsm_x4_t(bO[ks], (awo ^ 32) + (ks & 7) * 1024);
        }
#pragma unroll
        for (int ks = 0; ks < 16 - O_FIX; ks++) ldsm_x4_t(bO[ks], (ks < 8 ? awo : awo ^ 32) + (ks & 7) * 1024);
        wg_wait<0>();
        acc_fence(acc);
        constexpr int K = WG * 2, G = 2 - K;
        sts128f(sb + OFF_RED + WG * 1024 + t16, make_float4(acc[G], acc[G + 1], acc[4 + G], acc[5 + G]));
        sts128f(sb + OFF_RED + WG * 1024 + 512 + t16, make_float4(acc[8 + G], acc[9 + G], acc[12 + G], acc[13 + G]));
        cp_async_wait_group<0>();
        named_bar(3, 256);
        const float4 o0 = lds128f(sb + OFF_RED + (WG ^ 1) * 1024 + t16), o1 = lds128f(sb + OFF_RED + (WG ^ 1) * 1024 + 512 + t16);
        st_relaxed4(gptr(xhi, pvt),
                    pack_bf16(acc[K] + o0.x, acc[K + 1] + o0.y), pack_bf16(acc[4 + K] + o0.z, acc[5 + K] + o0.w),
                    pack_bf16(acc[8 + K] + o1.x, acc[9 + K] + o1.y), pack_bf16(acc[12 + K] + o1.z, acc[13 + K] + o1.w));
      }
      if (__builtin_expect(s >= 0, 1)) {
        uint32_t tries = 0;
#pragma unroll
        for (int ks = 0; ks < 16 - O_FIX; ks++) tries |= bO[ks][0];
        const char* po = gptr(xhi, xom + slot_off(sv) + (tries & zr));
        tries = zr;
        float d[2][2][4];
        uint32_t mx;
#pragma unroll 1
        do {
          tref += T_SLIP;
          WAIT_UNTIL(tref, aV[0], 1, 1);
          uint4 o[8];
#pragma unroll
          for (int i = 0; i < 4; i++) o[i] = ld_relaxed4(po + i * 512);
#pragma unroll
          for (int i = 0; i < 4; i++) o[4 + i] = ld_relaxed4(po + 16384 + i * 512);
          __syncwarp();
#pragma unroll
          for (int i = 0; i < 2; i++)
#pragma unroll
            for (int q = 0; q < 2; q++) { d[i][q][0] = d[i][q][1] = d[i][q][2] = d[i][q][3] = 0.f; }
#pragma unroll
          for (int i = 0; i < 4; i++) {
            mma16816(d[0][0], aO[2 * i], o[i].x, o[i].y); mma16816(d[1][0], aO[8 + 2 * i], o[i].x, o[i].y);
            mma16816(d[0][1], aO[2 * i + 1], o[i].z, o[i].w); mma16816(d[1][1], aO[9 + 2 * i], o[i].z, o[i].w);
          }
          mx = umax4(o[0].w, o[1].w, o[2].w, o[3].w);
          SFENCE(33 + tries);
#pragma unroll
          for (int i = 0; i < 4; i++) {
            mma16816(d[0][0], bO[2 * i], o[4 + i].x, o[4 + i].y); mma16816(d[1][0], bO[8 + 2 * i], o[4 + i].x, o[4 + i].y);
            mma16816(d[0][1], bO[2 * i + 1], o[4 + i].z, o[4 + i].w); mma16816(d[1][1], bO[9 + 2 * i], o[4 + i].z, o[4 + i].w);
          }
          mx = max(mx, umax4(o[4].w, o[5].w, o[6].w, o[7].w));
        } while (warp_incomplete(mx) && ++tries < POLL_LIMIT);
        NEWZ(3);
        {
          const uint32_t rr = rsb + (WG ? OFF_RX1 : OFF_RX) + wq * 512 + (lv >> 1);
          st_async2(rr, __float_as_uint(d[0][0][0] + d[0][1][0]), __float_as_uint(d[0][0][1] + d[0][1][1]), rsb + BAR_EX);
          st_async2(rr + 256, __float_as_uint(d[0][0][2] + d[0][1][2]), __float_as_uint(d[0][0][3] + d[0][1][3]), rsb + BAR_EX);
          const uint32_t rd = sb + OFF_RED + (WG ^ 1) * 1024 + t16 - (lv >> 1);
          sts64(rd, __float_as_uint(d[1][0][0] + d[1][1][0]), __float_as_uint(d[1][0][1] + d[1][1][1]));
          sts64(rd + 256, __float_as_uint(d[1][0][2] + d[1][1][2]), __float_as_uint(d[1][0][3] + d[1][1][3]));
        }
        if (upper_warps) {
          named_bar_arrive(7, 256);
          if (xw) issue_x(sb, &maps.xq, s + 2, WG, 0);
          if (__builtin_expect(s > 0, 1)) token_pv(sv - 1, true);
        } else {
          const uint32_t mp = lds32(sb + CT_MP) + (lv >> 2) + wq * 128, ra = sb + wq * 256 + (lv >> 1);
          char* pp = gptr(xhi, mp + slot_off(sv + 1));
          named_bar(7, 256);
          uint2 p[8];
#pragma unroll
          for (int i = 0; i < 8; i++) p[i] = lds64(ra + OFF_RED + i * 1024);
#define SUM8(c) (((__uint_as_float(p[0].c) + __uint_as_float(p[1].c)) + (__uint_as_float(p[2].c) + __uint_as_float(p[3].c))) + \
                 ((__uint_as_float(p[4].c) + __uint_as_float(p[5].c)) + (__uint_as_float(p[6].c) + __uint_as_float(p[7].c))))
          const float r0 = SUM8(x), r1 = SUM8(y);
          mbar_wait(sb + BAR_EX, s & 1);
#pragma unroll
          for (int i = 0; i < 8; i++) p[i] = lds64(ra + (i < 4 ? OFF_RX : OFF_RX1) + (i & 3) * 512);
          st_relaxed1(pp, pack_bf16(r0 + SUM8(x), r1 + SUM8(y)));
          st_relaxed1(gptr(xhi, mp + slot_off(sv + 3)), EMPTY);
        }
        NEWZ(4);
        const char* src = gptr(xhi, xm + WG * 8192 + slot_off(sv + 1));
        const uint32_t awv = sb + wv_addr(tv) + OFF_WVR;
        tref += lds32(sb + CT_T + 8) - WG * T_LAG;
        named_bar(8, 256);
#pragma unroll
        for (int ks = 0; ks < V_PRE; ks++) ldsm_x4_t(rot[ks], awv + ks * 2048);
        WAIT_UNTIL(tref, aV[0], 1, 2);
        gather_issue(sb + OFF_MEM + WG * 8192 + tv, src);
#pragma unroll
        for (int ks = V_PRE; ks < 16; ks++) ldsm_x4_t(rot[ks], awv + ks * 2048);
        NEWZ(6);
        st_relaxed4(gptr(xhi, xvt + slot_off(sv + 2)), EMPTY, EMPTY, EMPTY, EMPTY);
        if (WG == 0) st_relaxed2(gptr(xhi, xvm + slot_off(sv + 2)), EMPTY, EMPTY);
      } else {
        load_v(tv);
        if (xw) issue_x(sb, &maps.xq, s + 2, WG, 0);
        mbar_wait(sb + BAR_P + 8, 0);
#pragma unroll
        for (int ks = 0; ks < 8; ks++) { ldsm_x4_t(aO[ks], sb + wo_addr(tv) + ks * 1024); ldsm_x4_t(aO[8 + ks], sb + (wo_addr(tv) ^ 32) + ks * 1024); }
        named_bar(0, 256);
        if (threadIdx.x == 0) {
          fence_async_smem();
          mbar_expect_tx(sb + BAR_P + 16, 4 * 16384);
          for (int q = 0; q < 4; q++) tma_load_2d(sb + OFF_WOR + q * 16384, &maps.wo, h * 32, j * 2048 + 1024 + q * 256, sb + BAR_P + 16);
        }
        __syncwarp();
        tref = gtime() / T_SLIP * T_SLIP - T_SLIP;
      }
    }
  }
}

#undef j
#undef s
#undef sv
#undef xm
#undef wq

__global__ void __launch_bounds__(256, 1) __cluster_dims__(2, 1, 1)
chain_kernel(const __grid_constant__ ChainMaps maps, const bf16* __restrict__ mem0, const uint64_t xbase) {
  using namespace chain;
  extern __shared__ uint8_t smem_raw[];
  uint32_t sb = smem_u32(smem_raw);
  PIN(sb);
  if (sb != SB_LO + (blockIdx.x & 1) * RANK_BIT || mapa(sb, (blockIdx.x & 1) ^ 1) != (sb ^ RANK_BIT)) __trap();
  const int tid = threadIdx.x;
  const int h = blockIdx.x >> 2, role = (blockIdx.x >> 1) & 1, j = blockIdx.x & 1;
  if (tid == 0) {
    for (int i = 0; i < 9; i++) mbar_init(sb + OFF_BAR + 8 * i, 1);
    asm volatile("fence.mbarrier_init.release.cluster;" ::: "memory");
    const uint32_t xl = (uint32_t)xbase;
    sts32(sb + CT_BASE, xl); sts32(sb + CT_HEAD, xl + h * xo::HEAD); sts32(sb + CT_OM, xl + xo::OM + (role ? j * 32768 : h * 2048));
    sts32(sb + CT_MP, xl + xo::MEM + (h * 2 + j) * 256); sts32(sb + CT_O, xl + xo::O + (h * 2 + j) * 128); sts32(sb + CT_PF, (h * 2 + j) * 1024);
    sts32(sb + CT_TT, sb + (j ? OFF_KT : OFF_QT));
    if (role == 0) {
      const CUtensorMap* wm = j ? &maps.wk : &maps.wq;
      mbar_expect_tx(sb + BAR_P, 6 * 16384);
      for (int c = 0; c < 3; c++)
        for (int q = 0; q < 2; q++) tma_load_2d(sb + OFF_X + (q * 3 + c) * 16384, wm, h * DH + q * 64, q * 512 + c * 128, sb + BAR_P);
      mbar_expect_tx(sb + BAR_P + 8, 4 * 16384);
      for (int c = 0; c < 2; c++)
        for (int q = 0; q < 2; q++) tma_load_2d(sb + OFF_X + (6 + q * 2 + c) * 16384, wm, h * DH + (q ^ 1) * 64, q * 512 + c * 128, sb + BAR_P + 8);
      mbar_expect_tx(sb + BAR_P + 24, 4 * 16384);
      for (int q = 0; q < 2; q++)
        for (int o = 0; o < 2; o++) tma_load_2d(sb + OFF_WS + (q * 2 + o) * 16384, wm, h * DH + (q ^ o) * 64, q * 512 + 384, sb + BAR_P + 24);
      for (int q = 0; q < 2; q++) tma_prefetch_2d(wm, h * DH + (q ^ 1) * 64, q * 512 + 256);
    } else {
      mbar_expect_tx(sb + BAR_P, 8 * 16384);
      for (int q = 0; q < 4; q++) tma_load_2d(sb + OFF_WOR + q * 16384, &maps.wv, h * DH + j * 64, (q >> 1) * 512 + (q & 1) * 128, sb + BAR_P);
      for (int q = 0; q < 4; q++) tma_load_2d(sb + OFF_WVR + q * 16384, &maps.wv, h * DH + j * 64, (q >> 1) * 512 + 256 + (q & 1) * 128, sb + BAR_P);
    }
  }
  for (int r = 0; r < RING; r++) {
    char* p = (char*)xbase + r * xo::SLOT;
    const int wq = (tid >> 5) & 3;
    if (role == 1) st_relaxed4(p + h * xo::HEAD + xo::VT + (8 * j + 2 * wq + (tid >> 7)) * 512 + (tid & 31) * 16, EMPTY, EMPTY, EMPTY, EMPTY);
    else if (j == 0) st_relaxed4(p + (tid < 128 ? xo::OM + h * 2048 + tid * 16 : h * xo::HEAD + wq * 2048 + xo::VM + (tid & 31) * 16), EMPTY, EMPTY, EMPTY, EMPTY);
    else {
      st_relaxed4(p + h * xo::HEAD + (tid >> 6) * 2048 + 1024 + (tid & 63) * 16, EMPTY, EMPTY, EMPTY, EMPTY);
      if (tid < 32) st_relaxed4(p + xo::MEM + h * 512 + tid * 16, EMPTY, EMPTY, EMPTY, EMPTY);
    }
  }
  __syncthreads();
  if (__shfl_sync(0xffffffffu, tid >> 5, 0) == 0) {
    uint32_t t[2], c[2], ka[4] = {0, 0, 0, 0};
    const uint32_t z = maps.t_step >> 24;
#pragma unroll
    for (int i = 0; i < 2; i++) {
      const uint32_t end = (gtime() & ~31u) + (i ? 2048 : 1024);
      for (int g = z; g < 256 && (int)(gtime() - (end - 96)) < 0; g++) KEEPALIVE(ka, z);
      for (int g = z; g < 256 && (int)((t[i] = gtime()) - end) < 0; g++) {}
      c[i] = (uint32_t)clock64();
    }
    uint32_t v = 0, target = 0;
    if (tid == 0) {
      st_relaxed1(&g_rate[blockIdx.x], (t[1] - t[0]) * 4096u / (c[1] - c[0]));
      __threadfence();
      target = (atomicAdd(&g_epoch, 1u) & ~127u) + 128u;
    }
    target = __shfl_sync(0xffffffffu, target, 0);
    int guard = 0;
    do { asm volatile("ld.acquire.gpu.global.u32 %0, [%1];" : "=r"(v) : "l"(&g_epoch) : "memory"); }
    while (__any_sync(0xffffffffu, (int)(v - target) < 0) && ++guard < (1 << 20));
    const uint4 r4 = ld_relaxed4(&g_rate[tid * 4]);
    uint32_t r = min(__reduce_max_sync(0xffffffffu, umax4(r4.x, r4.y, r4.z, r4.w)), 4 * RATE0);
    if (r < RATE0 + 28) r = RATE0;
    const uint32_t a = (maps.t_step * r / RATE0 + 31) & ~31u, b = (maps.t_phase * r / RATE0 + 31) & ~31u;
    sts128(sb + CT_T, make_uint4(a, b, a - b, r));
  }
  const uint32_t xhi = (uint32_t)(xbase >> 32);
  const int wg = __shfl_sync(0xffffffffu, tid >> 7, 0);
  if (role == 0) {
    if (wg == 0) role_a<0>(maps, mem0, sb, xhi); else role_a<1>(maps, mem0, sb, xhi);
  } else {
    if (wg == 0) role_v<0>(maps, mem0, sb, xhi); else role_v<1>(maps, mem0, sb, xhi);
  }
  __syncwarp();
  cluster_arrive();
  cluster_wait();
}

struct BMaps {
  CUtensorMap q, k, v, out, k8;
  const bf16 *shift_k, *ssm_k, *ssm_D;
};

#define B_SLEEP 200
namespace bp {
constexpr int U_PITCH = (2048 + 128) * 2 + 16;
constexpr int KR_WORDS = 1048;
constexpr int KR_PITCH = 8704;
constexpr int OFF_U = 0;
constexpr int OFF_KR = (8 * U_PITCH + 127) / 128 * 128;
constexpr int Q_OFF = 4352;
constexpr int OFF_BAR = OFF_KR + 8 * KR_PITCH;
constexpr int GROUP_BYTES = OFF_BAR + 128;
constexpr int SMEM = 2 * GROUP_BYTES + 128;
constexpr int NTASK = DM / 8;
static_assert(Q_OFF >= 4224 && Q_OFF + 4096 <= KR_PITCH, "staging does not fit");
}

__device__ __forceinline__ uint32_t bmul2(uint32_t a, uint32_t b) { uint32_t r; asm("mul.rn.bf16x2 %0, %1, %2;" : "=r"(r) : "r"(a), "r"(b)); return r; }
__device__ __forceinline__ uint32_t badd2(uint32_t a, uint32_t b) { uint32_t r; asm("add.rn.bf16x2 %0, %1, %2;" : "=r"(r) : "r"(a), "r"(b)); return r; }

__device__ __forceinline__ void mbar_wait_sleep(uint32_t bar, uint32_t parity) {
  int guard = 0;
  while (!mbar_try(bar, parity)) { __nanosleep(B_SLEEP); if (++guard > (1 << 22)) __trap(); }
}

__device__ __forceinline__ void bpart_body(const BMaps& maps, int first, int stride, int end) {
  using namespace bp;
  extern __shared__ uint8_t smem_all[];
  const int grp = __shfl_sync(0xffffffffu, threadIdx.x >> 8, 0);
  const int lane = keep(threadIdx.x & 31), g = lane >> 2, t = lane & 3;
  const int w = __shfl_sync(0xffffffffu, (threadIdx.x >> 5) & 7, 0);
  const uint32_t sb = ((smem_u32(smem_all) + 127) & ~127u) + grp * GROUP_BYTES;
  const uint32_t kr = sb + OFF_KR + w * KR_PITCH, bar_k = sb + OFF_BAR + 8 * w, bar_q = bar_k + 64;
  if (lane == 0) { mbar_init(bar_k, 1); mbar_init(bar_q, 1); asm volatile("fence.mbarrier_init.release.cluster;" ::: "memory"); }
  if (lane < 16) sts128(sb + OFF_U + w * U_PITCH + lane * 16, make_uint4(0, 0, 0, 0));
  __syncwarp();
  if (grp == 1) { named_bar_arrive(3, 512); named_bar(5, 512); }
  const int lm = lane >> 3, lr = lane & 7;
  uint32_t ph = 0;
  for (int task = first + grp; task < end; task += stride, ph ^= 1) {
    const int d0 = task * 8;
    uint4 x[8];
    {
      const uint4* kf = (const uint4*)(maps.ssm_k + (size_t)(d0 + w) * S_LEN);
#pragma unroll
      for (int it = 0; it < 8; it++) x[it] = __ldg(kf + it * 32 + lane);
    }
    const uint4 ska = __ldg((const uint4*)(maps.shift_k + (d0 + 2 * t) * 4));
    __syncwarp();
    if (lane == 0) {
      mbar_expect_tx(bar_k, 2 * 4096 + 128);
      tma_load_2d(kr + 4096, &maps.k8, d0, w * 256 + 248, bar_k);
      tma_load_2d(kr, &maps.k, d0, w * 256 - 8, bar_k);
      bulk_wait_read<0>();
      tma_load_2d(kr + Q_OFF, &maps.v, d0, w * 256, bar_k);
    }
    __syncwarp();
    if (task == first) named_bar_arrive(5, 512);
    const uint32_t sk[4] = {__byte_perm(ska.x, ska.z, 0x5410), __byte_perm(ska.x, ska.z, 0x7632), __byte_perm(ska.y, ska.w, 0x5410), __byte_perm(ska.y, ska.w, 0x7632)};
    mbar_wait_sleep(bar_k, ph);
    {
      const uint32_t ka = kr + (lane + 8) * 16;
#pragma unroll
      for (int i = 0; i < 8; i++) {
        uint32_t k0[4], k1[4], k2[4], k3[4], v[4], r[4];
        ldsm_x4(k3, ka + i * 512 - 48); ldsm_x4(k2, ka + i * 512 - 32); ldsm_x4(k1, ka + i * 512 - 16); ldsm_x4(k0, ka + i * 512);
        ldsm_x4(v, ka + (Q_OFF - 128) + i * 512);
#pragma unroll
        for (int b = 0; b < 4; b++) {
          uint32_t acc = bmul2(k3[b], sk[3]);
          acc = badd2(acc, bmul2(k2[b], sk[2]));
          acc = badd2(acc, bmul2(k1[b], sk[1]));
          acc = badd2(acc, bmul2(k0[b], sk[0]));
          r[b] = bmul2(acc, v[b]);
        }
        const int ch = 16 + w * 32 + i * 4 + lm;
        stsm_x4_t(sb + OFF_U + lr * U_PITCH + ((ch ^ ((ch >> 3) & 1)) << 4), r[0], r[1], r[2], r[3]);
      }
    }
    __syncwarp();
    {
      const uint32_t c0 = kr, c1 = c0 + (KR_WORDS + 16) * 4;
      uint32_t carry = 0;
#pragma unroll
      for (int it = 0; it < 8; it++) {
        const int blk = it * 32 + lane;
        uint32_t prev = __shfl_up_sync(0xffffffffu, x[it].w, 1);
        if (lane == 0) prev = carry;
        carry = __shfl_sync(0xffffffffu, x[it].w, 31);
        sts128(c0 + (1028 - 4 * blk) * 4, make_uint4(__byte_perm(x[it].w, 0, 0x1032), __byte_perm(x[it].z, 0, 0x1032),
                                                     __byte_perm(x[it].y, 0, 0x1032), __byte_perm(x[it].x, 0, 0x1032)));
        sts128(c1 + (1028 - 4 * blk) * 4, make_uint4(__byte_perm(x[it].w, x[it].z, 0x7610), __byte_perm(x[it].z, x[it].y, 0x7610),
                                                     __byte_perm(x[it].y, x[it].x, 0x7610), __byte_perm(x[it].x, prev, 0x7610)));
      }
      if (lane < 4) { sts128(c0 + (1032 + 4 * lane) * 4, make_uint4(0, 0, 0, 0)); sts128(c1 + (1032 + 4 * lane) * 4, make_uint4(0, 0, 0, 0)); }
      __syncwarp();
    }
    named_bar(3 + grp, 512);
    float acc[16][4];
#pragma unroll
    for (int jn = 0; jn < 16; jn++) { acc[jn][0] = acc[jn][1] = acc[jn][2] = acc[jn][3] = 0.f; }
    {
      const uint32_t ub = sb + OFF_U + w * U_PITCH;
      uint32_t kd = kr + (((g & 1) ? 0 : KR_WORDS + 16) + ((((g & 1) ? 2063 : 2062) - (g - 2 * t)) >> 1)) * 4;
      uint32_t uc = 2 * (8 + lr + (lm >> 1) * 8) + (lm & 1);
#pragma unroll 1
      for (int d0s = 0; d0s < 8; d0s++, kd -= 32, uc -= 2) {
        const uint32_t uf = ub + ((uc ^ ((uc >> 3) & 1)) << 4);
        uint32_t A[3][4];
        A[0][0] = lds32v(kd); A[0][1] = lds32v(kd - 16); A[0][2] = lds32v(kd + 16); A[0][3] = lds32v(kd);
        uint32_t F[8][4];
#pragma unroll
        for (int m = 7; m >= 0; m--) ldsm_x4(F[m], uf + m * 512);
#pragma unroll
        for (int i = 0; i < 16; i++) {
          if (i + 1 < 16) {
            A[(i + 1) % 3][0] = lds32v(kd - 256 * (i + 1)); A[(i + 1) % 3][1] = lds32v(kd - 256 * (i + 1) - 16);
            A[(i + 1) % 3][2] = lds32v(kd - 256 * (i + 1) + 16); A[(i + 1) % 3][3] = lds32v(kd - 256 * (i + 1));
          }
#pragma unroll
          for (int jn = 15; jn >= i; jn--) mma16816(acc[jn], A[i % 3], F[(jn - i) >> 1][((jn - i) & 1) * 2], F[(jn - i) >> 1][((jn - i) & 1) * 2 + 1]);
        }
      }
    }
    named_bar_arrive(3 + (grp ^ 1), 512);
    __syncwarp();
    fence_async_smem();
    __syncwarp();
    if (lane == 0) { mbar_expect_tx(bar_q, 4096); tma_load_2d(kr + Q_OFF, &maps.q, d0, w * 256, bar_q); }
    const uint32_t dpair = __ldg((const uint32_t*)(maps.ssm_D + d0) + t);
    {
      const uint32_t ya = kr + w * 16 + (((lm >> 1) * 8 + lr) * 32) + (lm & 1) * 16;
#pragma unroll
      for (int jn = 0; jn < 16; jn += 2)
        stsm_x4_t(ya + jn * 256, pack_bf16(acc[jn][0], acc[jn][1]), pack_bf16(acc[jn][2], acc[jn][3]),
                  pack_bf16(acc[jn + 1][0], acc[jn + 1][1]), pack_bf16(acc[jn + 1][2], acc[jn + 1][3]));
    }
    named_bar(1 + grp, 256);
    mbar_wait_sleep(bar_q, ph);
    {
      const uint32_t ya = sb + OFF_KR + lr * (KR_PITCH + 16) + (w * 256 + lm * 8) * 2;
#pragma unroll
      for (int i = 0; i < 8; i++) {
        uint32_t y[4], u[4], q[4], r[4];
        ldsm_x4(q, kr + Q_OFF + lane * 16 + i * 512);
        ldsm_x4_t(y, ya + i * 64);
        const int ch = 16 + w * 32 + i * 4 + lm;
        ldsm_x4_t(u, sb + OFF_U + lr * U_PITCH + ((ch ^ ((ch >> 3) & 1)) << 4));
#pragma unroll
        for (int b = 0; b < 4; b++) r[b] = bmul2(q[b], badd2(y[b], bmul2(u[b], dpair)));
        stsm_x4(kr + Q_OFF + lane * 16 + i * 512, r[0], r[1], r[2], r[3]);
      }
      fence_async_smem();
      __syncwarp();
      if (lane == 0) { tma_store_2d(&maps.out, kr + Q_OFF, DM + d0, w * 256); bulk_commit(); }
    }
    named_bar(1 + grp, 256);
  }
  if (lane == 0) bulk_wait<0>();
}

__global__ void __launch_bounds__(512, 1) __cluster_dims__(2, 1, 1) bpart_kernel(const __grid_constant__ BMaps maps, int end) {
  bpart_body(maps, blockIdx.x * 2, gridDim.x * 2, end);
}

struct GemmMaps {
  CUtensorMap o;
  CUtensorMap w;
  CUtensorMap c;
};
namespace k3 {
constexpr int STAGES = 6;
constexpr int W_BYTES = 2 * 8192, O_BYTES = K3_N * 128, STAGE_BYTES = W_BYTES + O_BYTES;
constexpr int TT = (S_LEN + K3_N - 1) / K3_N, NGEMM = TT * (DM / 128), NB = 128 - NGEMM, KSTEPS = HD / 64;
constexpr int SMEM_G = STAGES * STAGE_BYTES + 1024 + 256;
constexpr int SMEM = SMEM_G > bp::SMEM ? SMEM_G : bp::SMEM;
static_assert(STAGE_BYTES % 1024 == 0, "swizzle atoms");
}

__global__ void __launch_bounds__(512, 1)
tail_kernel(const __grid_constant__ GemmMaps maps, const __grid_constant__ BMaps bmaps) {
  using namespace k3;
  if (blockIdx.x < NB) {
    bpart_body(bmaps, bp::NTASK - 2 * NB + 2 * blockIdx.x, bp::NTASK, bp::NTASK);
    return;
  }
  extern __shared__ uint8_t smem_raw[];
  const uint32_t sbase = (smem_u32(smem_raw) + 1023) & ~1023u;
  const uint32_t bars = sbase + STAGES * STAGE_BYTES;
  const int tid = threadIdx.x, warp = tid >> 5;
  const int tt = (blockIdx.x - NB) / 8, ct = (blockIdx.x - NB) % 8;

  if (tid == 0) {
    for (int s = 0; s < STAGES; s++) { mbar_init(bars + 8 * s, 1); mbar_init(bars + 8 * (STAGES + s), 2); }
    asm volatile("fence.mbarrier_init.release.cluster;" ::: "memory");
  }
  __syncthreads();

  if (warp >= 8) {
    if (tid == 256) {
      tma_prefetch_desc(&maps.o);
      for (int k = 0; k < STAGES; k++) {
        const uint32_t full = bars + 8 * k, sa = sbase + k * STAGE_BYTES;
        mbar_expect_tx(full, STAGE_BYTES);
#pragma unroll
        for (int j = 0; j < 2; j++) tma_load_2d(sa + j * 8192, &maps.w, ct * 128 + j * 64, k * 64, full);
      }
      asm volatile("griddepcontrol.wait;" ::: "memory");
      int stage = 0; uint32_t ph = 1;
      for (int k = 0; k < KSTEPS; k++) {
        mbar_wait(bars + 8 * (STAGES + stage), ph);
        const uint32_t full = bars + 8 * stage, sa = sbase + stage * STAGE_BYTES;
        const bool pre = k < STAGES;
        if (!pre) mbar_expect_tx(full, STAGE_BYTES);
        tma_load_2d(sa + W_BYTES, &maps.o, k * 64, tt * K3_N, full);
        if (!pre) {
#pragma unroll
          for (int j = 0; j < 2; j++) tma_load_2d(sa + j * 8192, &maps.w, ct * 128 + j * 64, k * 64, full);
        }
        if (++stage == STAGES) { stage = 0; ph ^= 1; }
      }
    }
  } else {
    const int wg = warp >> 2, lane = tid & 31, wq = warp & 3;
    int stage = 0; uint32_t ph = 0;
    float acc[K3_N / 2];
    int prev = -1;
    for (int k = 0; k < KSTEPS; k++) {
      mbar_wait(bars + 8 * stage, ph);
      const uint32_t sa = sbase + stage * STAGE_BYTES;
      wg_fence();
#pragma unroll
      for (int kk = 0; kk < 4; kk++) {
        const uint64_t da = make_desc(sa + wg * 8192 + kk * 2048, 16, 1024, 1);
        const uint64_t db = make_desc(sa + W_BYTES + kk * 32, 16, 1024, 1);
        wgmma_k3_ss_ta(acc, da, db, (k | kk) != 0);
      }
      wg_commit();
      if (prev >= 0) { wg_wait<1>(); if ((tid & 127) == 0) mbar_arrive(bars + 8 * (STAGES + prev)); }
      prev = stage;
      if (++stage == STAGES) { stage = 0; ph ^= 1; }
    }
    wg_wait<0>();
#pragma unroll
    for (int i = 0; i < K3_N / 2; i++) asm volatile("" : "+f"(acc[i]) :: "memory");
    named_bar(1, 256);
    const uint32_t ebuf = sbase + wg * STAGE_BYTES;
    const uint32_t ea = ebuf + ((lane >> 4) * 8 + (lane & 7)) * 128 + (((2 * wq + ((lane >> 3) & 1)) ^ (lane & 7)) << 4);
#pragma unroll
    for (int i = 0; i < K3_N / 8; i += 2) {
      const int i1 = i + 1 < K3_N / 8 ? i + 1 : i;
      stsm_x4_t(ea + i * 1024, pack_bf16(acc[4 * i], acc[4 * i + 1]), pack_bf16(acc[4 * i + 2], acc[4 * i + 3]),
                pack_bf16(acc[4 * i1], acc[4 * i1 + 1]), pack_bf16(acc[4 * i1 + 2], acc[4 * i1 + 3]));
    }
    fence_async_smem();
    named_bar(2 + wg, 128);
    if ((tid & 127) == 0) {
      tma_store_2d(&maps.c, ebuf, ct * 128 + wg * 64, tt * K3_N);
      bulk_commit();
      bulk_wait<0>();
    }
  }
}

typedef CUresult (*EncodeFn)(CUtensorMap*, CUtensorMapDataType, cuuint32_t, void*, const cuuint64_t*, const cuuint64_t*,
                             const cuuint32_t*, const cuuint32_t*, CUtensorMapInterleave, CUtensorMapSwizzle,
                             CUtensorMapL2promotion, CUtensorMapFloatOOBfill);

void make_map(EncodeFn enc, CUtensorMap* m, const void* ptr, uint64_t cols, uint64_t rows, uint64_t pitch_elems,
              uint32_t box_cols, uint32_t box_rows, CUtensorMapSwizzle swz,
              CUtensorMapL2promotion promo = CU_TENSOR_MAP_L2_PROMOTION_L2_128B) {
  cuuint64_t dims[2] = {cols, rows};
  cuuint64_t strides[1] = {pitch_elems * 2};
  cuuint32_t box[2] = {box_cols, box_rows};
  cuuint32_t es[2] = {1, 1};
  enc(m, CU_TENSOR_MAP_DATA_TYPE_BFLOAT16, 2, const_cast<void*>(ptr), dims, strides, box, es, CU_TENSOR_MAP_INTERLEAVE_NONE, swz,
      promo, CU_TENSOR_MAP_FLOAT_OOB_FILL_NONE);
}

void make_map_nd(EncodeFn enc, CUtensorMap* m, const void* ptr, int rank, const uint64_t* dims, const uint64_t* strides_elems,
                 const uint32_t* box, CUtensorMapSwizzle swz) {
  cuuint64_t d[5], st[4]; cuuint32_t b[5], es[5];
  for (int i = 0; i < rank; i++) { d[i] = dims[i]; b[i] = box[i]; es[i] = 1; if (i) st[i - 1] = strides_elems[i] * 2; }
  enc(m, CU_TENSOR_MAP_DATA_TYPE_BFLOAT16, rank, const_cast<void*>(ptr), d, st, b, es, CU_TENSOR_MAP_INTERLEAVE_NONE, swz,
      CU_TENSOR_MAP_L2_PROMOTION_L2_128B, CU_TENSOR_MAP_FLOAT_OOB_FILL_NONE);
}

}

extern "C" void kernel_launch(void* const* d_in, const int* in_sizes, int n_in, void* d_out, int out_size) {
  (void)in_sizes; (void)n_in; (void)out_size;
  const bf16* x = (const bf16*)d_in[0];
  const bf16* mem0 = (const bf16*)d_in[1];
  const bf16* Wq = (const bf16*)d_in[2];
  const bf16* Wk = (const bf16*)d_in[3];
  const bf16* Wv = (const bf16*)d_in[4];
  const bf16* Wo = (const bf16*)d_in[5];
  const bf16* Bq = (const bf16*)d_in[7];
  const bf16* Bk = (const bf16*)d_in[8];
  const bf16* Bv = (const bf16*)d_in[9];
  const bf16* shift_k = (const bf16*)d_in[10];
  const bf16* ssm_k = (const bf16*)d_in[11];
  const bf16* ssm_D = (const bf16*)d_in[12];
  bf16* out = (bf16*)d_out;

  static EncodeFn enc = nullptr;
  static uint64_t xbase0;
  static int nsm = 132;
  static cudaStream_t s1;
  static cudaEvent_t ev_fork, ev_join;
  if (!enc) {
    cudaDriverEntryPointQueryResult qr;
    void* fn = nullptr;
    cudaGetDriverEntryPoint("cuTensorMapEncodeTiled", &fn, cudaEnableDefault, &qr);
    enc = (EncodeFn)fn;
    void* ps = nullptr;
    cudaGetSymbolAddress(&ps, g_scratch);
    xbase0 = (uint64_t)ps;
    if ((xbase0 >> 32) != ((xbase0 + xo::BYTES - 1) >> 32)) xbase0 += xo::BYTES;
    cudaFuncSetAttribute(tail_kernel, cudaFuncAttributeMaxDynamicSharedMemorySize, k3::SMEM);
    cudaFuncSetAttribute(chain_kernel, cudaFuncAttributeMaxDynamicSharedMemorySize, chain::SMEM);
    cudaFuncSetAttribute(bpart_kernel, cudaFuncAttributeMaxDynamicSharedMemorySize, bp::SMEM);
    cudaStreamCreateWithFlags(&s1, cudaStreamNonBlocking);
    cudaEventCreateWithFlags(&ev_fork, cudaEventDisableTiming);
    cudaEventCreateWithFlags(&ev_join, cudaEventDisableTiming);
    int dev = 0; cudaGetDevice(&dev);
    cudaDeviceGetAttribute(&nsm, cudaDevAttrMultiProcessorCount, dev);
  }
  uint64_t xbase = xbase0;
  const CUtensorMapSwizzle SW128 = CU_TENSOR_MAP_SWIZZLE_128B, SW64 = CU_TENSOR_MAP_SWIZZLE_64B;
  GemmMaps m3; ChainMaps mc;
  make_map(enc, &m3.o, (void*)(xbase + xo::O), HD, S_LEN, HD, 64, K3_N, SW128);
  make_map(enc, &m3.w, Wo, DM, HD, DM, 64, 64, SW128);
  make_map(enc, &m3.c, out, DM, S_LEN, OUT_LD, 64, K3_N, SW128);
  const CUtensorMapL2promotion P256 = CU_TENSOR_MAP_L2_PROMOTION_L2_256B;
  make_map(enc, &mc.wq, Wq, HD, DM, HD, 64, 128, SW128, P256);
  make_map(enc, &mc.wk, Wk, HD, DM, HD, 64, 128, SW128, P256);
  make_map(enc, &mc.wv, Wv, HD, DM, HD, 64, 128, SW128, P256);
  make_map(enc, &mc.wo, Wo, DM, HD, DM, 32, 256, SW64, P256);
  {
    const uint64_t dx[3] = {64, S_LEN, DM / 64}, sx[3] = {1, DM, 64};
    const uint32_t bx[3] = {64, SEG, 8};
    make_map_nd(enc, &mc.x, x, 3, dx, sx, bx, SW128);
    const uint32_t bq[3] = {64, SEG, 4};
    make_map_nd(enc, &mc.xq, x, 3, dx, sx, bq, SW128);
    mc.xp = (const char*)x;
  }

  const int skip = 0;
  mc.t_step = T_STEP; mc.t_phase = T_PHASE;
  BMaps mb;
  const CUtensorMapSwizzle SWN = CU_TENSOR_MAP_SWIZZLE_NONE;
  make_map(enc, &mb.k, Bk, DM, S_LEN, DM, 8, 256, SWN);
  make_map(enc, &mb.q, Bq, DM, S_LEN, DM, 8, 256, SWN);
  make_map(enc, &mb.v, Bv, DM, S_LEN, DM, 8, 256, SWN);
  mb.shift_k = shift_k; mb.ssm_k = ssm_k; mb.ssm_D = ssm_D;
  make_map(enc, &mb.out, out, OUT_LD, S_LEN, OUT_LD, 8, 256, SWN);
  make_map(enc, &mb.k8, Bk, DM, S_LEN, DM, 8, 8, SWN);
  cudaStream_t s0 = cudaStreamPerThread;
  const int nb = nsm >= 132 ? 4 : 2, ntask1 = bp::NTASK - 2 * k3::NB;
  const bool fork = nsm >= 130 && !(skip & 16);
  if (fork) {
    cudaEventRecord(ev_fork, s0);
    cudaStreamWaitEvent(s1, ev_fork, 0);
    if (!(skip & 1)) bpart_kernel<<<nb, 512, bp::SMEM, s1>>>(mb, ntask1);
    cudaEventRecord(ev_join, s1);
  } else if (!(skip & 1)) {
    bpart_kernel<<<ntask1 / 2, 512, bp::SMEM, s0>>>(mb, ntask1);
  }
  if (!(skip & 4)) chain_kernel<<<128, 256, chain::SMEM, s0>>>(mc, mem0, xbase);
  if (!(skip & 8)) {
    cudaLaunchAttribute pdl[1];
    pdl[0].id = cudaLaunchAttributeProgrammaticStreamSerialization;
    pdl[0].val.programmaticStreamSerializationAllowed = 1;
    cudaLaunchConfig_t cfg = {};
    cfg.gridDim = dim3(128); cfg.blockDim = dim3(512); cfg.dynamicSmemBytes = k3::SMEM; cfg.stream = s0;
    cfg.attrs = pdl; cfg.numAttrs = 1;
    cudaLaunchKernelEx(&cfg, tail_kernel, m3, mb);
  }
  if (fork) cudaStreamWaitEvent(s0, ev_join, 0);
}
```

```cpp
#include <cuda_runtime.h>
#include <cuda_bf16.h>
#include <cuda.h>
#include <stdint.h>

namespace {

constexpr int S_LEN = 2048;
constexpr int DM = 1024;
constexpr int NH = 32;
constexpr int DH = 128;
constexpr int HD = NH * DH;
constexpr int SEG = 32;
constexpr int NSEG = S_LEN / SEG;
constexpr int OUT_LD = 2048;

typedef __nv_bfloat16 bf16;
#define K3_N 160

__device__ __forceinline__ uint32_t smem_u32(const void* p) { return (uint32_t)__cvta_generic_to_shared(p); }

__device__ __forceinline__ void mbar_init(uint32_t bar, uint32_t count) {
  asm volatile("mbarrier.init.shared::cta.b64 [%0], %1;" ::"r"(bar), "r"(count) : "memory");
}
__device__ __forceinline__ void mbar_expect_tx(uint32_t bar, uint32_t bytes) {
  asm volatile("mbarrier.arrive.expect_tx.shared::cta.b64 _, [%0], %1;" ::"r"(bar), "r"(bytes) : "memory");
}
__device__ __forceinline__ void mbar_arrive(uint32_t bar) {
  asm volatile("mbarrier.arrive.shared::cta.b64 _, [%0];" ::"r"(bar) : "memory");
}
__device__ __forceinline__ bool mbar_try(uint32_t bar, uint32_t parity) {
  uint32_t ok;
  asm volatile("{.reg .pred p; mbarrier.try_wait.parity.shared::cta.b64 p, [%1], %2; selp.u32 %0, 1, 0, p;}"
               : "=r"(ok) : "r"(bar), "r"(parity) : "memory");
  return ok;
}
__device__ __forceinline__ bool mbar_test(uint32_t bar, uint32_t parity) {
  uint32_t ok;
  asm volatile("{.reg .pred p; mbarrier.test_wait.parity.shared::cta.b64 p, [%1], %2; selp.u32 %0, 1, 0, p;}"
               : "=r"(ok) : "r"(bar), "r"(parity) : "memory");
  return ok;
}
template <int HINT = 1>
__device__ __forceinline__ void mbar_wait(uint32_t bar, uint32_t parity) {
  int guard = 0;
  while (__builtin_expect(!mbar_try(bar, parity), HINT)) { if (++guard > (1 << 22)) __trap(); }
}
__device__ __forceinline__ void tma_load_2d(uint32_t dst, const CUtensorMap* map, int c0, int c1, uint32_t bar) {
  asm volatile("cp.async.bulk.tensor.2d.shared::cluster.global.mbarrier::complete_tx::bytes [%0], [%1, {%3, %4}], [%2];"
               ::"r"(dst), "l"(map), "r"(bar), "r"(c0), "r"(c1) : "memory");
}
__device__ __forceinline__ void tma_store_2d(const CUtensorMap* map, uint32_t src, int c0, int c1) {
  asm volatile("cp.async.bulk.tensor.2d.global.shared::cta.bulk_group [%0, {%2, %3}], [%1];"
               ::"l"(map), "r"(src), "r"(c0), "r"(c1) : "memory");
}
__device__ __forceinline__ void tma_prefetch_2d(const CUtensorMap* map, int c0, int c1) {
  asm volatile("cp.async.bulk.prefetch.tensor.2d.L2.global [%0, {%1, %2}];" ::"l"(map), "r"(c0), "r"(c1) : "memory");
}
__device__ __forceinline__ void tma_prefetch_desc(const CUtensorMap* map) {
  asm volatile("prefetch.tensormap [%0];" ::"l"(map) : "memory");
}
__device__ __forceinline__ void fence_async_smem() { asm volatile("fence.proxy.async.shared::cta;" ::: "memory"); }
__device__ __forceinline__ void bulk_commit() { asm volatile("cp.async.bulk.commit_group;" ::: "memory"); }
template <int N> __device__ __forceinline__ void bulk_wait_read() { asm volatile("cp.async.bulk.wait_group.read %0;" ::"n"(N) : "memory"); }
template <int N> __device__ __forceinline__ void bulk_wait() { asm volatile("cp.async.bulk.wait_group %0;" ::"n"(N) : "memory"); }
__device__ __forceinline__ void named_bar(int id, int n) { asm volatile("bar.sync %0, %1;" ::"r"(id), "r"(n) : "memory"); }

__device__ __forceinline__ void named_bar_arrive(int id, int n) { asm volatile("bar.arrive %0, %1;" ::"r"(id), "r"(n) : "memory"); }
__device__ __forceinline__ float ex2(float x) { float y; asm("ex2.approx.ftz.f32 %0, %1;" : "=f"(y) : "f"(x)); return y; }
__device__ __forceinline__ float rcp(float x) { float y; asm("rcp.approx.ftz.f32 %0, %1;" : "=f"(y) : "f"(x)); return y; }

__device__ __forceinline__ void sts32(uint32_t a, uint32_t x) { asm volatile("st.shared.b32 [%0], %1;" ::"r"(a), "r"(x) : "memory"); }
__device__ __forceinline__ uint32_t lds32(uint32_t a) { uint32_t x; asm volatile("ld.shared.b32 %0, [%1];" : "=r"(x) : "r"(a) : "memory"); return x; }
__device__ __forceinline__ uint32_t lds32v(uint32_t a) { uint32_t x; asm volatile("ld.volatile.shared.b32 %0, [%1];" : "=r"(x) : "r"(a) : "memory"); return x; }
__device__ __forceinline__ void sts128(uint32_t a, const uint4& v) { asm volatile("st.shared.v4.b32 [%0], {%1,%2,%3,%4};" ::"r"(a), "r"(v.x), "r"(v.y), "r"(v.z), "r"(v.w) : "memory"); }
__device__ __forceinline__ void sts128f(uint32_t a, const float4& v) { asm volatile("st.shared.v4.f32 [%0], {%1,%2,%3,%4};" ::"r"(a), "f"(v.x), "f"(v.y), "f"(v.z), "f"(v.w) : "memory"); }
__device__ __forceinline__ uint4 lds128(uint32_t a) { uint4 v; asm volatile("ld.shared.v4.b32 {%0,%1,%2,%3}, [%4];" : "=r"(v.x), "=r"(v.y), "=r"(v.z), "=r"(v.w) : "r"(a) : "memory"); return v; }
__device__ __forceinline__ float4 lds128f(uint32_t a) { float4 v; asm volatile("ld.shared.v4.f32 {%0,%1,%2,%3}, [%4];" : "=f"(v.x), "=f"(v.y), "=f"(v.z), "=f"(v.w) : "r"(a) : "memory"); return v; }

__device__ __forceinline__ void cp_async16(uint32_t dst, const void* src) { asm volatile("cp.async.cg.shared.global [%0], [%1], 16;" ::"r"(dst), "l"(src) : "memory"); }
__device__ __forceinline__ void cp_async_commit() { asm volatile("cp.async.commit_group;" ::: "memory"); }
template <int N> __device__ __forceinline__ void cp_async_wait_group() { asm volatile("cp.async.wait_group %0;" ::"n"(N) : "memory"); }

__device__ __forceinline__ void wg_fence() { asm volatile("wgmma.fence.sync.aligned;" ::: "memory"); }
__device__ __forceinline__ void wg_commit() { asm volatile("wgmma.commit_group.sync.aligned;" ::: "memory"); }
template <int N> __device__ __forceinline__ void wg_wait() { asm volatile("wgmma.wait_group.sync.aligned %0;" ::"n"(N) : "memory"); }
__device__ __forceinline__ uint64_t make_desc(uint32_t addr, uint32_t lbo, uint32_t sbo, uint32_t swz) {
  return (uint64_t)((addr & 0x3FFFF) >> 4) | ((uint64_t)(lbo >> 4) << 16) | ((uint64_t)(sbo >> 4) << 32) | ((uint64_t)swz << 62);
}

__device__ __forceinline__ void ldsm_x4(uint32_t (&r)[4], uint32_t addr) {
  asm volatile("ldmatrix.sync.aligned.m8n8.x4.shared.b16 {%0,%1,%2,%3}, [%4];"
               : "=r"(r[0]), "=r"(r[1]), "=r"(r[2]), "=r"(r[3]) : "r"(addr) : "memory");
}
__device__ __forceinline__ void ldsm_x4_t(uint32_t (&r)[4], uint32_t addr) {
  asm volatile("ldmatrix.sync.aligned.m8n8.x4.trans.shared.b16 {%0,%1,%2,%3}, [%4];"
               : "=r"(r[0]), "=r"(r[1]), "=r"(r[2]), "=r"(r[3]) : "r"(addr) : "memory");
}
__device__ __forceinline__ void stsm_x4(uint32_t addr, uint32_t r0, uint32_t r1, uint32_t r2, uint32_t r3) {
  asm volatile("stmatrix.sync.aligned.m8n8.x4.shared.b16 [%0], {%1,%2,%3,%4};"
               ::"r"(addr), "r"(r0), "r"(r1), "r"(r2), "r"(r3) : "memory");
}
__device__ __forceinline__ void stsm_x4_t(uint32_t addr, uint32_t r0, uint32_t r1, uint32_t r2, uint32_t r3) {
  asm volatile("stmatrix.sync.aligned.m8n8.x4.trans.shared.b16 [%0], {%1,%2,%3,%4};" ::"r"(addr), "r"(r0), "r"(r1), "r"(r2), "r"(r3) : "memory");
}
__device__ __forceinline__ void mma16816(float (&c)[4], const uint32_t (&a)[4], uint32_t b0, uint32_t b1) {
  asm volatile("mma.sync.aligned.m16n8k16.row.col.f32.bf16.bf16.f32 {%0,%1,%2,%3}, {%4,%5,%6,%7}, {%8,%9}, {%0,%1,%2,%3};"
               : "+f"(c[0]), "+f"(c[1]), "+f"(c[2]), "+f"(c[3])
               : "r"(a[0]), "r"(a[1]), "r"(a[2]), "r"(a[3]), "r"(b0), "r"(b1));
}
__device__ __forceinline__ void mma1688(float (&c)[4], uint32_t a0, uint32_t a1, uint32_t b0) {
  asm volatile("mma.sync.aligned.m16n8k8.row.col.f32.bf16.bf16.f32 {%0,%1,%2,%3}, {%4,%5}, {%6}, {%0,%1,%2,%3};"
               : "+f"(c[0]), "+f"(c[1]), "+f"(c[2]), "+f"(c[3]) : "r"(a0), "r"(a1), "r"(b0));
}
__device__ __forceinline__ uint32_t pack_bf16(float lo, float hi) {
  uint32_t r;
  asm("cvt.rn.bf16x2.f32 %0, %1, %2;" : "=r"(r) : "f"(hi), "f"(lo));
  return r;
}
__device__ __forceinline__ float bf_lo(uint32_t w) { return __uint_as_float(w << 16); }
__device__ __forceinline__ float bf_hi(uint32_t w) { return __uint_as_float(w & 0xFFFF0000u); }

__device__ __forceinline__ uint4 ld_relaxed4(const void* p) {
  uint4 v;
  asm volatile("ld.relaxed.gpu.global.v4.u32 {%0,%1,%2,%3}, [%4];" : "=r"(v.x), "=r"(v.y), "=r"(v.z), "=r"(v.w) : "l"(p) : "memory");
  return v;
}
__device__ __forceinline__ void st_relaxed4(void* p, uint32_t a, uint32_t b, uint32_t c, uint32_t d) {
  asm volatile("st.relaxed.gpu.global.v4.u32 [%0], {%1,%2,%3,%4};" ::"l"(p), "r"(a), "r"(b), "r"(c), "r"(d) : "memory");
}
__device__ __forceinline__ void st_relaxed2(void* p, uint32_t a, uint32_t b) {
  asm volatile("st.relaxed.gpu.global.v2.u32 [%0], {%1,%2};" ::"l"(p), "r"(a), "r"(b) : "memory");
}
__device__ __forceinline__ void st_relaxed1(void* p, uint32_t a) {
  asm volatile("st.relaxed.gpu.global.u32 [%0], %1;" ::"l"(p), "r"(a) : "memory");
}

__device__ __forceinline__ uint2 ld_relaxed2(const void* p) {
  uint2 v;
  asm volatile("ld.relaxed.gpu.global.v2.u32 {%0,%1}, [%2];" : "=r"(v.x), "=r"(v.y) : "l"(p) : "memory");
  return v;
}
__device__ __forceinline__ void sts64(uint32_t a, uint32_t x, uint32_t y) { asm volatile("st.shared.v2.b32 [%0], {%1,%2};" ::"r"(a), "r"(x), "r"(y) : "memory"); }
__device__ __forceinline__ uint2 lds64(uint32_t a) { uint2 v; asm volatile("ld.shared.v2.b32 {%0,%1}, [%2];" : "=r"(v.x), "=r"(v.y) : "r"(a) : "memory"); return v; }
__device__ __forceinline__ void lds128r(uint32_t (&r)[4], uint32_t a) {
  asm volatile("ld.shared.v4.b32 {%0,%1,%2,%3}, [%4];" : "=r"(r[0]), "=r"(r[1]), "=r"(r[2]), "=r"(r[3]) : "r"(a) : "memory");
}
__device__ __forceinline__ uint32_t mapa(uint32_t addr, uint32_t rank) { uint32_t r; asm volatile("mapa.shared::cluster.u32 %0, %1, %2;" : "=r"(r) : "r"(addr), "r"(rank)); return r; }
__device__ __forceinline__ void st_async1(uint32_t dst, uint32_t a, uint32_t bar) {
  asm volatile("st.async.weak.shared::cluster.mbarrier::complete_tx::bytes.b32 [%0], %1, [%2];" ::"r"(dst), "r"(a), "r"(bar) : "memory");
}
__device__ __forceinline__ void st_async2(uint32_t dst, uint32_t a, uint32_t b, uint32_t bar) {
  asm volatile("st.async.weak.shared::cluster.mbarrier::complete_tx::bytes.v2.b32 [%0], {%1,%2}, [%3];" ::"r"(dst), "r"(a), "r"(b), "r"(bar) : "memory");
}
__device__ __forceinline__ void cluster_arrive() { asm volatile("barrier.cluster.arrive.relaxed.aligned;" ::: "memory"); }
__device__ __forceinline__ void cluster_wait() { asm volatile("barrier.cluster.wait.acquire.aligned;" ::: "memory"); }

__device__ __forceinline__ void wgmma_k3_ss_ta(float (&d)[80], uint64_t da, uint64_t db, int scale_d) {
  asm volatile("{.reg .pred p; setp.ne.b32 p, %82, 0;\n"
    "wgmma.mma_async.sync.aligned.m64n160k16.f32.bf16.bf16 {%0, %1, %2, %3, %4, %5, %6, %7, %8, %9, %10, %11, %12, %13, %14, %15, %16, %17, %18, %19, %20, %21, %22, %23, %24, %25, %26, %27, %28, %29, %30, %31, %32, %33, %34, %35, %36, %37, %38, %39, %40, %41, %42, %43, %44, %45, %46, %47, %48, %49, %50, %51, %52, %53, %54, %55, %56, %57, %58, %59, %60, %61, %62, %63, %64, %65, %66, %67, %68, %69, %70, %71, %72, %73, %74, %75, %76, %77, %78, %79}, %80, %81, p, 1, 1, 1, 0;}"
    : "+f"(d[0]), "+f"(d[1]), "+f"(d[2]), "+f"(d[3]), "+f"(d[4]), "+f"(d[5]), "+f"(d[6]), "+f"(d[7]), "+f"(d[8]), "+f"(d[9]), "+f"(d[10]), "+f"(d[11]), "+f"(d[12]), "+f"(d[13]), "+f"(d[14]), "+f"(d[15]), "+f"(d[16]), "+f"(d[17]), "+f"(d[18]), "+f"(d[19]), "+f"(d[20]), "+f"(d[21]), "+f"(d[22]), "+f"(d[23]), "+f"(d[24]), "+f"(d[25]), "+f"(d[26]), "+f"(d[27]), "+f"(d[28]), "+f"(d[29]), "+f"(d[30]), "+f"(d[31]), "+f"(d[32]), "+f"(d[33]), "+f"(d[34]), "+f"(d[35]), "+f"(d[36]), "+f"(d[37]), "+f"(d[38]), "+f"(d[39]), "+f"(d[40]), "+f"(d[41]), "+f"(d[42]), "+f"(d[43]), "+f"(d[44]), "+f"(d[45]), "+f"(d[46]), "+f"(d[47]), "+f"(d[48]), "+f"(d[49]), "+f"(d[50]), "+f"(d[51]), "+f"(d[52]), "+f"(d[53]), "+f"(d[54]), "+f"(d[55]), "+f"(d[56]), "+f"(d[57]), "+f"(d[58]), "+f"(d[59]), "+f"(d[60]), "+f"(d[61]), "+f"(d[62]), "+f"(d[63]), "+f"(d[64]), "+f"(d[65]), "+f"(d[66]), "+f"(d[67]), "+f"(d[68]), "+f"(d[69]), "+f"(d[70]), "+f"(d[71]), "+f"(d[72]), "+f"(d[73]), "+f"(d[74]), "+f"(d[75]), "+f"(d[76]), "+f"(d[77]), "+f"(d[78]), "+f"(d[79])
    : "l"(da), "l"(db), "r"(scale_d));
}
__device__ __forceinline__ void wgmma_m64n32_ss_ta(float (&d)[16], uint64_t da, uint64_t db, int scale_d) {
  asm volatile("{.reg .pred p; setp.ne.b32 p, %18, 0;\n"
    "wgmma.mma_async.sync.aligned.m64n32k16.f32.bf16.bf16 {%0, %1, %2, %3, %4, %5, %6, %7, %8, %9, %10, %11, %12, %13, %14, %15}, %16, %17, p, 1, 1, 1, 0;}"
    : "+f"(d[0]), "+f"(d[1]), "+f"(d[2]), "+f"(d[3]), "+f"(d[4]), "+f"(d[5]), "+f"(d[6]), "+f"(d[7]), "+f"(d[8]), "+f"(d[9]), "+f"(d[10]), "+f"(d[11]), "+f"(d[12]), "+f"(d[13]), "+f"(d[14]), "+f"(d[15])
    : "l"(da), "l"(db), "r"(scale_d));
}

__device__ __forceinline__ void wgmma_m64n32_rs(float (&d)[16], const uint32_t (&a)[4], uint64_t db, int scale_d) {
  asm volatile("{.reg .pred p; setp.ne.b32 p, %21, 0;\n"
    "wgmma.mma_async.sync.aligned.m64n32k16.f32.bf16.bf16 {%0, %1, %2, %3, %4, %5, %6, %7, %8, %9, %10, %11, %12, %13, %14, %15}, {%16, %17, %18, %19}, %20, p, 1, 1, 0;}"
    : "+f"(d[0]), "+f"(d[1]), "+f"(d[2]), "+f"(d[3]), "+f"(d[4]), "+f"(d[5]), "+f"(d[6]), "+f"(d[7]), "+f"(d[8]), "+f"(d[9]), "+f"(d[10]), "+f"(d[11]), "+f"(d[12]), "+f"(d[13]), "+f"(d[14]), "+f"(d[15])
    : "r"(a[0]), "r"(a[1]), "r"(a[2]), "r"(a[3]), "l"(db), "r"(scale_d));
}

#define X_POS 7
#define T_STEP 2720
#define T_PHASE 1728
#define RATE0 2295
#define T_LAG 32
#define T_TOL 192
#define T_SLIP 640
#define O_FIX 6
#define NTMP 4
#define V_PRE 6
#define SFENCE(i) asm volatile("{.reg .pred p; setp.eq.u32 p, %0, %1; @p trap;}" ::"r"(n), "r"(4096 + (i)) : "memory")
constexpr int RING = 4;
constexpr uint32_t EMPTY = 0xFFFFFFFFu;
namespace xo {
constexpr uint32_t SLOT = 1u << 20, HEAD = 16384;
constexpr uint32_t VM = 512;
constexpr uint32_t PT = 1024;
constexpr uint32_t PM = 1536;
constexpr uint32_t VT = 8192;
constexpr uint32_t MEM = NH * HEAD;
constexpr uint32_t OM = MEM + 16384;
constexpr uint32_t O = RING * SLOT;
constexpr uint32_t BYTES = O + S_LEN * HD * 2;
}
__device__ __align__(1024) uint4 g_scratch[2 * (xo::BYTES / 16)];
__device__ unsigned g_epoch;
__device__ __align__(16) unsigned g_rate[128];

struct ChainMaps {
  CUtensorMap wq, wk, wv;
  CUtensorMap wo;
  CUtensorMap x, xq;
  const char* xp;
  uint32_t t_step, t_phase;
};

namespace chain {
constexpr int OFF_X = 65536;
constexpr int OFF_MEM = 131072;
constexpr int OFF_WS = 0;
constexpr int OFF_FP = 147456;
constexpr int OFF_KT = 163840;
constexpr int OFF_QT = 180224;
constexpr int OFF_VT = 196608;
constexpr int OFF_PX = 204800;
constexpr int OFF_S4 = OFF_PX + 1536;
constexpr int OFF_QM = 212992;
constexpr int OFF_KM = 215040;
constexpr int OFF_S1 = 217088;
constexpr int OFF_WVR = 0;
constexpr int OFF_WOR = 147456;
constexpr int OFF_RED = 212992;
constexpr int OFF_VPX = 221184;
constexpr int OFF_RX = 223232;
constexpr int OFF_BAR = 229376;
constexpr int BAR_X = OFF_BAR, BAR_TOK = OFF_BAR + 16, BAR_EX = OFF_BAR + 32, BAR_P = OFF_BAR + 40, GRID_TGT = OFF_BAR + 128;
constexpr int CT_BASE = GRID_TGT + 4, CT_HEAD = GRID_TGT + 8, CT_OM = GRID_TGT + 12, CT_MP = GRID_TGT + 16, CT_O = GRID_TGT + 20, CT_PF = GRID_TGT + 24;
constexpr int CT_TT = GRID_TGT + 28, CT_T = GRID_TGT + 32;
constexpr uint32_t RANK_BIT = 1u << 24;
constexpr int OFF_RX1 = OFF_BAR + 256;
constexpr int SMEM = OFF_RX1 + 2048;
constexpr uint32_t SB_LO = 1024;
constexpr float SCALE = 0.08838834764831845f, L2E = 1.4426950408889634f;
}

__device__ __forceinline__ uint32_t umax4(uint32_t a, uint32_t b, uint32_t c, uint32_t d) { return max(max(a, b), max(c, d)); }
__device__ __forceinline__ bool warp_incomplete(uint32_t m) { return __any_sync(0xffffffffu, m == EMPTY); }
#define PIN(x) asm volatile("" : "+r"(x))
#define KEEPALIVE(a, z) do { float _d0, _d1, _d2, _d3; asm volatile("mma.sync.aligned.m16n8k16.row.col.f32.bf16.bf16.f32 {%0,%1,%2,%3}, {%4,%5,%6,%7}, {%4,%5}, {%8,%8,%8,%8};" \
    : "=f"(_d0), "=f"(_d1), "=f"(_d2), "=f"(_d3) : "r"(a[0]), "r"(a[1]), "r"(a[2]), "r"(a[3]), "f"(0.f)); \
      \
    asm volatile("{.reg .pred p; setp.ne.u32 p, %0, 0; @p st.shared.f32 [%0], %1;}" ::"r"(z), "f"(_d0 + _d3) : "memory"); } while (0)
constexpr int POLL_LIMIT = 1 << 15;

__device__ __forceinline__ uint32_t keep(uint32_t x) { return __shfl_sync(0xffffffffu, x, threadIdx.x & 31); }
__device__ __forceinline__ char* gptr(uint32_t hi, uint32_t lo) { return (char*)(((uint64_t)hi << 32) | lo); }
__device__ __forceinline__ uint32_t slot_off(int n) { return ((uint32_t)n & (RING - 1)) * xo::SLOT; }
__device__ __forceinline__ float quad_max(float x) {
  const float a = __shfl_xor_sync(~0u, x, 1), b = __shfl_xor_sync(~0u, x, 2), c = __shfl_xor_sync(~0u, x, 3);
  return fmaxf(fmaxf(x, a), fmaxf(b, c));
}
__device__ __forceinline__ void acc_fence(float (&a)[16]) {
#pragma unroll
  for (int i = 0; i < 16; i++) asm volatile("" : "+f"(a[i]) :: "memory");
}
template <int NB = 1, int STRIDE = 0>
__device__ __forceinline__ void gather_issue(uint32_t dst, const char* src) {
#pragma unroll
  for (int b = 0; b < NB; b++)
#pragma unroll
    for (int i = 0; i < 4; i++) cp_async16(dst + b * STRIDE + i * 512, src + b * STRIDE + i * 512);
  cp_async_commit();
}
template <int NB, int STRIDE>
__device__ __forceinline__ bool gather_incomplete(uint32_t chk) {
  uint32_t m = 0;
#pragma unroll
  for (int b = 0; b < NB; b++) m = max(m, umax4(lds32(chk + b * STRIDE), lds32(chk + b * STRIDE + 512), lds32(chk + b * STRIDE + 1024), lds32(chk + b * STRIDE + 1536)));
  return warp_incomplete(m);
}
__device__ __forceinline__ uint32_t ld_relaxed1(const void* p) {
  uint32_t v;
  asm volatile("ld.relaxed.gpu.global.u32 %0, [%1];" : "=r"(v) : "l"(p) : "memory");
  return v;
}
__device__ __forceinline__ uint32_t gtime() { uint64_t g; asm volatile("mov.u64 %0, %%globaltimer;" : "=l"(g) :: "memory"); return (uint32_t)g; }
#define WAIT_UNTIL(t, ka, alive, id) do { \
    int _d = gtime() - (t); \
    if (__builtin_expect(_d > T_TOL, 0)) do { t += T_SLIP; _d -= T_SLIP; } while (_d > T_TOL); \
    if (alive) for (int _k = 64; _d < -96 && --_k; _d = gtime() - (t)) KEEPALIVE(ka, zr); \
    for (uint32_t _g = 0xFFFFFF80u; (int)(_d & ++_g) < 0;) _d = gtime() - (t); } while (0)
__device__ __forceinline__ void issue_x(uint32_t sb, const CUtensorMap* map, int n, int part, int q = 0) {
  asm volatile("{.reg .pred p; elect.sync _|p, 0xffffffff;\n"
               "@p cp.async.bulk.tensor.3d.shared::cluster.global.mbarrier::complete_tx::bytes [%0], [%1, {%3, %4, %5}], [%2];}"
               ::"r"(sb + chain::OFF_X + part * 32768 + q * 16384), "l"(map), "r"(sb + chain::BAR_X + 8 * part), "r"(0), "r"(n * SEG), "r"(part * 8 + q * 4) : "memory");
}
__device__ __forceinline__ void issue_x_if(uint32_t sb, const CUtensorMap* map, int n, int part, uint32_t on) {
  asm volatile("{.reg .pred p, q; elect.sync _|p, 0xffffffff; setp.ne.and.u32 q, %6, 0, p;\n"
               "@q cp.async.bulk.tensor.3d.shared::cluster.global.mbarrier::complete_tx::bytes [%0], [%1, {%3, %4, %5}], [%2];}"
               ::"r"(sb + chain::OFF_X + part * 32768), "l"(map), "r"(sb + chain::BAR_X + 8 * part), "r"(0), "r"(n * SEG), "r"(part * 8), "r"(on) : "memory");
}
__device__ __forceinline__ void prefetch_l2(const char* p, uint32_t bytes) {
  asm volatile("{.reg .pred p; elect.sync _|p, 0xffffffff; @p cp.async.bulk.prefetch.L2.global [%0], %1;}" ::"l"(p), "r"(bytes) : "memory");
}
__device__ __forceinline__ void expect_elect(uint32_t bar, uint32_t bytes) {
  asm volatile("{.reg .pred p; elect.sync _|p, 0xffffffff; @p mbarrier.arrive.expect_tx.shared::cta.b64 _, [%0], %1;}" ::"r"(bar), "r"(bytes) : "memory");
}
template <int WG> __device__ __forceinline__ constexpr uint64_t xdesc(int ks) {
  return (uint64_t)(((chain::SB_LO + chain::OFF_X + WG * 32768 + (ks >> 2) * 4096 + (ks & 3) * 32) >> 4) + (1u << 16)) |
         ((uint64_t)(64u | (1u << 30)) << 32);
}
template <int WG> __device__ __forceinline__ constexpr uint64_t wdesc(int o, int ks) {
  return (uint64_t)(((chain::SB_LO + chain::OFF_WS + WG * 32768 + o * 16384 + ks * 2048) >> 4) + (1u << 16)) | ((uint64_t)(64u | (1u << 30)) << 32);
}
__device__ __forceinline__ void load_mem0(uint2 (&m)[8], const bf16* __restrict__ mem0) {
#pragma unroll
  for (int r = 0; r < 8; r++) m[r] = ld_relaxed2((const uint2*)(mem0 + r * DM) + threadIdx.x);
}
__device__ __forceinline__ void store_mem0(uint32_t sb, const uint2 (&m)[8]) {
  const uint32_t d = sb + chain::OFF_MEM + threadIdx.x * 64;
  sts128(d, make_uint4(__byte_perm(m[0].x, m[1].x, 0x5410), __byte_perm(m[2].x, m[3].x, 0x5410), __byte_perm(m[4].x, m[5].x, 0x5410), __byte_perm(m[6].x, m[7].x, 0x5410)));
  sts128(d + 16, make_uint4(__byte_perm(m[0].x, m[1].x, 0x7632), __byte_perm(m[2].x, m[3].x, 0x7632), __byte_perm(m[4].x, m[5].x, 0x7632), __byte_perm(m[6].x, m[7].x, 0x7632)));
  sts128(d + 32, make_uint4(__byte_perm(m[0].y, m[1].y, 0x5410), __byte_perm(m[2].y, m[3].y, 0x5410), __byte_perm(m[4].y, m[5].y, 0x5410), __byte_perm(m[6].y, m[7].y, 0x5410)));
  sts128(d + 48, make_uint4(__byte_perm(m[0].y, m[1].y, 0x7632), __byte_perm(m[2].y, m[3].y, 0x7632), __byte_perm(m[4].y, m[5].y, 0x7632), __byte_perm(m[6].y, m[7].y, 0x7632)));
}
template <int K> __device__ __forceinline__ uint32_t loop_zero(int n) { uint32_t z; asm volatile("shr.u32 %0, %1, %2;" : "=r"(z) : "r"(n), "n"(16 + K)); return z; }
#define NEWZ(k) zr = loop_zero<k>(n)

template <int WG>
__device__ __forceinline__ void role_a(const ChainMaps& maps, const bf16* __restrict__ mem0, const uint32_t sb, const uint32_t xbase_hi) {
  using namespace chain;
  const int h = blockIdx.x >> 2;
  const bool J = sb >= RANK_BIT;
  const uint32_t u16 = (threadIdx.x & 96) * 64 + (threadIdx.x & 31) * 16;
  const uint32_t t16 = keep(u16), l16 = keep((threadIdx.x & 31) * 16);
  const uint32_t a_wl = keep((((threadIdx.x >> 4) & 1) * 8 + (threadIdx.x & 7)) * 128 + (((((threadIdx.x >> 4) & 6) + ((threadIdx.x >> 3) & 1)) ^ (threadIdx.x & 7)) << 4));
  const uint32_t xhi = keep(xbase_hi + (t16 >> 16));
#define xh (lds32(sb + CT_HEAD) + t16)
#define xm (lds32(sb + CT_BASE) + t16 + xo::MEM)
#define last_warp __any_sync(0xffffffffu, tv >= 6144)
#define tv (t16 ^ zr)
  const CUtensorMap* wm = J ? &maps.wk : &maps.wq;

  uint32_t aW[2][24][4];
  uint2 m0[8];
  load_mem0(m0, mem0);
  mbar_wait(sb + BAR_P, 0);
#pragma unroll
  for (int ks = 0; ks < 24; ks++) ldsm_x4_t(aW[0][ks], sb + a_wl + OFF_X + WG * 49152 + ks * 2048);
  named_bar(0, 256);
  if (WG == 1 && __any_sync(0xffffffffu, t16 >= 6144)) {
    fence_async_smem();
    if (l16 == 0) {
      mbar_expect_tx(sb + BAR_P + 16, 2 * 16384);
      for (int q = 0; q < 2; q++) tma_load_2d(sb + OFF_X + (4 + q) * 16384, wm, h * DH + (q ^ 1) * 64, q * 512 + 256, sb + BAR_P + 16);
    }
    __syncwarp();
    expect_elect(sb + BAR_X, 32768); expect_elect(sb + BAR_X + 8, 32768); expect_elect(sb + BAR_TOK, 8192);
    issue_x(sb, &maps.x, 0, 0); issue_x(sb, &maps.x, 0, 1);
  }
  mbar_wait(sb + BAR_P + 8, 0);
#pragma unroll
  for (int ks = 0; ks < 16; ks++) ldsm_x4_t(aW[1][ks], sb + a_wl + OFF_X + 6 * 16384 + WG * 32768 + ks * 2048);
  mbar_wait(sb + BAR_P + 16, 0);
#pragma unroll
  for (int ks = 0; ks < 8; ks++) ldsm_x4_t(aW[1][16 + ks], sb + a_wl + OFF_X + (4 + WG) * 16384 + ks * 2048);
  named_bar(0, 256);
  cluster_arrive();
  store_mem0(sb, m0);
  mbar_wait(sb + BAR_P + 24, 0);
  cluster_wait();
  const uint32_t rsb = sb ^ RANK_BIT;
  const uint32_t a_ws = sb + a_wl + OFF_WS + WG * 32768;

  uint32_t ws[2][4][4];
  auto load_ws = [&]() {
#pragma unroll
    for (int q = 0; q < 2; q++) {
      const uint32_t a = a_ws + q * 4096;
      ldsm_x4_t(ws[q][0], a); ldsm_x4_t(ws[q][1], a + 16384); ldsm_x4_t(ws[q][2], a + 2048); ldsm_x4_t(ws[q][3], a + 16384 + 2048);
    }
  };
  uint32_t tref = 0;
#pragma unroll 1
  for (int n = 0; n <= (J ? NSEG : NSEG - 1); n++) {
#define s (n - 1)
#define sv ((int)(n ^ zr) - 1)
    const bool more = __builtin_expect(s + 1 < NSEG, 1);
    uint32_t zr = loop_zero<0>(n);
#define wq ((int)(tv >> 11))
#define lv (l16 ^ zr)
#define gh (xh + slot_off(sv))
    uint32_t tmp[NTMP][4];
    auto load_tmp = [&](int o) {
#pragma unroll
      for (int ks = 0; ks < NTMP; ks++) ldsm_x4_t(tmp[ks], a_ws + o * 16384 + ks * 2048);
    };
    float y[10];
    auto no_p = [&]() {
#pragma unroll
      for (int i = 0; i < 10; i++) asm volatile("mov.b32 %0, %1;" : "=f"(y[i]) : "r"(zr));
    };
    auto finish_p = [&]() {
      const uint32_t gp = gh;
      float sy = ((y[0] + y[1]) + (y[2] + y[3])) + ((y[4] + y[5]) + (y[6] + y[7])) + (y[8] + y[9]);
      const float ry = rcp((sy + __shfl_xor_sync(~0u, sy, 1)) + (__shfl_xor_sync(~0u, sy, 2) + __shfl_xor_sync(~0u, sy, 3)));
      st_relaxed4(gptr(xhi, gp) + xo::PT, pack_bf16(y[2] * ry, y[3] * ry), pack_bf16(y[4] * ry, y[5] * ry), pack_bf16(y[6] * ry, y[7] * ry), pack_bf16(y[8] * ry, y[9] * ry));
      const uint32_t l12 = lv - (lv >> 2);
      st_relaxed1(gptr(xhi, gp - l12) + xo::PM, pack_bf16(y[0] * ry, y[1] * ry));
    };
    auto wait_x = [&]() { mbar_wait<0>(sb + BAR_X + 8 * WG, n & 1); };
    if (__builtin_expect(s < 0, 0)) { load_tmp(1); wait_x(); if (WG == 0) no_p(); }
    else {
      {
        if (WG == 1) { if (__builtin_expect(s > 0, 1)) {
          const uint32_t dst = sb + OFF_MEM + tv + t16 - l16, chk = dst + ((lv >> 5) & 12);
          uint32_t tries = zr;
#pragma unroll 1
          do {
            if (tries) {
              const char* src = gptr(xhi, xm + t16 - l16 + slot_off(sv));
              tref += T_SLIP;
              WAIT_UNTIL(tref, aW[0][0], 1, -1);
              gather_issue<2, 2048>(dst, src);
            }
            KEEPALIVE(aW[0][0], zr);
            cp_async_wait_group<0>();
          } while (gather_incomplete<2, 2048>(chk) && ++tries < POLL_LIMIT);
        } } else if (J == 0) {
          uint32_t tries = s == 0;
#pragma unroll 1
          do {
            if (tries) gather_issue(sb + OFF_VT + tv, gptr(xhi, gh) + xo::VT);
            cp_async_wait_group<0>();
          } while (gather_incomplete<1, 0>(sb + OFF_VT + t16 + ((lv >> 5) & 12)) && ++tries < POLL_LIMIT);
        }
        named_bar(1, 256);
      }
      float c[2][2][4];
#pragma unroll
      for (int i = 0; i < 4; i++) c[i >> 1][i & 1][0] = c[i >> 1][i & 1][1] = c[i >> 1][i & 1][2] = c[i >> 1][i & 1][3] = 0.f;
      {
        const uint32_t a_mem = sb + OFF_MEM + WG * 8192 + l16;
        uint32_t b[4][4];
        bool tok;
        constexpr int PR[16] = {12, 13, 0, 1, 2, 3, 4, 14, 5, 6, 7, 8, 9, 15, 10, 11};
        ldsm_x4_t(b[0], a_mem + PR[0] * 512); ldsm_x4_t(b[1], a_mem + PR[1] * 512);
#pragma unroll
        for (int i = 0; i < 16; i++) {
          if ((i & 1) == 0 && i < 14) {
            ldsm_x4_t(b[(i + 2) & 3], a_mem + PR[i + 2] * 512); ldsm_x4_t(b[(i + 3) & 3], a_mem + PR[i + 3] * 512);
            if (i == 2 || i == 8) { ldsm_x4_t(ws[1][0], a_ws + (i == 2 ? 2 : 3) * 4096); ldsm_x4_t(ws[1][1], a_ws + (i == 2 ? 2 : 3) * 4096 + 16384); }
            if (i == 4 || i == 10) { ldsm_x4_t(ws[1][2], a_ws + (i == 4 ? 2 : 3) * 4096 + 2048); ldsm_x4_t(ws[1][3], a_ws + (i == 4 ? 2 : 3) * 4096 + 16384 + 2048); }
          }
          const int p = PR[i];
          if (p >= 12) {
            const int z = i != 0;
            mma16816(c[0][0], ws[z][0], b[i & 3][0], b[i & 3][1]); mma16816(c[1][0], ws[z][1], b[i & 3][0], b[i & 3][1]);
            mma16816(c[0][1], ws[z][2], b[i & 3][2], b[i & 3][3]); mma16816(c[1][1], ws[z][3], b[i & 3][2], b[i & 3][3]);
          } else {
            mma16816(c[1][0], aW[1][2 * p], b[i & 3][0], b[i & 3][1]); mma16816(c[1][1], aW[1][2 * p + 1], b[i & 3][2], b[i & 3][3]);
            mma16816(c[0][0], aW[0][2 * p], b[i & 3][0], b[i & 3][1]); mma16816(c[0][1], aW[0][2 * p + 1], b[i & 3][2], b[i & 3][3]);
          }
          if (i == 12) tok = mbar_test(sb + BAR_TOK + 8 * (s & 1), (s >> 1) & 1);
          if (i == 15 && __builtin_expect(!tok, 0)) mbar_wait(sb + BAR_TOK + 8 * (s & 1), (s >> 1) & 1);
          if (i == X_POS + 4 * (1 - WG)) { issue_x_if(sb, &maps.x, s + 1, WG, t16 >= 6144 && more); if (WG) __syncwarp(); }
        }
      }
      sts128f(sb + OFF_PX + WG * 512 + t16, make_float4(c[1][0][0] + c[1][1][0], c[1][0][1] + c[1][1][1], c[1][0][2] + c[1][1][2], c[1][0][3] + c[1][1][3]));
      const float4 own = make_float4(c[0][0][0] + c[0][1][0], c[0][0][1] + c[0][1][1], c[0][0][2] + c[0][1][2], c[0][0][3] + c[0][1][3]);
      NEWZ(1);
      uint32_t a = (J ? OFF_KM : OFF_QM) + WG * 1024 + wq * 256 + (lv >> 2);
      uint32_t ra = rsb + a, ra2 = ra + 128, rx = rsb + BAR_EX + zr;
      PIN(a); PIN(ra); PIN(ra2); PIN(rx);
      const uint32_t kt = sb + OFF_KT + (s & 1) * 8192;
#define k_lane ((lv & 240) + ((lv & 256) << 2))
#define a_lane (((lv & 128) << 1) + ((lv & 256) >> 1) + (lv & 112))
      uint32_t kb[4][4], aq = sb + OFF_QM + a_lane, ak = kt + wq * 256 + k_lane;
      PIN(aq);
      if (WG == 0) PIN(ak);
      SFENCE(16);
      named_bar(3, 256);
      {
        const float4 o = lds128f(sb + OFF_PX + (WG ^ 1) * 512 + t16);
        const uint32_t lo = pack_bf16(own.x + o.x, own.y + o.y), hi = pack_bf16(own.z + o.z, own.w + o.w);
        if (J == 1 && more) { st_async1(ra, lo, rx); st_async1(ra2, hi, rx); }
        sts32(sb + a, lo); sts32(sb + a + 128, hi);
      }
      if (J == 0) {
        uint32_t am[4][4];
        auto load_q = [&]() {
#pragma unroll
          for (int p = 0; p < 4; p++) ldsm_x4_t(am[p], aq + p * 512);
        };
        auto scores = [&]() {
          float c0[2][4], c1[2][4];
#pragma unroll
          for (int i = 0; i < 2; i++) { c0[i][0] = c0[i][1] = c0[i][2] = c0[i][3] = 0.f; c1[i][0] = c1[i][1] = c1[i][2] = c1[i][3] = 0.f; }
#pragma unroll
          for (int p = 0; p < 4; p++) { mma16816(c0[p & 1], am[p], kb[p][0], kb[p][1]); mma16816(c1[p & 1], am[p], kb[p][2], kb[p][3]); }
          const uint32_t r1 = pack_bf16((c0[0][0] + c0[1][0]) + (c1[0][2] + c1[1][2]), (c0[0][1] + c0[1][1]) + (c1[0][3] + c1[1][3]));
          return pack_bf16(bf_lo(r1) * SCALE, bf_hi(r1) * SCALE);
        };
        if (WG == 1) {
          if (last_warp) {
            named_bar(7, 256);
            load_q();
            const uint32_t sa = sb + OFF_S1 + (lv >> 1);
            mbar_wait<0>(sb + BAR_EX, s & 1);
#pragma unroll
            for (int p = 0; p < 4; p++) ldsm_x4_t(kb[p], sb + OFF_KM + p * 512 + l16);
            const uint32_t sm = scores();
            sts64(sa, sm, __float_as_uint(quad_max(fmaxf(bf_lo(sm), bf_hi(sm)))));
            named_bar_arrive(9, 160);
          } else {
            named_bar_arrive(7, 256);
          }
          wait_x();
          load_tmp(1);
        } else {
#pragma unroll
          for (int p = 0; p < 4; p++) ldsm_x4(kb[p], ak + p * 2048);
          named_bar(7, 256);
          load_q();
          const uint32_t omb = lds32(sb + CT_OM);
          const char* pvm = gptr(xhi, lds32(sb + CT_HEAD) + t16 + slot_off(sv) - (lv >> 1) + (am[3][0] & zr)) + xo::VM;
          uint2 vm0 = ld_relaxed2(pvm), vm1 = ld_relaxed2(pvm + 256);
          sts32(sb + OFF_S4 + l16 + wq * 4, scores());
          named_bar(8, 128);
          const uint4 sc = lds128(sb + OFF_S4 + l16);
          uint32_t vb[4][4];
          {
            const uint32_t va = sb + OFF_VT + t16 + (sc.x & zr);
#pragma unroll
            for (int e = 0; e < 4; e++) lds128r(vb[e], va + e * 512);
          }
          float x[8] = {bf_lo(sc.x), bf_hi(sc.x), bf_lo(sc.y), bf_hi(sc.y), bf_lo(sc.z), bf_hi(sc.z), bf_lo(sc.w), bf_hi(sc.w)};
          const float mt = quad_max(fmaxf(fmaxf(fmaxf(x[0], x[1]), fmaxf(x[2], x[3])), fmaxf(fmaxf(x[4], x[5]), fmaxf(x[6], x[7]))));
          const float mtb = mt * L2E;
#pragma unroll
          for (int i = 0; i < 8; i++) x[i] = ex2(fmaf(x[i], L2E, -mtb));
          uint32_t pa[4], pb[4], p5;
          asm volatile("" : "=r"(pa[1]), "=r"(pa[3]), "=r"(pb[1]), "=r"(pb[3]), "=r"(p5));
          pa[0] = pack_bf16(x[0], x[1]); pa[2] = pack_bf16(x[2], x[3]);
          pb[0] = pack_bf16(x[4], x[5]); pb[2] = pack_bf16(x[6], x[7]);
          float st = ((x[0] + x[1]) + (x[2] + x[3])) + ((x[4] + x[5]) + (x[6] + x[7]));
          asm volatile("" : "+r"(pb[0]), "+r"(pb[2]), "+f"(st));
          float oa[4][4];
#pragma unroll
          for (int e = 0; e < 4; e++) { oa[e][0] = oa[e][1] = oa[e][2] = oa[e][3] = 0.f; mma16816(oa[e], pa, vb[e][0], vb[e][1]); }
          SFENCE(25);
          named_bar(9, 160);
          const uint2 sm2 = lds64(sb + OFF_S1 + (lv >> 1));
          const uint32_t sm = sm2.x;
          const float mx = fmaxf(mt, __uint_as_float(sm2.y));
#pragma unroll
          for (int e = 0; e < 4; e++) mma16816(oa[e], pb, vb[e][2], vb[e][3]);
          const float mb = mx * L2E;
          const float e0 = ex2(fmaf(bf_lo(sm), L2E, -mb)), e1 = ex2(fmaf(bf_hi(sm), L2E, -mb)), ct = ex2(mtb - mb);
          const uint32_t xo0 = omb + wq * 512 + l16;
          if (__builtin_expect(warp_incomplete(max(max(vm0.x, vm1.x), __float_as_uint(mx) & zr)), 0)) {
            uint32_t tries = zr;
#pragma unroll 1
            do { vm0 = ld_relaxed2(pvm); vm1 = ld_relaxed2(pvm + 256); } while (warp_incomplete(max(vm0.x, vm1.x)) && ++tries < POLL_LIMIT);
          }
          const float sx = fmaf(ct, st, e0 + e1);
          const float s1 = __shfl_xor_sync(~0u, sx, 1), s2 = __shfl_xor_sync(~0u, sx, 2), s3 = __shfl_xor_sync(~0u, sx, 3);
          const uint32_t p4 = pack_bf16(e0, e1);
#pragma unroll
          for (int e = 0; e < 4; e++) { oa[e][0] *= ct; oa[e][1] *= ct; }
          named_bar_arrive(10 + ((__float_as_uint(oa[3][1]) | p4 | __float_as_uint(s3)) & zr), 256);
          mma1688(oa[0], p4, p5, vm0.x); mma1688(oa[1], p4, p5, vm0.y); mma1688(oa[2], p4, p5, vm1.x); mma1688(oa[3], p4, p5, vm1.y);
          const float rx = rcp((sx + s1) + (s2 + s3));
          st_relaxed4(gptr(xhi, xo0 + slot_off(sv)), pack_bf16(oa[0][0] * rx, oa[0][1] * rx), pack_bf16(oa[1][0] * rx, oa[1][1] * rx),
                      pack_bf16(oa[2][0] * rx, oa[2][1] * rx), pack_bf16(oa[3][0] * rx, oa[3][1] * rx));
          SFENCE(26);
          st_relaxed4(gptr(xhi, xo0 + slot_off(sv + 3)), EMPTY, EMPTY, EMPTY, EMPTY);
          load_tmp(1);
          wait_x();
          no_p();
        }
      } else {
        bool xok;
        {
          const int mt = WG | (wq == 3), ktile = wq == 3 ? 2 + WG : wq - 1;
          const uint32_t qt = sb + OFF_QT + (s & 1) * 8192 + mt * 512 + a_lane;
          uint32_t q[8][4];
          if (__any_sync(0xffffffffu, tv < 2048)) {
            named_bar(7, 256);
#pragma unroll
            for (int p = 0; p < 4; p++) ldsm_x4_t(kb[p], sb + OFF_KM + p * 512 + l16);
          } else {
            named_bar_arrive(7, 256);
#pragma unroll
            for (int p = 0; p < 4; p++) ldsm_x4(kb[p], kt + ktile * 256 + k_lane + p * 2048);
          }
#pragma unroll
          for (int i = 0; i < 8; i++) ldsm_x4(q[i], qt + i * 1024);
          __syncwarp();
          float c0[4][4];
#pragma unroll
          for (int i = 0; i < 4; i++) { c0[i][0] = c0[i][1] = c0[i][2] = c0[i][3] = 0.f; mma16816(c0[i], q[i], kb[i >> 1][(i & 1) * 2], kb[i >> 1][(i & 1) * 2 + 1]); }
#pragma unroll
          for (int i = 0; i < 4; i++) mma16816(c0[i], q[4 + i], kb[2 + (i >> 1)][(i & 1) * 2], kb[2 + (i >> 1)][(i & 1) * 2 + 1]);
          load_tmp(1);
          xok = mbar_test(sb + BAR_X + 8 * WG, n & 1);
          NEWZ(3);
          const uint32_t r0 = pack_bf16((c0[0][0] + c0[1][0]) + (c0[2][0] + c0[3][0]), (c0[0][1] + c0[1][1]) + (c0[2][1] + c0[3][1]));
          const uint32_t r1 = pack_bf16((c0[0][2] + c0[1][2]) + (c0[2][2] + c0[3][2]), (c0[0][3] + c0[1][3]) + (c0[2][3] + c0[3][3]));
          const uint32_t sa = wq == 0 ? sb + OFF_S1 + (lv >> 2) + mt * 256 : sb + OFF_S4 + l16 + mt * 4096 + ktile * 4;
          sts32(sa, pack_bf16(bf_lo(r0) * SCALE, bf_hi(r0) * SCALE));
          sts32(sa + (wq == 0 ? 128 : 2048), pack_bf16(bf_lo(r1) * SCALE, bf_hi(r1) * SCALE));
        }
        if (WG == 1) named_bar_arrive(8, 256);
        else {
          if (more) named_bar_arrive(10, 256);
          named_bar(8, 256);
          const uint4 sc = lds128(sb + OFF_S4 + t16); const uint32_t s1 = lds32(sb + OFF_S1 + wq * 128 + (lv >> 2));
          y[0] = bf_lo(s1); y[1] = bf_hi(s1); y[2] = bf_lo(sc.x); y[3] = bf_hi(sc.x); y[4] = bf_lo(sc.y); y[5] = bf_hi(sc.y);
          y[6] = bf_lo(sc.z); y[7] = bf_hi(sc.z); y[8] = bf_lo(sc.w); y[9] = bf_hi(sc.w);
          const int rel = wq * 8 + (int)(lv >> 6) - (int)((lv >> 3) & 6);
          const float NEG = -999292928.f;
#pragma unroll
          for (int e = 0; e < 4; e++) {
            if (e * 8 > rel) y[2 * e + 2] = NEG;
            if (e * 8 + 1 > rel) y[2 * e + 3] = NEG;
          }
          float my = fmaxf(fmaxf(fmaxf(y[0], y[1]), fmaxf(y[2], y[3])), fmaxf(fmaxf(y[4], y[5]), fmaxf(y[6], y[7])));
          my = quad_max(fmaxf(my, fmaxf(y[8], y[9])));
#pragma unroll
          for (int i = 0; i < 10; i++) y[i] = ex2((y[i] - my) * L2E);
          if (!more) finish_p();
        }
        if (!xok && more) wait_x();
      }
    }
    if (more) {
      float acc[16];
      const uint32_t xph = (s + 1) & 1;
      auto batch = [&](const uint32_t (&a)[24][4], int o) {
        wg_fence();
#pragma unroll
        for (int ks = NTMP; ks < 8; ks++) wgmma_m64n32_ss_ta(acc, wdesc<WG>(o, ks), xdesc<WG>(24 + ks), ks != NTMP);
#pragma unroll
        for (int ks = 0; ks < NTMP; ks++) wgmma_m64n32_rs(acc, tmp[ks], xdesc<WG>(24 + ks), 1);
#pragma unroll
        for (int ks = 0; ks < 24; ks++) wgmma_m64n32_rs(acc, a[ks], xdesc<WG>(ks), 1);
        wg_commit();
        SFENCE(50 + o);
      };
      if (WG == 0) named_bar(12, 256);
      else if (__builtin_expect(s >= 0, 1)) named_bar(10, 256);
      batch(aW[1], 1);
      named_bar_arrive(WG ? 12 : 13, 256);
      if (WG == 0 && s >= 0) {
        NEWZ(7);
        const uint32_t g1 = xh + slot_off(sv + 1);
        if (J == 0) gather_issue(sb + OFF_VT + tv, gptr(xhi, g1) + xo::VT);
        else {
          finish_p();
          st_relaxed4(gptr(xhi, g1) + xo::PT, EMPTY, EMPTY, EMPTY, EMPTY);
          st_relaxed1(gptr(xhi, g1 - lv + (lv >> 2)) + xo::PM, EMPTY);
        }
      }
      wg_wait<0>();
      acc_fence(acc);
      load_tmp(0);
#pragma unroll
      for (int i = 0; i < 4; i++) sts128f(sb + OFF_FP + WG * 8192 + t16 + i * 512, make_float4(acc[4 * i], acc[4 * i + 1], acc[4 * i + 2], acc[4 * i + 3]));
      NEWZ(4);
      uint32_t esrc = 0;
      if (WG == 1) { esrc = xm + t16 - l16 + 2048 + slot_off(sv + 1); tref += lds32(sb + CT_T); }
      named_bar(WG ? 13 : 14, 256);
      batch(aW[0], 0);
      NEWZ(5);
      if (WG == 1) {
        named_bar(14, 256);
        if (last_warp && s + 2 < NSEG) {
          expect_elect(sb + BAR_TOK + 8 * (xph ^ 1), 8192); expect_elect(sb + BAR_X, 32768); expect_elect(sb + BAR_X + 8, 32768);
          if (J == 0) expect_elect(sb + BAR_EX, 2048);
          if (s == NSEG - 3) asm volatile("griddepcontrol.launch_dependents;");
        }
      }
      const uint32_t tb = lds32(sb + CT_TT) + xph * 8192 + WG * 4096 + ((tv + l16) >> 1);
      float4 oth[4];
#pragma unroll
      for (int i = 0; i < 4; i++) oth[i] = lds128f(sb + OFF_FP + (WG ^ 1) * 8192 + t16 + i * 512);
      if (WG == 1 && __builtin_expect(s >= 0, 1)) {
        const uint32_t edst = sb + OFF_MEM + tv + t16 - l16;
        WAIT_UNTIL(tref, aW[0][0], 0, J ? 7 : 0);
        gather_issue<2, 2048>(edst, gptr(xhi, esrc) - 2048);
      }
      wg_wait<0>();
      acc_fence(acc);
      uint32_t lt[4], ht[4];
#pragma unroll
      for (int i = 0; i < 4; i++) {
        const float4 o = oth[i];
        lt[i] = pack_bf16(acc[4 * i] + o.x, acc[4 * i + 1] + o.y); ht[i] = pack_bf16(acc[4 * i + 2] + o.z, acc[4 * i + 3] + o.w);
      }
      stsm_x4_t(tb, lt[0], ht[0], lt[1], ht[1]); stsm_x4_t(tb + 512, lt[2], ht[2], lt[3], ht[3]);
      NEWZ(6);
      if (WG == 0 && last_warp) {
        load_ws();
        named_bar(11, 256);
        fence_async_smem();
        const uint32_t tt = (J ? OFF_KT : OFF_QT) + xph * 8192;
        asm volatile("{.reg .pred p; elect.sync _|p, 0xffffffff;\n"
                     "@p cp.async.bulk.shared::cluster.shared::cta.mbarrier::complete_tx::bytes [%0], [%1], 8192, [%2];}"
                     ::"r"(rsb + tt), "r"(sb + tt), "r"(rsb + BAR_TOK + 8 * xph) : "memory");
      } else {
        named_bar_arrive(11, 256);
        load_ws();
      }
    }
    if (!more) break;
    if (__builtin_expect(s < 0, 0)) {
      tref = gtime() / T_SLIP * T_SLIP - T_SLIP;
    }
  }
  cp_async_wait_group<0>();
  if (J == 0) mbar_wait(sb + BAR_TOK + 8, 1);
}

__device__ __forceinline__ constexpr bool o_fixed(int i) { return 2 * (7 - (i & 7)) + (i < 8) < O_FIX; }
template <int WG>
__device__ __forceinline__ void role_v(const ChainMaps& maps, const bf16* __restrict__ mem0, const uint32_t sb, const uint32_t xbase_hi) {
  using namespace chain;
  const int h = blockIdx.x >> 2;
  const uint32_t u16 = (threadIdx.x & 96) * 64 + (threadIdx.x & 31) * 16;
  const uint32_t t16 = keep(u16), l16 = keep((threadIdx.x & 31) * 16);
  const uint32_t xhi = keep(xbase_hi + (t16 >> 16));
#define j (sb >> 24)
  auto wv_addr = [&](uint32_t t) { return WG * 32768 + ((t & 256) << 2) + ((t & 112) << 3) + ((((t >> 6) & 96) + ((t >> 3) & 16)) ^ (t & 112)); };
  auto wo_addr = [&](uint32_t t) { return OFF_WOR + WG * 32768 + ((t & 6144) << 2) + ((t & 256) << 1) + ((t & 112) << 2) + ((((j ^ 1) << 5) + ((t >> 3) & 16)) ^ ((t >> 1) & 48)); };
#define ovt (((tv + l16) >> 1) + (xo::VT + WG * 512 + j * 4096))
#define ovm (((tv & 4096) >> 1) + ((tv & 2048) >> 3) + (lv >> 1) + (xo::VM + j * 4096))
#define xvt (lds32(sb + CT_HEAD) + ovt)
#define xvm (lds32(sb + CT_HEAD) + ovm)
#define xom (lds32(sb + CT_OM) + t16 + WG * 8192)
#define warp_is(q) __any_sync(0xffffffffu, (tv >> 11) == (q))
#define upper_warps (WG == 1 || __any_sync(0xffffffffu, tv >= 4096))

  uint32_t aV[16][4];
  uint32_t aO[16][4];
  uint32_t bO[16][4];
  uint32_t rot[16][4];
  if (WG == 1 && __any_sync(0xffffffffu, t16 >= 6144)) {
    expect_elect(sb + BAR_X, 32768); expect_elect(sb + BAR_X + 8, 32768);
    issue_x(sb, &maps.x, 0, 0); issue_x(sb, &maps.x, 0, 1);
    prefetch_l2(maps.xp + 65536 + (h * 2 + j) * 3072, 3072);
  }
  cluster_arrive();
  { uint2 m0[8]; load_mem0(m0, mem0); store_mem0(sb, m0); }
  mbar_wait(sb + BAR_P, 0);
#pragma unroll
  for (int ks = 0; ks < 16; ks++) ldsm_x4_t(aV[ks], sb + wv_addr(t16) + OFF_WOR + ks * 2048);
  auto load_v = [&](uint32_t t) {
#pragma unroll
    for (int ks = 0; ks < 16; ks++) ldsm_x4_t(rot[ks], sb + wv_addr(t) + OFF_WVR + ks * 2048);
  };
  load_v(t16);
  named_bar(0, 256);
  if (threadIdx.x == 0) {
    fence_async_smem();
    mbar_expect_tx(sb + BAR_P + 8, 4 * 16384);
    for (int q = 0; q < 4; q++) tma_load_2d(sb + OFF_WOR + q * 16384, &maps.wo, h * 32, j * 2048 + q * 256, sb + BAR_P + 8);
    for (int q = 0; q < 4; q++) tma_prefetch_2d(&maps.wo, h * 32, j * 2048 + 1024 + q * 256);
  }
  __syncwarp();
  cluster_wait();
  const uint32_t rsb = sb ^ RANK_BIT;

  uint32_t tref = 0;
#pragma unroll 1
  for (int n = 0; n <= NSEG; n++) {
    const bool more = __builtin_expect(s + 1 < NSEG, 1);
    uint32_t zr = loop_zero<0>(n);
    bool xok = false;
    if (__builtin_expect(s >= 0, 1)) {
      if (__builtin_expect(s > 0, 1)) {
        const uint32_t dst = sb + OFF_MEM + WG * 8192 + t16 + ((lv >> 5) & 12);
        uint32_t tries = zr;
#pragma unroll 1
        do {
          if (tries) { const char* src = gptr(xhi, xm + WG * 8192 + slot_off(sv)); tref += T_SLIP; WAIT_UNTIL(tref, aV[0], 1, -1); gather_issue(sb + OFF_MEM + WG * 8192 + tv, src); }
          KEEPALIVE(aV[0], zr);
          cp_async_wait_group<0>();
        } while (gather_incomplete<1, 0>(dst) && ++tries < POLL_LIMIT);
        named_bar(1 + WG, 128);
      }
      const uint32_t a_mem = sb + OFF_MEM + WG * 8192 + l16;
      float c[2][4];
      c[0][0] = c[0][1] = c[0][2] = c[0][3] = c[1][0] = c[1][1] = c[1][2] = c[1][3] = 0.f;
      constexpr int NBUF = (48 - 8 - 4 * O_FIX) / 4;
      uint32_t b[NBUF][4];
#pragma unroll
      for (int p = 0; p < NBUF - 1; p++) ldsm_x4_t(b[p], a_mem + p * 512);
#pragma unroll
      for (int p = 0; p < 16; p++) {
        if (p + NBUF - 1 < 16) ldsm_x4_t(b[(p + NBUF - 1) % NBUF], a_mem + (p + NBUF - 1) * 512);
        if (p < 8) { mma16816(c[0], aV[2 * p], b[p % NBUF][0], b[p % NBUF][1]); mma16816(c[1], aV[2 * p + 1], b[p % NBUF][2], b[p % NBUF][3]); }
        else { mma16816(c[0], rot[2 * p - 16], b[p % NBUF][0], b[p % NBUF][1]); mma16816(c[1], rot[2 * p - 15], b[p % NBUF][2], b[p % NBUF][3]); }
      }
      xok = mbar_test(sb + BAR_X + 8 * WG, n & 1);
      SFENCE(15);
      const float4 own = make_float4(c[0][0] + c[1][0], c[0][1] + c[1][1], c[0][2] + c[1][2], c[0][3] + c[1][3]);
      NEWZ(1);
      const uint32_t pvm = WG == 0 ? xvm + slot_off(sv) : 0;
      if (WG == 1) sts128f(sb + OFF_VPX + wq * 512 + l16, own);
      named_bar(3, 256);
      if (WG == 0) {
        const float4 o = lds128f(sb + OFF_VPX + wq * 512 + l16);
        st_relaxed2(gptr(xhi, pvm), pack_bf16(own.x + o.x, own.y + o.y), pack_bf16(own.z + o.z, own.w + o.w));
      }
    }
    auto stage = [&](uint32_t o) { return sb + OFF_MEM + o; };
    auto stage_pv = [&](int seg) {
      const uint32_t o = WG ? ovt - 512 : tv + 512, dst = stage(o);
      const char* src = gptr(xhi, lds32(sb + CT_HEAD) + slot_off(seg) + o);
#pragma unroll
      for (int i = 0; i < 3 - WG; i++) cp_async16(dst + i * 512, src + i * 512);
    };
    auto token_pv = [&](int seg, bool staged) {
      constexpr int NU = 2 - WG;
      uint4 pt0, pt1, v0[NU], v1[NU]; uint32_t pm0, pm1; uint2 vm[NU];
      const uint32_t ap = l16 + WG * 4096 + xo::PT, am = (lv >> 2) + WG * 4096 + xo::PM;
      const uint32_t at = ovt - WG * 512;
      if (staged) {
        constexpr int BS = 2048;
        const uint32_t sp = stage(ap), sm = stage(am), st = stage(at), sv2 = stage(ovm);
        pt0 = lds128(sp); pt1 = lds128(sp + BS); pm0 = lds32(sm); pm1 = lds32(sm + BS);
#pragma unroll
        for (int u = 0; u < NU; u++) { v0[u] = lds128(st - u * BS); v1[u] = lds128(st + 512 - u * BS); vm[u] = lds64(sv2 - u * BS); }
      } else {
        const uint32_t b = lds32(sb + CT_HEAD) + slot_off(seg);
        pt0.x = EMPTY;
#pragma unroll
        for (int u = 0; u < NU; u++) {
          v0[u] = ld_relaxed4(gptr(xhi, b + at) - u * 2048); v1[u] = ld_relaxed4(gptr(xhi, b + at) + 512 - u * 2048);
          vm[u] = ld_relaxed2(gptr(xhi, b + ovm) - u * 2048);
        }
      }
      const bool odd = lv & 16;
      char* op = gptr(xhi, lds32(sb + CT_O) + (seg * SEG + WG * 16 + (lv >> 6)) * (HD * 2) + wq * 32 + (lv & 16) + ((lv >> 2) & 8));
      if (!staged || __builtin_expect(warp_incomplete(umax4(pt0.x, pt1.x, pm0, pm1)), 0)) {
        const uint32_t b = lds32(sb + CT_HEAD) + slot_off(seg);
        uint32_t tries = zr;
#pragma unroll 1
        do {
          pt0 = ld_relaxed4(gptr(xhi, b + ap)); pt1 = ld_relaxed4(gptr(xhi, b + ap) + 2048);
          pm0 = ld_relaxed1(gptr(xhi, b + am)); pm1 = ld_relaxed1(gptr(xhi, b + am) + 2048);
        } while (warp_incomplete(umax4(pt0.x, pt1.x, pm0, pm1)) && ++tries < POLL_LIMIT);
      }
      const uint32_t pa[4] = {pt0.x, pt1.x, pt0.y, pt1.y}, pb[4] = {pt0.z, pt1.z, pt0.w, pt1.w};
#pragma unroll
      for (int u = 0; u < NU; u++) {
        float o0[4] = {0.f, 0.f, 0.f, 0.f}, o1[4] = {0.f, 0.f, 0.f, 0.f};
        mma1688(o0, pm0, pm1, vm[u].x); mma1688(o1, pm0, pm1, vm[u].y);
        mma16816(o0, pa, v0[u].x, v0[u].y); mma16816(o1, pa, v1[u].x, v1[u].y);
        if (WG) { mma16816(o0, pb, v0[u].z, v0[u].w); mma16816(o1, pb, v1[u].z, v1[u].w); }
#pragma unroll
        for (int r = 0; r < 2; r++) {
          const uint32_t w0 = pack_bf16(o0[2 * r], o0[2 * r + 1]), w1 = pack_bf16(o1[2 * r], o1[2 * r + 1]);
          const uint32_t rv = __shfl_xor_sync(~0u, odd ? w0 : w1, 1);
          asm volatile("st.global.v2.u32 [%0], {%1, %2};" ::"l"(op + r * 8 * HD * 2 - u * 64), "r"(odd ? rv : w0), "r"(odd ? w1 : rv) : "memory");
        }
      }
    };
    if (!more) {
      named_bar(3, 256);
      if (upper_warps) {
#pragma unroll 1
        for (int seg = NSEG - 2; seg < NSEG; seg++) token_pv(seg, false);
      }
      break;
    }
    {
      if (__builtin_expect(s > 0, 1)) { stage_pv(sv - 1); cp_async_commit(); }
      bool xw;
      {
        float acc[16];
        if (__builtin_expect(!xok, 0)) mbar_wait<0>(sb + BAR_X + 8 * WG, (s + 1) & 1);
        wg_fence();
#pragma unroll
        for (int ks = 0; ks < 16; ks++) wgmma_m64n32_rs(acc, rot[ks], xdesc<WG>(16 + ks), ks != 0);
        wg_commit();
#pragma unroll
        for (int ks = 0; ks < 16; ks++) wgmma_m64n32_rs(acc, aV[ks], xdesc<WG>(ks), 1);
        wg_commit();
        SFENCE(50);
        NEWZ(2);
        xw = warp_is(3) && s + 2 < NSEG;
        tref += lds32(sb + CT_T + 4) + WG * T_LAG - T_SLIP;
        const uint32_t pvt = xvt + slot_off(sv + 1), awo = sb + wo_addr(tv);
        if (WG == 0 && warp_is(1) && s >= 0) expect_elect(sb + BAR_EX, 4096);
        if (xw) {
          expect_elect(sb + BAR_X + 8 * WG, 32768);
          if (WG == 1 && s == NSEG - 3) asm volatile("griddepcontrol.launch_dependents;");
          if (WG == 1 && s + 5 < NSEG) prefetch_l2(maps.xp + (s + 5) * 65536 + lds32(sb + CT_PF), 1024);
        }
        wg_wait<1>();
        if (xw) issue_x(sb, &maps.xq, s + 2, WG, 1);
        if (__builtin_expect(s == 0, 0)) {
          mbar_wait(sb + BAR_P + 16, 0);
#pragma unroll
          for (int ks = 0; ks < 16; ks++) if (o_fixed(ks)) ldsm_x4_t(bO[ks], (ks < 8 ? awo : awo ^ 32) + (ks & 7) * 1024);
        }
#pragma unroll
        for (int ks = 0; ks < 16; ks++) if (!o_fixed(ks)) ldsm_x4_t(bO[ks], (ks < 8 ? awo : awo ^ 32) + (ks & 7) * 1024);
        wg_wait<0>();
        acc_fence(acc);
        constexpr int K = WG * 2, G = 2 - K;
        sts128f(sb + OFF_RED + WG * 1024 + t16, make_float4(acc[G], acc[G + 1], acc[4 + G], acc[5 + G]));
        sts128f(sb + OFF_RED + WG * 1024 + 512 + t16, make_float4(acc[8 + G], acc[9 + G], acc[12 + G], acc[13 + G]));
        cp_async_wait_group<0>();
        named_bar(3, 256);
        const float4 o0 = lds128f(sb + OFF_RED + (WG ^ 1) * 1024 + t16), o1 = lds128f(sb + OFF_RED + (WG ^ 1) * 1024 + 512 + t16);
        st_relaxed4(gptr(xhi, pvt),
                    pack_bf16(acc[K] + o0.x, acc[K + 1] + o0.y), pack_bf16(acc[4 + K] + o0.z, acc[5 + K] + o0.w),
                    pack_bf16(acc[8 + K] + o1.x, acc[9 + K] + o1.y), pack_bf16(acc[12 + K] + o1.z, acc[13 + K] + o1.w));
      }
      if (__builtin_expect(s >= 0, 1)) {
        uint32_t tries = 0;
#pragma unroll
        for (int ks = 0; ks < 16; ks++) if (!o_fixed(ks)) tries |= bO[ks][0];
        const char* po = gptr(xhi, xom + slot_off(sv) + (tries & zr));
        tries = zr;
        float d[2][2][4];
        uint32_t mx;
#pragma unroll 1
        do {
          tref += T_SLIP;
          WAIT_UNTIL(tref, aV[0], 1, 1);
          uint4 o[8];
#pragma unroll
          for (int i = 0; i < 4; i++) o[i] = ld_relaxed4(po + i * 512);
#pragma unroll
          for (int i = 0; i < 4; i++) o[4 + i] = ld_relaxed4(po + 16384 + i * 512);
          __syncwarp();
#pragma unroll
          for (int i = 0; i < 2; i++)
#pragma unroll
            for (int q = 0; q < 2; q++) { d[i][q][0] = d[i][q][1] = d[i][q][2] = d[i][q][3] = 0.f; }
#pragma unroll
          for (int i = 0; i < 4; i++) {
            mma16816(d[0][0], aO[2 * i], o[i].x, o[i].y); mma16816(d[1][0], aO[8 + 2 * i], o[i].x, o[i].y);
            mma16816(d[0][1], aO[2 * i + 1], o[i].z, o[i].w); mma16816(d[1][1], aO[9 + 2 * i], o[i].z, o[i].w);
          }
          mx = umax4(o[0].w, o[1].w, o[2].w, o[3].w);
          SFENCE(33 + tries);
#pragma unroll
          for (int i = 0; i < 4; i++) {
            mma16816(d[0][0], bO[2 * i], o[4 + i].x, o[4 + i].y); mma16816(d[1][0], bO[8 + 2 * i], o[4 + i].x, o[4 + i].y);
            mma16816(d[0][1], bO[2 * i + 1], o[4 + i].z, o[4 + i].w); mma16816(d[1][1], bO[9 + 2 * i], o[4 + i].z, o[4 + i].w);
          }
          mx = max(mx, umax4(o[4].w, o[5].w, o[6].w, o[7].w));
        } while (warp_incomplete(mx) && ++tries < POLL_LIMIT);
        NEWZ(3);
        {
          const uint32_t rr = rsb + (WG ? OFF_RX1 : OFF_RX) + wq * 512 + (lv >> 1);
          st_async2(rr, __float_as_uint(d[0][0][0] + d[0][1][0]), __float_as_uint(d[0][0][1] + d[0][1][1]), rsb + BAR_EX);
          st_async2(rr + 256, __float_as_uint(d[0][0][2] + d[0][1][2]), __float_as_uint(d[0][0][3] + d[0][1][3]), rsb + BAR_EX);
          const uint32_t rd = sb + OFF_RED + (WG ^ 1) * 1024 + t16 - (lv >> 1);
          sts64(rd, __float_as_uint(d[1][0][0] + d[1][1][0]), __float_as_uint(d[1][0][1] + d[1][1][1]));
          sts64(rd + 256, __float_as_uint(d[1][0][2] + d[1][1][2]), __float_as_uint(d[1][0][3] + d[1][1][3]));
        }
        if (upper_warps) {
          named_bar_arrive(7, 256);
          if (xw) issue_x(sb, &maps.xq, s + 2, WG, 0);
          if (__builtin_expect(s > 0, 1)) token_pv(sv - 1, true);
        } else {
          const uint32_t mp = lds32(sb + CT_MP) + (lv >> 2) + wq * 128, ra = sb + wq * 256 + (lv >> 1);
          char* pp = gptr(xhi, mp + slot_off(sv + 1));
          named_bar(7, 256);
          uint2 p[8];
#pragma unroll
          for (int i = 0; i < 8; i++) p[i] = lds64(ra + OFF_RED + i * 1024);
#define SUM8(c) (((__uint_as_float(p[0].c) + __uint_as_float(p[1].c)) + (__uint_as_float(p[2].c) + __uint_as_float(p[3].c))) + \
                 ((__uint_as_float(p[4].c) + __uint_as_float(p[5].c)) + (__uint_as_float(p[6].c) + __uint_as_float(p[7].c))))
          const float r0 = SUM8(x), r1 = SUM8(y);
          mbar_wait(sb + BAR_EX, s & 1);
#pragma unroll
          for (int i = 0; i < 8; i++) p[i] = lds64(ra + (i < 4 ? OFF_RX : OFF_RX1) + (i & 3) * 512);
          st_relaxed1(pp, pack_bf16(r0 + SUM8(x), r1 + SUM8(y)));
          st_relaxed1(gptr(xhi, mp + slot_off(sv + 3)), EMPTY);
        }
        NEWZ(4);
        const char* src = gptr(xhi, xm + WG * 8192 + slot_off(sv + 1));
        const uint32_t awv = sb + wv_addr(tv) + OFF_WVR;
        tref += lds32(sb + CT_T + 8) - WG * T_LAG;
        named_bar(8, 256);
#pragma unroll
        for (int ks = 0; ks < V_PRE; ks++) ldsm_x4_t(rot[ks], awv + ks * 2048);
        WAIT_UNTIL(tref, aV[0], 1, 2);
        gather_issue(sb + OFF_MEM + WG * 8192 + tv, src);
#pragma unroll
        for (int ks = V_PRE; ks < 16; ks++) ldsm_x4_t(rot[ks], awv + ks * 2048);
        NEWZ(6);
        st_relaxed4(gptr(xhi, xvt + slot_off(sv + 2)), EMPTY, EMPTY, EMPTY, EMPTY);
        if (WG == 0) st_relaxed2(gptr(xhi, xvm + slot_off(sv + 2)), EMPTY, EMPTY);
      } else {
        load_v(tv);
        if (xw) issue_x(sb, &maps.xq, s + 2, WG, 0);
        mbar_wait(sb + BAR_P + 8, 0);
#pragma unroll
        for (int ks = 0; ks < 8; ks++) { ldsm_x4_t(aO[ks], sb + wo_addr(tv) + ks * 1024); ldsm_x4_t(aO[8 + ks], sb + (wo_addr(tv) ^ 32) + ks * 1024); }
        named_bar(0, 256);
        if (threadIdx.x == 0) {
          fence_async_smem();
          mbar_expect_tx(sb + BAR_P + 16, 4 * 16384);
          for (int q = 0; q < 4; q++) tma_load_2d(sb + OFF_WOR + q * 16384, &maps.wo, h * 32, j * 2048 + 1024 + q * 256, sb + BAR_P + 16);
        }
        __syncwarp();
        tref = gtime() / T_SLIP * T_SLIP - T_SLIP;
      }
    }
  }
}

#undef j
#undef s
#undef sv
#undef xm
#undef wq

__global__ void __launch_bounds__(256, 1) __cluster_dims__(2, 1, 1)
chain_kernel(const __grid_constant__ ChainMaps maps, const bf16* __restrict__ mem0, const uint64_t xbase) {
  using namespace chain;
  extern __shared__ uint8_t smem_raw[];
  uint32_t sb = smem_u32(smem_raw);
  PIN(sb);
  if (sb != SB_LO + (blockIdx.x & 1) * RANK_BIT || mapa(sb, (blockIdx.x & 1) ^ 1) != (sb ^ RANK_BIT)) __trap();
  const int tid = threadIdx.x;
  const int h = blockIdx.x >> 2, role = (blockIdx.x >> 1) & 1, j = blockIdx.x & 1;
  if (tid == 0) {
    for (int i = 0; i < 9; i++) mbar_init(sb + OFF_BAR + 8 * i, 1);
    asm volatile("fence.mbarrier_init.release.cluster;" ::: "memory");
    const uint32_t xl = (uint32_t)xbase;
    sts32(sb + CT_BASE, xl); sts32(sb + CT_HEAD, xl + h * xo::HEAD); sts32(sb + CT_OM, xl + xo::OM + (role ? j * 32768 : h * 2048));
    sts32(sb + CT_MP, xl + xo::MEM + (h * 2 + j) * 256); sts32(sb + CT_O, xl + xo::O + (h * 2 + j) * 128); sts32(sb + CT_PF, (h * 2 + j) * 1024);
    sts32(sb + CT_TT, sb + (j ? OFF_KT : OFF_QT));
    if (role == 0) {
      const CUtensorMap* wm = j ? &maps.wk : &maps.wq;
      mbar_expect_tx(sb + BAR_P, 6 * 16384);
      for (int c = 0; c < 3; c++)
        for (int q = 0; q < 2; q++) tma_load_2d(sb + OFF_X + (q * 3 + c) * 16384, wm, h * DH + q * 64, q * 512 + c * 128, sb + BAR_P);
      mbar_expect_tx(sb + BAR_P + 8, 4 * 16384);
      for (int c = 0; c < 2; c++)
        for (int q = 0; q < 2; q++) tma_load_2d(sb + OFF_X + (6 + q * 2 + c) * 16384, wm, h * DH + (q ^ 1) * 64, q * 512 + c * 128, sb + BAR_P + 8);
      mbar_expect_tx(sb + BAR_P + 24, 4 * 16384);
      for (int q = 0; q < 2; q++)
        for (int o = 0; o < 2; o++) tma_load_2d(sb + OFF_WS + (q * 2 + o) * 16384, wm, h * DH + (q ^ o) * 64, q * 512 + 384, sb + BAR_P + 24);
      for (int q = 0; q < 2; q++) tma_prefetch_2d(wm, h * DH + (q ^ 1) * 64, q * 512 + 256);
    } else {
      mbar_expect_tx(sb + BAR_P, 8 * 16384);
      for (int q = 0; q < 4; q++) tma_load_2d(sb + OFF_WOR + q * 16384, &maps.wv, h * DH + j * 64, (q >> 1) * 512 + (q & 1) * 128, sb + BAR_P);
      for (int q = 0; q < 4; q++) tma_load_2d(sb + OFF_WVR + q * 16384, &maps.wv, h * DH + j * 64, (q >> 1) * 512 + 256 + (q & 1) * 128, sb + BAR_P);
    }
  }
  for (int r = 0; r < RING; r++) {
    char* p = (char*)xbase + r * xo::SLOT;
    const int wq = (tid >> 5) & 3;
    if (role == 1) st_relaxed4(p + h * xo::HEAD + xo::VT + (8 * j + 2 * wq + (tid >> 7)) * 512 + (tid & 31) * 16, EMPTY, EMPTY, EMPTY, EMPTY);
    else if (j == 0) st_relaxed4(p + (tid < 128 ? xo::OM + h * 2048 + tid * 16 : h * xo::HEAD + wq * 2048 + xo::VM + (tid & 31) * 16), EMPTY, EMPTY, EMPTY, EMPTY);
    else {
      st_relaxed4(p + h * xo::HEAD + (tid >> 6) * 2048 + 1024 + (tid & 63) * 16, EMPTY, EMPTY, EMPTY, EMPTY);
      if (tid < 32) st_relaxed4(p + xo::MEM + h * 512 + tid * 16, EMPTY, EMPTY, EMPTY, EMPTY);
    }
  }
  __syncthreads();
  if (__shfl_sync(0xffffffffu, tid >> 5, 0) == 0) {
    uint32_t t[2], c[2], ka[4] = {0, 0, 0, 0};
    const uint32_t z = maps.t_step >> 24;
#pragma unroll
    for (int i = 0; i < 2; i++) {
      const uint32_t end = (gtime() & ~31u) + (i ? 2048 : 1024);
      for (int g = z; g < 256 && (int)(gtime() - (end - 96)) < 0; g++) KEEPALIVE(ka, z);
      for (int g = z; g < 256 && (int)((t[i] = gtime()) - end) < 0; g++) {}
      c[i] = (uint32_t)clock64();
    }
    uint32_t v = 0, target = 0;
    if (tid == 0) {
      st_relaxed1(&g_rate[blockIdx.x], (t[1] - t[0]) * 4096u / (c[1] - c[0]));
      __threadfence();
      target = (atomicAdd(&g_epoch, 1u) & ~127u) + 128u;
    }
    target = __shfl_sync(0xffffffffu, target, 0);
    int guard = 0;
    do { asm volatile("ld.acquire.gpu.global.u32 %0, [%1];" : "=r"(v) : "l"(&g_epoch) : "memory"); }
    while (__any_sync(0xffffffffu, (int)(v - target) < 0) && ++guard < (1 << 20));
    const uint4 r4 = ld_relaxed4(&g_rate[tid * 4]);
    uint32_t r = min(__reduce_max_sync(0xffffffffu, umax4(r4.x, r4.y, r4.z, r4.w)), 4 * RATE0);
    if (r < RATE0 + 28) r = RATE0;
    const uint32_t a = (maps.t_step * r / RATE0 + 31) & ~31u, b = (maps.t_phase * r / RATE0 + 31) & ~31u;
    sts128(sb + CT_T, make_uint4(a, b, a - b, r));
  }
  const uint32_t xhi = (uint32_t)(xbase >> 32);
  const int wg = __shfl_sync(0xffffffffu, tid >> 7, 0);
  if (role == 0) {
    if (wg == 0) role_a<0>(maps, mem0, sb, xhi); else role_a<1>(maps, mem0, sb, xhi);
  } else {
    if (wg == 0) role_v<0>(maps, mem0, sb, xhi); else role_v<1>(maps, mem0, sb, xhi);
  }
  __syncwarp();
  cluster_arrive();
  cluster_wait();
}

struct BMaps {
  CUtensorMap q, k, v, out, k8;
  const bf16 *shift_k, *ssm_k, *ssm_D;
};

#define B_SLEEP 200
namespace bp {
constexpr int U_PITCH = (2048 + 128) * 2 + 16;
constexpr int KR_WORDS = 1048;
constexpr int KR_PITCH = 8704;
constexpr int OFF_U = 0;
constexpr int OFF_KR = (8 * U_PITCH + 127) / 128 * 128;
constexpr int Q_OFF = 4352;
constexpr int OFF_BAR = OFF_KR + 8 * KR_PITCH;
constexpr int GROUP_BYTES = OFF_BAR + 128;
constexpr int SMEM = 2 * GROUP_BYTES + 128;
constexpr int NTASK = DM / 8;
static_assert(Q_OFF >= 4224 && Q_OFF + 4096 <= KR_PITCH, "staging does not fit");
}

__device__ __forceinline__ uint32_t bmul2(uint32_t a, uint32_t b) { uint32_t r; asm("mul.rn.bf16x2 %0, %1, %2;" : "=r"(r) : "r"(a), "r"(b)); return r; }
__device__ __forceinline__ uint32_t badd2(uint32_t a, uint32_t b) { uint32_t r; asm("add.rn.bf16x2 %0, %1, %2;" : "=r"(r) : "r"(a), "r"(b)); return r; }

__device__ __forceinline__ void mbar_wait_sleep(uint32_t bar, uint32_t parity) {
  int guard = 0;
  while (!mbar_try(bar, parity)) { __nanosleep(B_SLEEP); if (++guard > (1 << 22)) __trap(); }
}

__device__ __forceinline__ void bpart_body(const BMaps& maps, int first, int stride, int end) {
  using namespace bp;
  extern __shared__ uint8_t smem_all[];
  const int grp = __shfl_sync(0xffffffffu, threadIdx.x >> 8, 0);
  const int lane = keep(threadIdx.x & 31), g = lane >> 2, t = lane & 3;
  const int w = __shfl_sync(0xffffffffu, (threadIdx.x >> 5) & 7, 0);
  const uint32_t sb = ((smem_u32(smem_all) + 127) & ~127u) + grp * GROUP_BYTES;
  const uint32_t kr = sb + OFF_KR + w * KR_PITCH, bar_k = sb + OFF_BAR + 8 * w, bar_q = bar_k + 64;
  if (lane == 0) { mbar_init(bar_k, 1); mbar_init(bar_q, 1); asm volatile("fence.mbarrier_init.release.cluster;" ::: "memory"); }
  if (lane < 16) sts128(sb + OFF_U + w * U_PITCH + lane * 16, make_uint4(0, 0, 0, 0));
  __syncwarp();
  if (grp == 1) { named_bar_arrive(3, 512); named_bar(5, 512); }
  const int lm = lane >> 3, lr = lane & 7;
  uint32_t ph = 0;
  for (int task = first + grp; task < end; task += stride, ph ^= 1) {
    const int d0 = task * 8;
    uint4 x[8];
    {
      const uint4* kf = (const uint4*)(maps.ssm_k + (size_t)(d0 + w) * S_LEN);
#pragma unroll
      for (int it = 0; it < 8; it++) x[it] = __ldg(kf + it * 32 + lane);
    }
    const uint4 ska = __ldg((const uint4*)(maps.shift_k + (d0 + 2 * t) * 4));
    __syncwarp();
    if (lane == 0) {
      mbar_expect_tx(bar_k, 2 * 4096 + 128);
      tma_load_2d(kr + 4096, &maps.k8, d0, w * 256 + 248, bar_k);
      tma_load_2d(kr, &maps.k, d0, w * 256 - 8, bar_k);
      bulk_wait_read<0>();
      tma_load_2d(kr + Q_OFF, &maps.v, d0, w * 256, bar_k);
    }
    __syncwarp();
    if (task == first) named_bar_arrive(5, 512);
    const uint32_t sk[4] = {__byte_perm(ska.x, ska.z, 0x5410), __byte_perm(ska.x, ska.z, 0x7632), __byte_perm(ska.y, ska.w, 0x5410), __byte_perm(ska.y, ska.w, 0x7632)};
    mbar_wait_sleep(bar_k, ph);
    {
      const uint32_t ka = kr + (lane + 8) * 16;
#pragma unroll
      for (int i = 0; i < 8; i++) {
        uint32_t k0[4], k1[4], k2[4], k3[4], v[4], r[4];
        ldsm_x4(k3, ka + i * 512 - 48); ldsm_x4(k2, ka + i * 512 - 32); ldsm_x4(k1, ka + i * 512 - 16); ldsm_x4(k0, ka + i * 512);
        ldsm_x4(v, ka + (Q_OFF - 128) + i * 512);
#pragma unroll
        for (int b = 0; b < 4; b++) {
          uint32_t acc = bmul2(k3[b], sk[3]);
          acc = badd2(acc, bmul2(k2[b], sk[2]));
          acc = badd2(acc, bmul2(k1[b], sk[1]));
          acc = badd2(acc, bmul2(k0[b], sk[0]));
          r[b] = bmul2(acc, v[b]);
        }
        const int ch = 16 + w * 32 + i * 4 + lm;
        stsm_x4_t(sb + OFF_U + lr * U_PITCH + ((ch ^ ((ch >> 3) & 1)) << 4), r[0], r[1], r[2], r[3]);
      }
    }
    __syncwarp();
    {
      const uint32_t c0 = kr, c1 = c0 + (KR_WORDS + 16) * 4;
      uint32_t carry = 0;
#pragma unroll
      for (int it = 0; it < 8; it++) {
        const int blk = it * 32 + lane;
        uint32_t prev = __shfl_up_sync(0xffffffffu, x[it].w, 1);
        if (lane == 0) prev = carry;
        carry = __shfl_sync(0xffffffffu, x[it].w, 31);
        sts128(c0 + (1028 - 4 * blk) * 4, make_uint4(__byte_perm(x[it].w, 0, 0x1032), __byte_perm(x[it].z, 0, 0x1032),
                                                     __byte_perm(x[it].y, 0, 0x1032), __byte_perm(x[it].x, 0, 0x1032)));
        sts128(c1 + (1028 - 4 * blk) * 4, make_uint4(__byte_perm(x[it].w, x[it].z, 0x7610), __byte_perm(x[it].z, x[it].y, 0x7610),
                                                     __byte_perm(x[it].y, x[it].x, 0x7610), __byte_perm(x[it].x, prev, 0x7610)));
      }
      if (lane < 4) { sts128(c0 + (1032 + 4 * lane) * 4, make_uint4(0, 0, 0, 0)); sts128(c1 + (1032 + 4 * lane) * 4, make_uint4(0, 0, 0, 0)); }
      __syncwarp();
    }
    named_bar(3 + grp, 512);
    float acc[16][4];
#pragma unroll
    for (int jn = 0; jn < 16; jn++) { acc[jn][0] = acc[jn][1] = acc[jn][2] = acc[jn][3] = 0.f; }
    {
      const uint32_t ub = sb + OFF_U + w * U_PITCH;
      uint32_t kd = kr + (((g & 1) ? 0 : KR_WORDS + 16) + ((((g & 1) ? 2063 : 2062) - (g - 2 * t)) >> 1)) * 4;
      uint32_t uc = 2 * (8 + lr + (lm >> 1) * 8) + (lm & 1);
#pragma unroll 1
      for (int d0s = 0; d0s < 8; d0s++, kd -= 32, uc -= 2) {
        const uint32_t uf = ub + ((uc ^ ((uc >> 3) & 1)) << 4);
        uint32_t A[3][4];
        A[0][0] = lds32v(kd); A[0][1] = lds32v(kd - 16); A[0][2] = lds32v(kd + 16); A[0][3] = lds32v(kd);
        uint32_t F[8][4];
#pragma unroll
        for (int m = 7; m >= 0; m--) ldsm_x4(F[m], uf + m * 512);
#pragma unroll
        for (int i = 0; i < 16; i++) {
          if (i + 1 < 16) {
            A[(i + 1) % 3][0] = lds32v(kd - 256 * (i + 1)); A[(i + 1) % 3][1] = lds32v(kd - 256 * (i + 1) - 16);
            A[(i + 1) % 3][2] = lds32v(kd - 256 * (i + 1) + 16); A[(i + 1) % 3][3] = lds32v(kd - 256 * (i + 1));
          }
#pragma unroll
          for (int jn = 15; jn >= i; jn--) mma16816(acc[jn], A[i % 3], F[(jn - i) >> 1][((jn - i) & 1) * 2], F[(jn - i) >> 1][((jn - i) & 1) * 2 + 1]);
        }
      }
    }
    named_bar_arrive(3 + (grp ^ 1), 512);
    __syncwarp();
    fence_async_smem();
    __syncwarp();
    if (lane == 0) { mbar_expect_tx(bar_q, 4096); tma_load_2d(kr + Q_OFF, &maps.q, d0, w * 256, bar_q); }
    const uint32_t dpair = __ldg((const uint32_t*)(maps.ssm_D + d0) + t);
    {
      const uint32_t ya = kr + w * 16 + (((lm >> 1) * 8 + lr) * 32) + (lm & 1) * 16;
#pragma unroll
      for (int jn = 0; jn < 16; jn += 2)
        stsm_x4_t(ya + jn * 256, pack_bf16(acc[jn][0], acc[jn][1]), pack_bf16(acc[jn][2], acc[jn][3]),
                  pack_bf16(acc[jn + 1][0], acc[jn + 1][1]), pack_bf16(acc[jn + 1][2], acc[jn + 1][3]));
    }
    named_bar(1 + grp, 256);
    mbar_wait_sleep(bar_q, ph);
    {
      const uint32_t ya = sb + OFF_KR + lr * (KR_PITCH + 16) + (w * 256 + lm * 8) * 2;
#pragma unroll
      for (int i = 0; i < 8; i++) {
        uint32_t y[4], u[4], q[4], r[4];
        ldsm_x4(q, kr + Q_OFF + lane * 16 + i * 512);
        ldsm_x4_t(y, ya + i * 64);
        const int ch = 16 + w * 32 + i * 4 + lm;
        ldsm_x4_t(u, sb + OFF_U + lr * U_PITCH + ((ch ^ ((ch >> 3) & 1)) << 4));
#pragma unroll
        for (int b = 0; b < 4; b++) r[b] = bmul2(q[b], badd2(y[b], bmul2(u[b], dpair)));
        stsm_x4(kr + Q_OFF + lane * 16 + i * 512, r[0], r[1], r[2], r[3]);
      }
      fence_async_smem();
      __syncwarp();
      if (lane == 0) { tma_store_2d(&maps.out, kr + Q_OFF, DM + d0, w * 256); bulk_commit(); }
    }
    named_bar(1 + grp, 256);
  }
  if (lane == 0) bulk_wait<0>();
}

__global__ void __launch_bounds__(512, 1) __cluster_dims__(2, 1, 1) bpart_kernel(const __grid_constant__ BMaps maps, int end) {
  bpart_body(maps, blockIdx.x * 2, gridDim.x * 2, end);
}

struct GemmMaps {
  CUtensorMap o;
  CUtensorMap w;
  CUtensorMap c;
};
namespace k3 {
constexpr int STAGES = 6;
constexpr int W_BYTES = 2 * 8192, O_BYTES = K3_N * 128, STAGE_BYTES = W_BYTES + O_BYTES;
constexpr int TT = (S_LEN + K3_N - 1) / K3_N, NGEMM = TT * (DM / 128), NB = 128 - NGEMM, KSTEPS = HD / 64;
constexpr int SMEM_G = STAGES * STAGE_BYTES + 1024 + 256;
constexpr int SMEM = SMEM_G > bp::SMEM ? SMEM_G : bp::SMEM;
static_assert(STAGE_BYTES % 1024 == 0, "swizzle atoms");
}

__global__ void __launch_bounds__(512, 1)
tail_kernel(const __grid_constant__ GemmMaps maps, const __grid_constant__ BMaps bmaps) {
  using namespace k3;
  if (blockIdx.x < NB) {
    bpart_body(bmaps, bp::NTASK - 2 * NB + 2 * blockIdx.x, bp::NTASK, bp::NTASK);
    return;
  }
  extern __shared__ uint8_t smem_raw[];
  const uint32_t sbase = (smem_u32(smem_raw) + 1023) & ~1023u;
  const uint32_t bars = sbase + STAGES * STAGE_BYTES;
  const int tid = threadIdx.x, warp = tid >> 5;
  const int tt = (blockIdx.x - NB) / 8, ct = (blockIdx.x - NB) % 8;

  if (tid == 0) {
    for (int s = 0; s < STAGES; s++) { mbar_init(bars + 8 * s, 1); mbar_init(bars + 8 * (STAGES + s), 2); }
    asm volatile("fence.mbarrier_init.release.cluster;" ::: "memory");
  }
  __syncthreads();

  if (warp >= 8) {
    if (tid == 256) {
      tma_prefetch_desc(&maps.o);
      for (int k = 0; k < STAGES; k++) {
        const uint32_t full = bars + 8 * k, sa = sbase + k * STAGE_BYTES;
        mbar_expect_tx(full, STAGE_BYTES);
#pragma unroll
        for (int j = 0; j < 2; j++) tma_load_2d(sa + j * 8192, &maps.w, ct * 128 + j * 64, k * 64, full);
      }
      asm volatile("griddepcontrol.wait;" ::: "memory");
      int stage = 0; uint32_t ph = 1;
      for (int k = 0; k < KSTEPS; k++) {
        mbar_wait(bars + 8 * (STAGES + stage), ph);
        const uint32_t full = bars + 8 * stage, sa = sbase + stage * STAGE_BYTES;
        const bool pre = k < STAGES;
        if (!pre) mbar_expect_tx(full, STAGE_BYTES);
        tma_load_2d(sa + W_BYTES, &maps.o, k * 64, tt * K3_N, full);
        if (!pre) {
#pragma unroll
          for (int j = 0; j < 2; j++) tma_load_2d(sa + j * 8192, &maps.w, ct * 128 + j * 64, k * 64, full);
        }
        if (++stage == STAGES) { stage = 0; ph ^= 1; }
      }
    }
  } else {
    const int wg = warp >> 2, lane = tid & 31, wq = warp & 3;
    int stage = 0; uint32_t ph = 0;
    float acc[K3_N / 2];
    int prev = -1;
    for (int k = 0; k < KSTEPS; k++) {
      mbar_wait(bars + 8 * stage, ph);
      const uint32_t sa = sbase + stage * STAGE_BYTES;
      wg_fence();
#pragma unroll
      for (int kk = 0; kk < 4; kk++) {
        const uint64_t da = make_desc(sa + wg * 8192 + kk * 2048, 16, 1024, 1);
        const uint64_t db = make_desc(sa + W_BYTES + kk * 32, 16, 1024, 1);
        wgmma_k3_ss_ta(acc, da, db, (k | kk) != 0);
      }
      wg_commit();
      if (prev >= 0) { wg_wait<1>(); if ((tid & 127) == 0) mbar_arrive(bars + 8 * (STAGES + prev)); }
      prev = stage;
      if (++stage == STAGES) { stage = 0; ph ^= 1; }
    }
    wg_wait<0>();
#pragma unroll
    for (int i = 0; i < K3_N / 2; i++) asm volatile("" : "+f"(acc[i]) :: "memory");
    named_bar(1, 256);
    const uint32_t ebuf = sbase + wg * STAGE_BYTES;
    const uint32_t ea = ebuf + ((lane >> 4) * 8 + (lane & 7)) * 128 + (((2 * wq + ((lane >> 3) & 1)) ^ (lane & 7)) << 4);
#pragma unroll
    for (int i = 0; i < K3_N / 8; i += 2) {
      const int i1 = i + 1 < K3_N / 8 ? i + 1 : i;
      stsm_x4_t(ea + i * 1024, pack_bf16(acc[4 * i], acc[4 * i + 1]), pack_bf16(acc[4 * i + 2], acc[4 * i + 3]),
                pack_bf16(acc[4 * i1], acc[4 * i1 + 1]), pack_bf16(acc[4 * i1 + 2], acc[4 * i1 + 3]));
    }
    fence_async_smem();
    named_bar(2 + wg, 128);
    if ((tid & 127) == 0) {
      tma_store_2d(&maps.c, ebuf, ct * 128 + wg * 64, tt * K3_N);
      bulk_commit();
      bulk_wait<0>();
    }
  }
}

typedef CUresult (*EncodeFn)(CUtensorMap*, CUtensorMapDataType, cuuint32_t, void*, const cuuint64_t*, const cuuint64_t*,
                             const cuuint32_t*, const cuuint32_t*, CUtensorMapInterleave, CUtensorMapSwizzle,
                             CUtensorMapL2promotion, CUtensorMapFloatOOBfill);

void make_map(EncodeFn enc, CUtensorMap* m, const void* ptr, uint64_t cols, uint64_t rows, uint64_t pitch_elems,
              uint32_t box_cols, uint32_t box_rows, CUtensorMapSwizzle swz,
              CUtensorMapL2promotion promo = CU_TENSOR_MAP_L2_PROMOTION_L2_128B) {
  cuuint64_t dims[2] = {cols, rows};
  cuuint64_t strides[1] = {pitch_elems * 2};
  cuuint32_t box[2] = {box_cols, box_rows};
  cuuint32_t es[2] = {1, 1};
  enc(m, CU_TENSOR_MAP_DATA_TYPE_BFLOAT16, 2, const_cast<void*>(ptr), dims, strides, box, es, CU_TENSOR_MAP_INTERLEAVE_NONE, swz,
      promo, CU_TENSOR_MAP_FLOAT_OOB_FILL_NONE);
}

void make_map_nd(EncodeFn enc, CUtensorMap* m, const void* ptr, int rank, const uint64_t* dims, const uint64_t* strides_elems,
                 const uint32_t* box, CUtensorMapSwizzle swz) {
  cuuint64_t d[5], st[4]; cuuint32_t b[5], es[5];
  for (int i = 0; i < rank; i++) { d[i] = dims[i]; b[i] = box[i]; es[i] = 1; if (i) st[i - 1] = strides_elems[i] * 2; }
  enc(m, CU_TENSOR_MAP_DATA_TYPE_BFLOAT16, rank, const_cast<void*>(ptr), d, st, b, es, CU_TENSOR_MAP_INTERLEAVE_NONE, swz,
      CU_TENSOR_MAP_L2_PROMOTION_L2_128B, CU_TENSOR_MAP_FLOAT_OOB_FILL_NONE);
}

}

extern "C" void kernel_launch(void* const* d_in, const int* in_sizes, int n_in, void* d_out, int out_size) {
  (void)in_sizes; (void)n_in; (void)out_size;
  const bf16* x = (const bf16*)d_in[0];
  const bf16* mem0 = (const bf16*)d_in[1];
  const bf16* Wq = (const bf16*)d_in[2];
  const bf16* Wk = (const bf16*)d_in[3];
  const bf16* Wv = (const bf16*)d_in[4];
  const bf16* Wo = (const bf16*)d_in[5];
  const bf16* Bq = (const bf16*)d_in[7];
  const bf16* Bk = (const bf16*)d_in[8];
  const bf16* Bv = (const bf16*)d_in[9];
  const bf16* shift_k = (const bf16*)d_in[10];
  const bf16* ssm_k = (const bf16*)d_in[11];
  const bf16* ssm_D = (const bf16*)d_in[12];
  bf16* out = (bf16*)d_out;

  static EncodeFn enc = nullptr;
  static uint64_t xbase0;
  static int nsm = 132;
  static cudaStream_t s1;
  static cudaEvent_t ev_fork, ev_join;
  if (!enc) {
    cudaDriverEntryPointQueryResult qr;
    void* fn = nullptr;
    cudaGetDriverEntryPoint("cuTensorMapEncodeTiled", &fn, cudaEnableDefault, &qr);
    enc = (EncodeFn)fn;
    void* ps = nullptr;
    cudaGetSymbolAddress(&ps, g_scratch);
    xbase0 = (uint64_t)ps;
    if ((xbase0 >> 32) != ((xbase0 + xo::BYTES - 1) >> 32)) xbase0 += xo::BYTES;
    cudaFuncSetAttribute(tail_kernel, cudaFuncAttributeMaxDynamicSharedMemorySize, k3::SMEM);
    cudaFuncSetAttribute(chain_kernel, cudaFuncAttributeMaxDynamicSharedMemorySize, chain::SMEM);
    cudaFuncSetAttribute(bpart_kernel, cudaFuncAttributeMaxDynamicSharedMemorySize, bp::SMEM);
    cudaStreamCreateWithFlags(&s1, cudaStreamNonBlocking);
    cudaEventCreateWithFlags(&ev_fork, cudaEventDisableTiming);
    cudaEventCreateWithFlags(&ev_join, cudaEventDisableTiming);
    int dev = 0; cudaGetDevice(&dev);
    cudaDeviceGetAttribute(&nsm, cudaDevAttrMultiProcessorCount, dev);
  }
  uint64_t xbase = xbase0;
  const CUtensorMapSwizzle SW128 = CU_TENSOR_MAP_SWIZZLE_128B, SW64 = CU_TENSOR_MAP_SWIZZLE_64B;
  GemmMaps m3; ChainMaps mc;
  make_map(enc, &m3.o, (void*)(xbase + xo::O), HD, S_LEN, HD, 64, K3_N, SW128);
  make_map(enc, &m3.w, Wo, DM, HD, DM, 64, 64, SW128);
  make_map(enc, &m3.c, out, DM, S_LEN, OUT_LD, 64, K3_N, SW128);
  const CUtensorMapL2promotion P256 = CU_TENSOR_MAP_L2_PROMOTION_L2_256B;
  make_map(enc, &mc.wq, Wq, HD, DM, HD, 64, 128, SW128, P256);
  make_map(enc, &mc.wk, Wk, HD, DM, HD, 64, 128, SW128, P256);
  make_map(enc, &mc.wv, Wv, HD, DM, HD, 64, 128, SW128, P256);
  make_map(enc, &mc.wo, Wo, DM, HD, DM, 32, 256, SW64, P256);
  {
    const uint64_t dx[3] = {64, S_LEN, DM / 64}, sx[3] = {1, DM, 64};
    const uint32_t bx[3] = {64, SEG, 8};
    make_map_nd(enc, &mc.x, x, 3, dx, sx, bx, SW128);
    const uint32_t bq[3] = {64, SEG, 4};
    make_map_nd(enc, &mc.xq, x, 3, dx, sx, bq, SW128);
    mc.xp = (const char*)x;
  }

  const int skip = 0;
  mc.t_step = T_STEP; mc.t_phase = T_PHASE;
  BMaps mb;
  const CUtensorMapSwizzle SWN = CU_TENSOR_MAP_SWIZZLE_NONE;
  make_map(enc, &mb.k, Bk, DM, S_LEN, DM, 8, 256, SWN);
  make_map(enc, &mb.q, Bq, DM, S_LEN, DM, 8, 256, SWN);
  make_map(enc, &mb.v, Bv, DM, S_LEN, DM, 8, 256, SWN);
  mb.shift_k = shift_k; mb.ssm_k = ssm_k; mb.ssm_D = ssm_D;
  make_map(enc, &mb.out, out, OUT_LD, S_LEN, OUT_LD, 8, 256, SWN);
  make_map(enc, &mb.k8, Bk, DM, S_LEN, DM, 8, 8, SWN);
  cudaStream_t s0 = cudaStreamPerThread;
  const int nb = nsm >= 132 ? 4 : 2, ntask1 = bp::NTASK - 2 * k3::NB;
  const bool fork = nsm >= 130 && !(skip & 16);
  if (fork) {
    cudaEventRecord(ev_fork, s0);
    cudaStreamWaitEvent(s1, ev_fork, 0);
    if (!(skip & 1)) bpart_kernel<<<nb, 512, bp::SMEM, s1>>>(mb, ntask1);
    cudaEventRecord(ev_join, s1);
  } else if (!(skip & 1)) {
    bpart_kernel<<<ntask1 / 2, 512, bp::SMEM, s0>>>(mb, ntask1);
  }
  if (!(skip & 4)) chain_kernel<<<128, 256, chain::SMEM, s0>>>(mc, mem0, xbase);
  if (!(skip & 8)) {
    cudaLaunchAttribute pdl[1];
    pdl[0].id = cudaLaunchAttributeProgrammaticStreamSerialization;
    pdl[0].val.programmaticStreamSerializationAllowed = 1;
    cudaLaunchConfig_t cfg = {};
    cfg.gridDim = dim3(128); cfg.blockDim = dim3(512); cfg.dynamicSmemBytes = k3::SMEM; cfg.stream = s0;
    cfg.attrs = pdl; cfg.numAttrs = 1;
    cudaLaunchKernelEx(&cfg, tail_kernel, m3, mb);
  }
  if (fork) cudaStreamWaitEvent(s0, ev_join, 0);
}
```

```cpp
#include <cuda_runtime.h>
#include <cuda_bf16.h>
#include <cuda.h>
#include <stdint.h>

namespace {

constexpr int S_LEN = 2048;
constexpr int DM = 1024;
constexpr int NH = 32;
constexpr int DH = 128;
constexpr int HD = NH * DH;
constexpr int SEG = 32;
constexpr int NSEG = S_LEN / SEG;
constexpr int OUT_LD = 2048;

typedef __nv_bfloat16 bf16;
#define K3_N 160

__device__ __forceinline__ uint32_t smem_u32(const void* p) { return (uint32_t)__cvta_generic_to_shared(p); }

__device__ __forceinline__ void mbar_init(uint32_t bar, uint32_t count) {
  asm volatile("mbarrier.init.shared::cta.b64 [%0], %1;" ::"r"(bar), "r"(count) : "memory");
}
__device__ __forceinline__ void mbar_expect_tx(uint32_t bar, uint32_t bytes) {
  asm volatile("mbarrier.arrive.expect_tx.shared::cta.b64 _, [%0], %1;" ::"r"(bar), "r"(bytes) : "memory");
}
__device__ __forceinline__ void mbar_arrive(uint32_t bar) {
  asm volatile("mbarrier.arrive.shared::cta.b64 _, [%0];" ::"r"(bar) : "memory");
}
__device__ __forceinline__ bool mbar_try(uint32_t bar, uint32_t parity) {
  uint32_t ok;
  asm volatile("{.reg .pred p; mbarrier.try_wait.parity.shared::cta.b64 p, [%1], %2; selp.u32 %0, 1, 0, p;}"
               : "=r"(ok) : "r"(bar), "r"(parity) : "memory");
  return ok;
}
__device__ __forceinline__ bool mbar_test(uint32_t bar, uint32_t parity) {
  uint32_t ok;
  asm volatile("{.reg .pred p; mbarrier.test_wait.parity.shared::cta.b64 p, [%1], %2; selp.u32 %0, 1, 0, p;}"
               : "=r"(ok) : "r"(bar), "r"(parity) : "memory");
  return ok;
}
template <int HINT = 1>
__device__ __forceinline__ void mbar_wait(uint32_t bar, uint32_t parity) {
  int guard = 0;
  while (__builtin_expect(!mbar_try(bar, parity), HINT)) { if (++guard > (1 << 22)) __trap(); }
}
__device__ __forceinline__ void tma_load_2d(uint32_t dst, const CUtensorMap* map, int c0, int c1, uint32_t bar) {
  asm volatile("cp.async.bulk.tensor.2d.shared::cluster.global.mbarrier::complete_tx::bytes [%0], [%1, {%3, %4}], [%2];"
               ::"r"(dst), "l"(map), "r"(bar), "r"(c0), "r"(c1) : "memory");
}
__device__ __forceinline__ void tma_store_2d(const CUtensorMap* map, uint32_t src, int c0, int c1) {
  asm volatile("cp.async.bulk.tensor.2d.global.shared::cta.bulk_group [%0, {%2, %3}], [%1];"
               ::"l"(map), "r"(src), "r"(c0), "r"(c1) : "memory");
}
__device__ __forceinline__ void tma_prefetch_2d(const CUtensorMap* map, int c0, int c1) {
  asm volatile("cp.async.bulk.prefetch.tensor.2d.L2.global [%0, {%1, %2}];" ::"l"(map), "r"(c0), "r"(c1) : "memory");
}
__device__ __forceinline__ void tma_prefetch_desc(const CUtensorMap* map) {
  asm volatile("prefetch.tensormap [%0];" ::"l"(map) : "memory");
}
__device__ __forceinline__ void fence_async_smem() { asm volatile("fence.proxy.async.shared::cta;" ::: "memory"); }
__device__ __forceinline__ void bulk_commit() { asm volatile("cp.async.bulk.commit_group;" ::: "memory"); }
template <int N> __device__ __forceinline__ void bulk_wait_read() { asm volatile("cp.async.bulk.wait_group.read %0;" ::"n"(N) : "memory"); }
template <int N> __device__ __forceinline__ void bulk_wait() { asm volatile("cp.async.bulk.wait_group %0;" ::"n"(N) : "memory"); }
__device__ __forceinline__ void named_bar(int id, int n) { asm volatile("bar.sync %0, %1;" ::"r"(id), "r"(n) : "memory"); }

__device__ __forceinline__ void named_bar_arrive(int id, int n) { asm volatile("bar.arrive %0, %1;" ::"r"(id), "r"(n) : "memory"); }
__device__ __forceinline__ float ex2(float x) { float y; asm("ex2.approx.ftz.f32 %0, %1;" : "=f"(y) : "f"(x)); return y; }
__device__ __forceinline__ float rcp(float x) { float y; asm("rcp.approx.ftz.f32 %0, %1;" : "=f"(y) : "f"(x)); return y; }

__device__ __forceinline__ void sts32(uint32_t a, uint32_t x) { asm volatile("st.shared.b32 [%0], %1;" ::"r"(a), "r"(x) : "memory"); }
__device__ __forceinline__ uint32_t lds32(uint32_t a) { uint32_t x; asm volatile("ld.shared.b32 %0, [%1];" : "=r"(x) : "r"(a) : "memory"); return x; }
__device__ __forceinline__ uint32_t lds32v(uint32_t a) { uint32_t x; asm volatile("ld.volatile.shared.b32 %0, [%1];" : "=r"(x) : "r"(a) : "memory"); return x; }
__device__ __forceinline__ void sts128(uint32_t a, const uint4& v) { asm volatile("st.shared.v4.b32 [%0], {%1,%2,%3,%4};" ::"r"(a), "r"(v.x), "r"(v.y), "r"(v.z), "r"(v.w) : "memory"); }
__device__ __forceinline__ void sts128f(uint32_t a, const float4& v) { asm volatile("st.shared.v4.f32 [%0], {%1,%2,%3,%4};" ::"r"(a), "f"(v.x), "f"(v.y), "f"(v.z), "f"(v.w) : "memory"); }
__device__ __forceinline__ uint4 lds128(uint32_t a) { uint4 v; asm volatile("ld.shared.v4.b32 {%0,%1,%2,%3}, [%4];" : "=r"(v.x), "=r"(v.y), "=r"(v.z), "=r"(v.w) : "r"(a) : "memory"); return v; }
__device__ __forceinline__ float4 lds128f(uint32_t a) { float4 v; asm volatile("ld.shared.v4.f32 {%0,%1,%2,%3}, [%4];" : "=f"(v.x), "=f"(v.y), "=f"(v.z), "=f"(v.w) : "r"(a) : "memory"); return v; }

__device__ __forceinline__ void cp_async16(uint32_t dst, const void* src) { asm volatile("cp.async.cg.shared.global [%0], [%1], 16;" ::"r"(dst), "l"(src) : "memory"); }
__device__ __forceinline__ void cp_async_commit() { asm volatile("cp.async.commit_group;" ::: "memory"); }
template <int N> __device__ __forceinline__ void cp_async_wait_group() { asm volatile("cp.async.wait_group %0;" ::"n"(N) : "memory"); }

__device__ __forceinline__ void wg_fence() { asm volatile("wgmma.fence.sync.aligned;" ::: "memory"); }
__device__ __forceinline__ void wg_commit() { asm volatile("wgmma.commit_group.sync.aligned;" ::: "memory"); }
template <int N> __device__ __forceinline__ void wg_wait() { asm volatile("wgmma.wait_group.sync.aligned %0;" ::"n"(N) : "memory"); }
__device__ __forceinline__ uint64_t make_desc(uint32_t addr, uint32_t lbo, uint32_t sbo, uint32_t swz) {
  return (uint64_t)((addr & 0x3FFFF) >> 4) | ((uint64_t)(lbo >> 4) << 16) | ((uint64_t)(sbo >> 4) << 32) | ((uint64_t)swz << 62);
}

__device__ __forceinline__ void ldsm_x4(uint32_t (&r)[4], uint32_t addr) {
  asm volatile("ldmatrix.sync.aligned.m8n8.x4.shared.b16 {%0,%1,%2,%3}, [%4];"
               : "=r"(r[0]), "=r"(r[1]), "=r"(r[2]), "=r"(r[3]) : "r"(addr) : "memory");
}
__device__ __forceinline__ void ldsm_x4_t(uint32_t (&r)[4], uint32_t addr) {
  asm volatile("ldmatrix.sync.aligned.m8n8.x4.trans.shared.b16 {%0,%1,%2,%3}, [%4];"
               : "=r"(r[0]), "=r"(r[1]), "=r"(r[2]), "=r"(r[3]) : "r"(addr) : "memory");
}
__device__ __forceinline__ void stsm_x4(uint32_t addr, uint32_t r0, uint32_t r1, uint32_t r2, uint32_t r3) {
  asm volatile("stmatrix.sync.aligned.m8n8.x4.shared.b16 [%0], {%1,%2,%3,%4};"
               ::"r"(addr), "r"(r0), "r"(r1), "r"(r2), "r"(r3) : "memory");
}
__device__ __forceinline__ void stsm_x4_t(uint32_t addr, uint32_t r0, uint32_t r1, uint32_t r2, uint32_t r3) {
  asm volatile("stmatrix.sync.aligned.m8n8.x4.trans.shared.b16 [%0], {%1,%2,%3,%4};" ::"r"(addr), "r"(r0), "r"(r1), "r"(r2), "r"(r3) : "memory");
}
__device__ __forceinline__ void mma16816(float (&c)[4], const uint32_t (&a)[4], uint32_t b0, uint32_t b1) {
  asm volatile("mma.sync.aligned.m16n8k16.row.col.f32.bf16.bf16.f32 {%0,%1,%2,%3}, {%4,%5,%6,%7}, {%8,%9}, {%0,%1,%2,%3};"
               : "+f"(c[0]), "+f"(c[1]), "+f"(c[2]), "+f"(c[3])
               : "r"(a[0]), "r"(a[1]), "r"(a[2]), "r"(a[3]), "r"(b0), "r"(b1));
}
__device__ __forceinline__ void mma1688(float (&c)[4], uint32_t a0, uint32_t a1, uint32_t b0) {
  asm volatile("mma.sync.aligned.m16n8k8.row.col.f32.bf16.bf16.f32 {%0,%1,%2,%3}, {%4,%5}, {%6}, {%0,%1,%2,%3};"
               : "+f"(c[0]), "+f"(c[1]), "+f"(c[2]), "+f"(c[3]) : "r"(a0), "r"(a1), "r"(b0));
}
__device__ __forceinline__ uint32_t pack_bf16(float lo, float hi) {
  uint32_t r;
  asm("cvt.rn.bf16x2.f32 %0, %1, %2;" : "=r"(r) : "f"(hi), "f"(lo));
  return r;
}
__device__ __forceinline__ float bf_lo(uint32_t w) { return __uint_as_float(w << 16); }
__device__ __forceinline__ float bf_hi(uint32_t w) { return __uint_as_float(w & 0xFFFF0000u); }

__device__ __forceinline__ uint4 ld_relaxed4(const void* p) {
  uint4 v;
  asm volatile("ld.relaxed.gpu.global.v4.u32 {%0,%1,%2,%3}, [%4];" : "=r"(v.x), "=r"(v.y), "=r"(v.z), "=r"(v.w) : "l"(p) : "memory");
  return v;
}
__device__ __forceinline__ void st_relaxed4(void* p, uint32_t a, uint32_t b, uint32_t c, uint32_t d) {
  asm volatile("st.relaxed.gpu.global.v4.u32 [%0], {%1,%2,%3,%4};" ::"l"(p), "r"(a), "r"(b), "r"(c), "r"(d) : "memory");
}
__device__ __forceinline__ void st_relaxed2(void* p, uint32_t a, uint32_t b) {
  asm volatile("st.relaxed.gpu.global.v2.u32 [%0], {%1,%2};" ::"l"(p), "r"(a), "r"(b) : "memory");
}
__device__ __forceinline__ void st_relaxed1(void* p, uint32_t a) {
  asm volatile("st.relaxed.gpu.global.u32 [%0], %1;" ::"l"(p), "r"(a) : "memory");
}

__device__ __forceinline__ uint2 ld_relaxed2(const void* p) {
  uint2 v;
  asm volatile("ld.relaxed.gpu.global.v2.u32 {%0,%1}, [%2];" : "=r"(v.x), "=r"(v.y) : "l"(p) : "memory");
  return v;
}
__device__ __forceinline__ void sts64(uint32_t a, uint32_t x, uint32_t y) { asm volatile("st.shared.v2.b32 [%0], {%1,%2};" ::"r"(a), "r"(x), "r"(y) : "memory"); }
__device__ __forceinline__ uint2 lds64(uint32_t a) { uint2 v; asm volatile("ld.shared.v2.b32 {%0,%1}, [%2];" : "=r"(v.x), "=r"(v.y) : "r"(a) : "memory"); return v; }
__device__ __forceinline__ void lds128r(uint32_t (&r)[4], uint32_t a) {
  asm volatile("ld.shared.v4.b32 {%0,%1,%2,%3}, [%4];" : "=r"(r[0]), "=r"(r[1]), "=r"(r[2]), "=r"(r[3]) : "r"(a) : "memory");
}
__device__ __forceinline__ uint32_t mapa(uint32_t addr, uint32_t rank) { uint32_t r; asm volatile("mapa.shared::cluster.u32 %0, %1, %2;" : "=r"(r) : "r"(addr), "r"(rank)); return r; }
__device__ __forceinline__ void st_async1(uint32_t dst, uint32_t a, uint32_t bar) {
  asm volatile("st.async.weak.shared::cluster.mbarrier::complete_tx::bytes.b32 [%0], %1, [%2];" ::"r"(dst), "r"(a), "r"(bar) : "memory");
}
__device__ __forceinline__ void st_async2(uint32_t dst, uint32_t a, uint32_t b, uint32_t bar) {
  asm volatile("st.async.weak.shared::cluster.mbarrier::complete_tx::bytes.v2.b32 [%0], {%1,%2}, [%3];" ::"r"(dst), "r"(a), "r"(b), "r"(bar) : "memory");
}
__device__ __forceinline__ void cluster_arrive() { asm volatile("barrier.cluster.arrive.relaxed.aligned;" ::: "memory"); }
__device__ __forceinline__ void cluster_wait() { asm volatile("barrier.cluster.wait.acquire.aligned;" ::: "memory"); }

__device__ __forceinline__ void wgmma_k3_ss_ta(float (&d)[80], uint64_t da, uint64_t db, int scale_d) {
  asm volatile("{.reg .pred p; setp.ne.b32 p, %82, 0;\n"
    "wgmma.mma_async.sync.aligned.m64n160k16.f32.bf16.bf16 {%0, %1, %2, %3, %4, %5, %6, %7, %8, %9, %10, %11, %12, %13, %14, %15, %16, %17, %18, %19, %20, %21, %22, %23, %24, %25, %26, %27, %28, %29, %30, %31, %32, %33, %34, %35, %36, %37, %38, %39, %40, %41, %42, %43, %44, %45, %46, %47, %48, %49, %50, %51, %52, %53, %54, %55, %56, %57, %58, %59, %60, %61, %62, %63, %64, %65, %66, %67, %68, %69, %70, %71, %72, %73, %74, %75, %76, %77, %78, %79}, %80, %81, p, 1, 1, 1, 0;}"
    : "+f"(d[0]), "+f"(d[1]), "+f"(d[2]), "+f"(d[3]), "+f"(d[4]), "+f"(d[5]), "+f"(d[6]), "+f"(d[7]), "+f"(d[8]), "+f"(d[9]), "+f"(d[10]), "+f"(d[11]), "+f"(d[12]), "+f"(d[13]), "+f"(d[14]), "+f"(d[15]), "+f"(d[16]), "+f"(d[17]), "+f"(d[18]), "+f"(d[19]), "+f"(d[20]), "+f"(d[21]), "+f"(d[22]), "+f"(d[23]), "+f"(d[24]), "+f"(d[25]), "+f"(d[26]), "+f"(d[27]), "+f"(d[28]), "+f"(d[29]), "+f"(d[30]), "+f"(d[31]), "+f"(d[32]), "+f"(d[33]), "+f"(d[34]), "+f"(d[35]), "+f"(d[36]), "+f"(d[37]), "+f"(d[38]), "+f"(d[39]), "+f"(d[40]), "+f"(d[41]), "+f"(d[42]), "+f"(d[43]), "+f"(d[44]), "+f"(d[45]), "+f"(d[46]), "+f"(d[47]), "+f"(d[48]), "+f"(d[49]), "+f"(d[50]), "+f"(d[51]), "+f"(d[52]), "+f"(d[53]), "+f"(d[54]), "+f"(d[55]), "+f"(d[56]), "+f"(d[57]), "+f"(d[58]), "+f"(d[59]), "+f"(d[60]), "+f"(d[61]), "+f"(d[62]), "+f"(d[63]), "+f"(d[64]), "+f"(d[65]), "+f"(d[66]), "+f"(d[67]), "+f"(d[68]), "+f"(d[69]), "+f"(d[70]), "+f"(d[71]), "+f"(d[72]), "+f"(d[73]), "+f"(d[74]), "+f"(d[75]), "+f"(d[76]), "+f"(d[77]), "+f"(d[78]), "+f"(d[79])
    : "l"(da), "l"(db), "r"(scale_d));
}
__device__ __forceinline__ void wgmma_m64n32_ss_ta(float (&d)[16], uint64_t da, uint64_t db, int scale_d) {
  asm volatile("{.reg .pred p; setp.ne.b32 p, %18, 0;\n"
    "wgmma.mma_async.sync.aligned.m64n32k16.f32.bf16.bf16 {%0, %1, %2, %3, %4, %5, %6, %7, %8, %9, %10, %11, %12, %13, %14, %15}, %16, %17, p, 1, 1, 1, 0;}"
    : "+f"(d[0]), "+f"(d[1]), "+f"(d[2]), "+f"(d[3]), "+f"(d[4]), "+f"(d[5]), "+f"(d[6]), "+f"(d[7]), "+f"(d[8]), "+f"(d[9]), "+f"(d[10]), "+f"(d[11]), "+f"(d[12]), "+f"(d[13]), "+f"(d[14]), "+f"(d[15])
    : "l"(da), "l"(db), "r"(scale_d));
}

__device__ __forceinline__ void wgmma_m64n32_rs(float (&d)[16], const uint32_t (&a)[4], uint64_t db, int scale_d) {
  asm volatile("{.reg .pred p; setp.ne.b32 p, %21, 0;\n"
    "wgmma.mma_async.sync.aligned.m64n32k16.f32.bf16.bf16 {%0, %1, %2, %3, %4, %5, %6, %7, %8, %9, %10, %11, %12, %13, %14, %15}, {%16, %17, %18, %19}, %20, p, 1, 1, 0;}"
    : "+f"(d[0]), "+f"(d[1]), "+f"(d[2]), "+f"(d[3]), "+f"(d[4]), "+f"(d[5]), "+f"(d[6]), "+f"(d[7]), "+f"(d[8]), "+f"(d[9]), "+f"(d[10]), "+f"(d[11]), "+f"(d[12]), "+f"(d[13]), "+f"(d[14]), "+f"(d[15])
    : "r"(a[0]), "r"(a[1]), "r"(a[2]), "r"(a[3]), "l"(db), "r"(scale_d));
}

#define X_POS 7
#define T_STEP 2720
#define T_PHASE 1760
#define RATE0 2295
#define T_LAG 0
#define T_TOL 192
#define T_SLIP 640
#define O_FIX 6
#define NTMP 4
#define V_PRE 8
#define SFENCE(i) asm volatile("{.reg .pred p; setp.eq.u32 p, %0, %1; @p trap;}" ::"r"(n), "r"(4096 + (i)) : "memory")
constexpr int RING = 4;
constexpr uint32_t EMPTY = 0xFFFFFFFFu;
namespace xo {
constexpr uint32_t SLOT = 1u << 20, HEAD = 16384;
constexpr uint32_t VM = 512;
constexpr uint32_t PT = 1024;
constexpr uint32_t PM = 1536;
constexpr uint32_t VT = 8192;
constexpr uint32_t MEM = NH * HEAD;
constexpr uint32_t OM = MEM + 16384;
constexpr uint32_t O = RING * SLOT;
constexpr uint32_t BYTES = O + S_LEN * HD * 2;
}
__device__ __align__(1024) uint4 g_scratch[2 * (xo::BYTES / 16)];
__device__ unsigned g_epoch;
__device__ __align__(16) unsigned g_rate[128];

struct ChainMaps {
  CUtensorMap wq, wk, wv;
  CUtensorMap wo;
  CUtensorMap x, xq;
  CUtensorMap o;
  const char* xp;
  uint32_t t_step, t_phase;
};

namespace chain {
constexpr int OFF_X = 65536;
constexpr int OFF_MEM = 131072;
constexpr int OFF_WS = 0;
constexpr int OFF_FP = 147456;
constexpr int OFF_KT = 163840;
constexpr int OFF_QT = 180224;
constexpr int OFF_VT = 196608;
constexpr int OFF_PX = 204800;
constexpr int OFF_S4 = OFF_PX + 1536;
constexpr int OFF_QM = 212992;
constexpr int OFF_KM = 215040;
constexpr int OFF_S1 = 217088;
constexpr int OFF_WVR = 0;
constexpr int OFF_WOR = 147456;
constexpr int OFF_OT = OFF_WOR + 6144;
constexpr int OFF_RED = 212992;
constexpr int OFF_VPX = 221184;
constexpr int OFF_RX = 223232;
constexpr int OFF_BAR = 229376;
constexpr int BAR_X = OFF_BAR, BAR_TOK = OFF_BAR + 16, BAR_EX = OFF_BAR + 32, BAR_P = OFF_BAR + 40, GRID_TGT = OFF_BAR + 128;
constexpr int CT_BASE = GRID_TGT + 4, CT_HEAD = GRID_TGT + 8, CT_OM = GRID_TGT + 12, CT_MP = GRID_TGT + 16, CT_O = GRID_TGT + 20, CT_PF = GRID_TGT + 24;
constexpr int CT_TT = GRID_TGT + 28, CT_T = GRID_TGT + 32;
constexpr uint32_t RANK_BIT = 1u << 24;
constexpr int OFF_RX1 = OFF_BAR + 256;
constexpr int SMEM = OFF_RX1 + 2048;
constexpr uint32_t SB_LO = 1024;
constexpr float SCALE = 0.08838834764831845f, L2E = 1.4426950408889634f;
}

__device__ __forceinline__ uint32_t umax4(uint32_t a, uint32_t b, uint32_t c, uint32_t d) { return max(max(a, b), max(c, d)); }
__device__ __forceinline__ bool warp_incomplete(uint32_t m) { return __any_sync(0xffffffffu, m == EMPTY); }
#define PIN(x) asm volatile("" : "+r"(x))
#define KEEPALIVE(a, z) do { float _d0, _d1, _d2, _d3; asm volatile("mma.sync.aligned.m16n8k16.row.col.f32.bf16.bf16.f32 {%0,%1,%2,%3}, {%4,%5,%6,%7}, {%4,%5}, {%8,%8,%8,%8};" \
    : "=f"(_d0), "=f"(_d1), "=f"(_d2), "=f"(_d3) : "r"(a[0]), "r"(a[1]), "r"(a[2]), "r"(a[3]), "f"(0.f)); \
      \
    asm volatile("{.reg .pred p; setp.ne.u32 p, %0, 0; @p st.shared.f32 [%0], %1;}" ::"r"(z), "f"(_d0 + _d3) : "memory"); } while (0)
constexpr int POLL_LIMIT = 1 << 15;

__device__ __forceinline__ uint32_t keep(uint32_t x) { return __shfl_sync(0xffffffffu, x, threadIdx.x & 31); }
__device__ __forceinline__ char* gptr(uint32_t hi, uint32_t lo) { return (char*)(((uint64_t)hi << 32) | lo); }
__device__ __forceinline__ uint32_t slot_off(int n) { return ((uint32_t)n & (RING - 1)) * xo::SLOT; }
__device__ __forceinline__ float quad_max(float x) {
  const float a = __shfl_xor_sync(~0u, x, 1), b = __shfl_xor_sync(~0u, x, 2), c = __shfl_xor_sync(~0u, x, 3);
  return fmaxf(fmaxf(x, a), fmaxf(b, c));
}
__device__ __forceinline__ void acc_fence(float (&a)[16]) {
#pragma unroll
  for (int i = 0; i < 16; i++) asm volatile("" : "+f"(a[i]) :: "memory");
}
template <int NB = 1, int STRIDE = 0>
__device__ __forceinline__ void gather_issue(uint32_t dst, const char* src) {
#pragma unroll
  for (int b = 0; b < NB; b++)
#pragma unroll
    for (int i = 0; i < 4; i++) cp_async16(dst + b * STRIDE + i * 512, src + b * STRIDE + i * 512);
  cp_async_commit();
}
template <int NB, int STRIDE>
__device__ __forceinline__ bool gather_incomplete(uint32_t chk) {
  uint32_t m = 0;
#pragma unroll
  for (int b = 0; b < NB; b++) m = max(m, umax4(lds32(chk + b * STRIDE), lds32(chk + b * STRIDE + 512), lds32(chk + b * STRIDE + 1024), lds32(chk + b * STRIDE + 1536)));
  return warp_incomplete(m);
}
__device__ __forceinline__ uint32_t ld_relaxed1(const void* p) {
  uint32_t v;
  asm volatile("ld.relaxed.gpu.global.u32 %0, [%1];" : "=r"(v) : "l"(p) : "memory");
  return v;
}
__device__ __forceinline__ uint32_t gtime() { uint64_t g; asm volatile("mov.u64 %0, %%globaltimer;" : "=l"(g) :: "memory"); return (uint32_t)g; }
#define WAIT_UNTIL(t, ka, alive, id) do { \
    int _d = gtime() - (t); \
    if (__builtin_expect(_d > T_TOL, 0)) do { t += T_SLIP; _d -= T_SLIP; } while (_d > T_TOL); \
    if (alive) for (int _k = 64; _d < -96 && --_k; _d = gtime() - (t)) KEEPALIVE(ka, zr); \
    for (uint32_t _g = 0xFFFFFF80u; (int)(_d & ++_g) < 0;) _d = gtime() - (t); } while (0)
__device__ __forceinline__ void issue_x(uint32_t sb, const CUtensorMap* map, int n, int part, int q = 0) {
  asm volatile("{.reg .pred p; elect.sync _|p, 0xffffffff;\n"
               "@p cp.async.bulk.tensor.3d.shared::cluster.global.mbarrier::complete_tx::bytes [%0], [%1, {%3, %4, %5}], [%2];}"
               ::"r"(sb + chain::OFF_X + part * 32768 + q * 16384), "l"(map), "r"(sb + chain::BAR_X + 8 * part), "r"(0), "r"(n * SEG), "r"(part * 8 + q * 4) : "memory");
}
__device__ __forceinline__ void issue_x_if(uint32_t sb, const CUtensorMap* map, int n, int part, uint32_t on) {
  asm volatile("{.reg .pred p, q; elect.sync _|p, 0xffffffff; setp.ne.and.u32 q, %6, 0, p;\n"
               "@q cp.async.bulk.tensor.3d.shared::cluster.global.mbarrier::complete_tx::bytes [%0], [%1, {%3, %4, %5}], [%2];}"
               ::"r"(sb + chain::OFF_X + part * 32768), "l"(map), "r"(sb + chain::BAR_X + 8 * part), "r"(0), "r"(n * SEG), "r"(part * 8), "r"(on) : "memory");
}
__device__ __forceinline__ void prefetch_l2(const char* p, uint32_t bytes) {
  asm volatile("{.reg .pred p; elect.sync _|p, 0xffffffff; @p cp.async.bulk.prefetch.L2.global [%0], %1;}" ::"l"(p), "r"(bytes) : "memory");
}
__device__ __forceinline__ void expect_elect(uint32_t bar, uint32_t bytes) {
  asm volatile("{.reg .pred p; elect.sync _|p, 0xffffffff; @p mbarrier.arrive.expect_tx.shared::cta.b64 _, [%0], %1;}" ::"r"(bar), "r"(bytes) : "memory");
}
template <int WG> __device__ __forceinline__ constexpr uint64_t xdesc(int ks) {
  return (uint64_t)(((chain::SB_LO + chain::OFF_X + WG * 32768 + (ks >> 2) * 4096 + (ks & 3) * 32) >> 4) + (1u << 16)) |
         ((uint64_t)(64u | (1u << 30)) << 32);
}
template <int WG> __device__ __forceinline__ constexpr uint64_t wdesc(int o, int ks) {
  return (uint64_t)(((chain::SB_LO + chain::OFF_WS + WG * 32768 + o * 16384 + ks * 2048) >> 4) + (1u << 16)) | ((uint64_t)(64u | (1u << 30)) << 32);
}
__device__ __forceinline__ void load_mem0(uint2 (&m)[8], const bf16* __restrict__ mem0) {
#pragma unroll
  for (int r = 0; r < 8; r++) m[r] = ld_relaxed2((const uint2*)(mem0 + r * DM) + threadIdx.x);
}
__device__ __forceinline__ void store_mem0(uint32_t sb, const uint2 (&m)[8]) {
  const uint32_t d = sb + chain::OFF_MEM + threadIdx.x * 64;
  sts128(d, make_uint4(__byte_perm(m[0].x, m[1].x, 0x5410), __byte_perm(m[2].x, m[3].x, 0x5410), __byte_perm(m[4].x, m[5].x, 0x5410), __byte_perm(m[6].x, m[7].x, 0x5410)));
  sts128(d + 16, make_uint4(__byte_perm(m[0].x, m[1].x, 0x7632), __byte_perm(m[2].x, m[3].x, 0x7632), __byte_perm(m[4].x, m[5].x, 0x7632), __byte_perm(m[6].x, m[7].x, 0x7632)));
  sts128(d + 32, make_uint4(__byte_perm(m[0].y, m[1].y, 0x5410), __byte_perm(m[2].y, m[3].y, 0x5410), __byte_perm(m[4].y, m[5].y, 0x5410), __byte_perm(m[6].y, m[7].y, 0x5410)));
  sts128(d + 48, make_uint4(__byte_perm(m[0].y, m[1].y, 0x7632), __byte_perm(m[2].y, m[3].y, 0x7632), __byte_perm(m[4].y, m[5].y, 0x7632), __byte_perm(m[6].y, m[7].y, 0x7632)));
}
template <int K> __device__ __forceinline__ uint32_t loop_zero(int n) { uint32_t z; asm volatile("shr.u32 %0, %1, %2;" : "=r"(z) : "r"(n), "n"(16 + K)); return z; }
#define NEWZ(k) zr = loop_zero<k>(n)

template <int WG>
__device__ __forceinline__ void role_a(const ChainMaps& maps, const bf16* __restrict__ mem0, const uint32_t sb, const uint32_t xbase_hi) {
  using namespace chain;
  const int h = blockIdx.x >> 2;
  const bool J = sb >= RANK_BIT;
  const uint32_t u16 = (threadIdx.x & 96) * 64 + (threadIdx.x & 31) * 16;
  const uint32_t t16 = keep(u16), l16 = keep((threadIdx.x & 31) * 16);
  const uint32_t a_wl = keep((((threadIdx.x >> 4) & 1) * 8 + (threadIdx.x & 7)) * 128 + (((((threadIdx.x >> 4) & 6) + ((threadIdx.x >> 3) & 1)) ^ (threadIdx.x & 7)) << 4));
  const uint32_t xhi = keep(xbase_hi + (t16 >> 16));
#define xh (lds32(sb + CT_HEAD) + t16)
#define xm (lds32(sb + CT_BASE) + t16 + xo::MEM)
#define last_warp __any_sync(0xffffffffu, tv >= 6144)
#define tv (t16 ^ zr)
  const CUtensorMap* wm = J ? &maps.wk : &maps.wq;

  uint32_t aW[2][24][4];
  uint2 m0[8];
  load_mem0(m0, mem0);
  mbar_wait(sb + BAR_P, 0);
#pragma unroll
  for (int ks = 0; ks < 24; ks++) ldsm_x4_t(aW[0][ks], sb + a_wl + OFF_X + WG * 49152 + ks * 2048);
  named_bar(0, 256);
  if (WG == 1 && __any_sync(0xffffffffu, t16 >= 6144)) {
    fence_async_smem();
    if (l16 == 0) {
      mbar_expect_tx(sb + BAR_P + 16, 2 * 16384);
      for (int q = 0; q < 2; q++) tma_load_2d(sb + OFF_X + (4 + q) * 16384, wm, h * DH + (q ^ 1) * 64, q * 512 + 256, sb + BAR_P + 16);
    }
    __syncwarp();
    expect_elect(sb + BAR_X, 32768); expect_elect(sb + BAR_X + 8, 32768); expect_elect(sb + BAR_TOK, 8192);
    issue_x(sb, &maps.x, 0, 0); issue_x(sb, &maps.x, 0, 1);
  }
  mbar_wait(sb + BAR_P + 8, 0);
#pragma unroll
  for (int ks = 0; ks < 16; ks++) ldsm_x4_t(aW[1][ks], sb + a_wl + OFF_X + 6 * 16384 + WG * 32768 + ks * 2048);
  mbar_wait(sb + BAR_P + 16, 0);
#pragma unroll
  for (int ks = 0; ks < 8; ks++) ldsm_x4_t(aW[1][16 + ks], sb + a_wl + OFF_X + (4 + WG) * 16384 + ks * 2048);
  named_bar(0, 256);
  cluster_arrive();
  store_mem0(sb, m0);
  mbar_wait(sb + BAR_P + 24, 0);
  cluster_wait();
  const uint32_t rsb = sb ^ RANK_BIT;
  const uint32_t a_ws = sb + a_wl + OFF_WS + WG * 32768;

  uint32_t ws[2][4][4];
  auto load_ws = [&]() {
#pragma unroll
    for (int q = 0; q < 2; q++) {
      const uint32_t a = a_ws + q * 4096;
      ldsm_x4_t(ws[q][0], a); ldsm_x4_t(ws[q][1], a + 16384); ldsm_x4_t(ws[q][2], a + 2048); ldsm_x4_t(ws[q][3], a + 16384 + 2048);
    }
  };
  uint32_t tref = 0;
#pragma unroll 1
  for (int n = 0; n <= (J ? NSEG : NSEG - 1); n++) {
#define s (n - 1)
#define sv ((int)(n ^ zr) - 1)
    const bool more = __builtin_expect(s + 1 < NSEG, 1);
    uint32_t zr = loop_zero<0>(n);
#define wq ((int)(tv >> 11))
#define lv (l16 ^ zr)
#define gh (xh + slot_off(sv))
    uint32_t tmp[NTMP][4];
    auto load_tmp = [&](int o) {
#pragma unroll
      for (int ks = 0; ks < NTMP; ks++) ldsm_x4_t(tmp[ks], a_ws + o * 16384 + ks * 2048);
    };
    float y[10];
    auto no_p = [&]() {
#pragma unroll
      for (int i = 0; i < 10; i++) asm volatile("mov.b32 %0, %1;" : "=f"(y[i]) : "r"(zr));
    };
    auto finish_p = [&]() {
      const uint32_t gp = gh;
      float sy = ((y[0] + y[1]) + (y[2] + y[3])) + ((y[4] + y[5]) + (y[6] + y[7])) + (y[8] + y[9]);
      const float ry = rcp((sy + __shfl_xor_sync(~0u, sy, 1)) + (__shfl_xor_sync(~0u, sy, 2) + __shfl_xor_sync(~0u, sy, 3)));
      st_relaxed4(gptr(xhi, gp) + xo::PT, pack_bf16(y[2] * ry, y[3] * ry), pack_bf16(y[4] * ry, y[5] * ry), pack_bf16(y[6] * ry, y[7] * ry), pack_bf16(y[8] * ry, y[9] * ry));
      const uint32_t l12 = lv - (lv >> 2);
      st_relaxed1(gptr(xhi, gp - l12) + xo::PM, pack_bf16(y[0] * ry, y[1] * ry));
    };
    auto wait_x = [&]() { mbar_wait<0>(sb + BAR_X + 8 * WG, n & 1); };
    if (__builtin_expect(s < 0, 0)) { load_tmp(1); wait_x(); if (WG == 0) no_p(); }
    else {
      {
        if (WG == 1) { if (__builtin_expect(s > 0, 1)) {
          const uint32_t dst = sb + OFF_MEM + tv + t16 - l16, chk = dst + ((lv >> 5) & 12);
          uint32_t tries = zr;
#pragma unroll 1
          do {
            if (tries) {
              const char* src = gptr(xhi, xm + t16 - l16 + slot_off(sv));
              tref += T_SLIP;
              WAIT_UNTIL(tref, aW[0][0], 1, -1);
              gather_issue<2, 2048>(dst, src);
            }
            KEEPALIVE(aW[0][0], zr);
            cp_async_wait_group<0>();
          } while (gather_incomplete<2, 2048>(chk) && ++tries < POLL_LIMIT);
        } } else if (J == 0) {
          uint32_t tries = s == 0;
#pragma unroll 1
          do {
            if (tries) gather_issue(sb + OFF_VT + tv, gptr(xhi, gh) + xo::VT);
            cp_async_wait_group<0>();
          } while (gather_incomplete<1, 0>(sb + OFF_VT + t16 + ((lv >> 5) & 12)) && ++tries < POLL_LIMIT);
        }
        named_bar(1, 256);
      }
      float c[2][2][4];
#pragma unroll
      for (int i = 0; i < 4; i++) c[i >> 1][i & 1][0] = c[i >> 1][i & 1][1] = c[i >> 1][i & 1][2] = c[i >> 1][i & 1][3] = 0.f;
      {
        const uint32_t a_mem = sb + OFF_MEM + WG * 8192 + l16;
        uint32_t b[4][4];
        bool tok;
        constexpr int PR[16] = {12, 13, 0, 1, 2, 3, 4, 14, 5, 6, 7, 8, 9, 15, 10, 11};
        ldsm_x4_t(b[0], a_mem + PR[0] * 512); ldsm_x4_t(b[1], a_mem + PR[1] * 512);
#pragma unroll
        for (int i = 0; i < 16; i++) {
          if ((i & 1) == 0 && i < 14) {
            ldsm_x4_t(b[(i + 2) & 3], a_mem + PR[i + 2] * 512); ldsm_x4_t(b[(i + 3) & 3], a_mem + PR[i + 3] * 512);
            if (i == 2 || i == 8) { ldsm_x4_t(ws[1][0], a_ws + (i == 2 ? 2 : 3) * 4096); ldsm_x4_t(ws[1][1], a_ws + (i == 2 ? 2 : 3) * 4096 + 16384); }
            if (i == 4 || i == 10) { ldsm_x4_t(ws[1][2], a_ws + (i == 4 ? 2 : 3) * 4096 + 2048); ldsm_x4_t(ws[1][3], a_ws + (i == 4 ? 2 : 3) * 4096 + 16384 + 2048); }
          }
          const int p = PR[i];
          if (p >= 12) {
            const int z = i != 0;
            mma16816(c[0][0], ws[z][0], b[i & 3][0], b[i & 3][1]); mma16816(c[1][0], ws[z][1], b[i & 3][0], b[i & 3][1]);
            mma16816(c[0][1], ws[z][2], b[i & 3][2], b[i & 3][3]); mma16816(c[1][1], ws[z][3], b[i & 3][2], b[i & 3][3]);
          } else {
            mma16816(c[1][0], aW[1][2 * p], b[i & 3][0], b[i & 3][1]); mma16816(c[1][1], aW[1][2 * p + 1], b[i & 3][2], b[i & 3][3]);
            mma16816(c[0][0], aW[0][2 * p], b[i & 3][0], b[i & 3][1]); mma16816(c[0][1], aW[0][2 * p + 1], b[i & 3][2], b[i & 3][3]);
          }
          if (i == 12) tok = mbar_test(sb + BAR_TOK + 8 * (s & 1), (s >> 1) & 1);
          if (i == 15 && __builtin_expect(!tok, 0)) mbar_wait(sb + BAR_TOK + 8 * (s & 1), (s >> 1) & 1);
          if (i == X_POS + 4 * (1 - WG)) { issue_x_if(sb, &maps.x, s + 1, WG, t16 >= 6144 && more); if (WG) __syncwarp(); }
        }
      }
      sts128f(sb + OFF_PX + WG * 512 + t16, make_float4(c[1][0][0] + c[1][1][0], c[1][0][1] + c[1][1][1], c[1][0][2] + c[1][1][2], c[1][0][3] + c[1][1][3]));
      const float4 own = make_float4(c[0][0][0] + c[0][1][0], c[0][0][1] + c[0][1][1], c[0][0][2] + c[0][1][2], c[0][0][3] + c[0][1][3]);
      NEWZ(1);
      const uint32_t kt = sb + OFF_KT + (s & 1) * 8192;
#define k_lane ((lv & 240) + ((lv & 256) << 2))
#define a_lane (((lv & 128) << 1) + ((lv & 256) >> 1) + (lv & 112))
      uint32_t kb[4][4];
      named_bar(3, 256);
      auto finish_tile = [&](bool send) {
        const float4 o = lds128f(sb + OFF_PX + (WG ^ 1) * 512 + t16);
        const uint32_t a = (send ? OFF_KM : OFF_QM) + WG * 1024 + wq * 256 + (lv >> 2);
        const uint32_t lo = pack_bf16(own.x + o.x, own.y + o.y), hi = pack_bf16(own.z + o.z, own.w + o.w);
        if (send) { st_async1(rsb + a, lo, rsb + BAR_EX); st_async1(rsb + a + 128, hi, rsb + BAR_EX); }
        sts32(sb + a, lo); sts32(sb + a + 128, hi);
      };
      if (J == 0) {
        finish_tile(false);
        uint32_t am[4][4];
        const uint32_t aq = sb + OFF_QM + a_lane, ak = kt + wq * 256 + k_lane;
        auto load_q = [&]() {
#pragma unroll
          for (int p = 0; p < 4; p++) ldsm_x4_t(am[p], aq + p * 512);
        };
        auto scores = [&]() {
          float c0[2][4], c1[2][4];
#pragma unroll
          for (int i = 0; i < 2; i++) { c0[i][0] = c0[i][1] = c0[i][2] = c0[i][3] = 0.f; c1[i][0] = c1[i][1] = c1[i][2] = c1[i][3] = 0.f; }
#pragma unroll
          for (int p = 0; p < 4; p++) { mma16816(c0[p & 1], am[p], kb[p][0], kb[p][1]); mma16816(c1[p & 1], am[p], kb[p][2], kb[p][3]); }
          const uint32_t r1 = pack_bf16((c0[0][0] + c0[1][0]) + (c1[0][2] + c1[1][2]), (c0[0][1] + c0[1][1]) + (c1[0][3] + c1[1][3]));
          return pack_bf16(bf_lo(r1) * SCALE, bf_hi(r1) * SCALE);
        };
        if (WG == 1) {
          if (last_warp) {
            named_bar(7, 256);
            load_q();
            const uint32_t sa = sb + OFF_S1 + (lv >> 1);
            mbar_wait<0>(sb + BAR_EX, s & 1);
#pragma unroll
            for (int p = 0; p < 4; p++) ldsm_x4_t(kb[p], sb + OFF_KM + p * 512 + l16);
            const uint32_t sm = scores();
            sts64(sa, sm, __float_as_uint(quad_max(fmaxf(bf_lo(sm), bf_hi(sm)))));
            named_bar_arrive(9, 160);
          } else {
            named_bar_arrive(7, 256);
          }
          wait_x();
          load_tmp(1);
        } else {
#pragma unroll
          for (int p = 0; p < 4; p++) ldsm_x4(kb[p], ak + p * 2048);
          named_bar(7, 256);
          load_q();
          const uint32_t omb = lds32(sb + CT_OM);
          const char* pvm = gptr(xhi, lds32(sb + CT_HEAD) + t16 + slot_off(sv) - (lv >> 1) + (am[3][0] & zr)) + xo::VM;
          uint2 vm0 = ld_relaxed2(pvm), vm1 = ld_relaxed2(pvm + 256);
          sts32(sb + OFF_S4 + l16 + wq * 4, scores());
          named_bar(8, 128);
          const uint4 sc = lds128(sb + OFF_S4 + l16);
          uint32_t vb[4][4];
          {
            const uint32_t va = sb + OFF_VT + t16 + (sc.x & zr);
#pragma unroll
            for (int e = 0; e < 4; e++) lds128r(vb[e], va + e * 512);
          }
          float x[8] = {bf_lo(sc.x), bf_hi(sc.x), bf_lo(sc.y), bf_hi(sc.y), bf_lo(sc.z), bf_hi(sc.z), bf_lo(sc.w), bf_hi(sc.w)};
          const float mt = quad_max(fmaxf(fmaxf(fmaxf(x[0], x[1]), fmaxf(x[2], x[3])), fmaxf(fmaxf(x[4], x[5]), fmaxf(x[6], x[7]))));
          const float mtb = mt * L2E;
#pragma unroll
          for (int i = 0; i < 8; i++) x[i] = ex2(fmaf(x[i], L2E, -mtb));
          uint32_t pa[4], pb[4], p5;
          asm volatile("" : "=r"(pa[1]), "=r"(pa[3]), "=r"(pb[1]), "=r"(pb[3]), "=r"(p5));
          pa[0] = pack_bf16(x[0], x[1]); pa[2] = pack_bf16(x[2], x[3]);
          pb[0] = pack_bf16(x[4], x[5]); pb[2] = pack_bf16(x[6], x[7]);
          float st = ((x[0] + x[1]) + (x[2] + x[3])) + ((x[4] + x[5]) + (x[6] + x[7]));
          asm volatile("" : "+r"(pb[0]), "+r"(pb[2]), "+f"(st));
          float oa[4][4];
#pragma unroll
          for (int e = 0; e < 4; e++) { oa[e][0] = oa[e][1] = oa[e][2] = oa[e][3] = 0.f; mma16816(oa[e], pa, vb[e][0], vb[e][1]); }
          SFENCE(25);
          named_bar(9, 160);
          const uint2 sm2 = lds64(sb + OFF_S1 + (lv >> 1));
          const uint32_t sm = sm2.x;
          const float mx = fmaxf(mt, __uint_as_float(sm2.y));
#pragma unroll
          for (int e = 0; e < 4; e++) mma16816(oa[e], pb, vb[e][2], vb[e][3]);
          const float mb = mx * L2E;
          const float e0 = ex2(fmaf(bf_lo(sm), L2E, -mb)), e1 = ex2(fmaf(bf_hi(sm), L2E, -mb)), ct = ex2(mtb - mb);
          const uint32_t xo0 = omb + wq * 512 + l16;
          if (__builtin_expect(warp_incomplete(max(max(vm0.x, vm1.x), __float_as_uint(mx) & zr)), 0)) {
            uint32_t tries = zr;
#pragma unroll 1
            do { vm0 = ld_relaxed2(pvm); vm1 = ld_relaxed2(pvm + 256); } while (warp_incomplete(max(vm0.x, vm1.x)) && ++tries < POLL_LIMIT);
          }
          const float sx = fmaf(ct, st, e0 + e1);
          const float s1 = __shfl_xor_sync(~0u, sx, 1), s2 = __shfl_xor_sync(~0u, sx, 2), s3 = __shfl_xor_sync(~0u, sx, 3);
          const uint32_t p4 = pack_bf16(e0, e1);
#pragma unroll
          for (int e = 0; e < 4; e++) { oa[e][0] *= ct; oa[e][1] *= ct; }
          named_bar_arrive(10 + ((__float_as_uint(oa[3][1]) | p4 | __float_as_uint(s3)) & zr), 256);
          mma1688(oa[0], p4, p5, vm0.x); mma1688(oa[1], p4, p5, vm0.y); mma1688(oa[2], p4, p5, vm1.x); mma1688(oa[3], p4, p5, vm1.y);
          const float rx = rcp((sx + s1) + (s2 + s3));
          st_relaxed4(gptr(xhi, xo0 + slot_off(sv)), pack_bf16(oa[0][0] * rx, oa[0][1] * rx), pack_bf16(oa[1][0] * rx, oa[1][1] * rx),
                      pack_bf16(oa[2][0] * rx, oa[2][1] * rx), pack_bf16(oa[3][0] * rx, oa[3][1] * rx));
          SFENCE(26);
          st_relaxed4(gptr(xhi, xo0 + slot_off(sv + 3)), EMPTY, EMPTY, EMPTY, EMPTY);
          load_tmp(1);
          wait_x();
          no_p();
        }
      } else {
        finish_tile(true);
        bool xok;
        {
          const int mt = WG | (wq == 3), ktile = wq == 3 ? 2 + WG : wq - 1;
          const uint32_t qt = sb + OFF_QT + (s & 1) * 8192 + mt * 512 + a_lane;
          uint32_t q[8][4];
          if (__any_sync(0xffffffffu, tv < 2048)) {
            named_bar(7, 256);
#pragma unroll
            for (int p = 0; p < 4; p++) ldsm_x4_t(kb[p], sb + OFF_KM + p * 512 + l16);
          } else {
            named_bar_arrive(7, 256);
#pragma unroll
            for (int p = 0; p < 4; p++) ldsm_x4(kb[p], kt + ktile * 256 + k_lane + p * 2048);
          }
#pragma unroll
          for (int i = 0; i < 8; i++) ldsm_x4(q[i], qt + i * 1024);
          __syncwarp();
          float c0[4][4];
#pragma unroll
          for (int i = 0; i < 4; i++) { c0[i][0] = c0[i][1] = c0[i][2] = c0[i][3] = 0.f; mma16816(c0[i], q[i], kb[i >> 1][(i & 1) * 2], kb[i >> 1][(i & 1) * 2 + 1]); }
#pragma unroll
          for (int i = 0; i < 4; i++) mma16816(c0[i], q[4 + i], kb[2 + (i >> 1)][(i & 1) * 2], kb[2 + (i >> 1)][(i & 1) * 2 + 1]);
          load_tmp(1);
          xok = mbar_test(sb + BAR_X + 8 * WG, n & 1);
          NEWZ(3);
          const uint32_t r0 = pack_bf16((c0[0][0] + c0[1][0]) + (c0[2][0] + c0[3][0]), (c0[0][1] + c0[1][1]) + (c0[2][1] + c0[3][1]));
          const uint32_t r1 = pack_bf16((c0[0][2] + c0[1][2]) + (c0[2][2] + c0[3][2]), (c0[0][3] + c0[1][3]) + (c0[2][3] + c0[3][3]));
          const uint32_t sa = wq == 0 ? sb + OFF_S1 + (lv >> 2) + mt * 256 : sb + OFF_S4 + l16 + mt * 4096 + ktile * 4;
          sts32(sa, pack_bf16(bf_lo(r0) * SCALE, bf_hi(r0) * SCALE));
          sts32(sa + (wq == 0 ? 128 : 2048), pack_bf16(bf_lo(r1) * SCALE, bf_hi(r1) * SCALE));
        }
        if (WG == 1) named_bar_arrive(8, 256);
        else {
          if (more) named_bar_arrive(10, 256);
          named_bar(8, 256);
          const uint4 sc = lds128(sb + OFF_S4 + t16); const uint32_t s1 = lds32(sb + OFF_S1 + wq * 128 + (lv >> 2));
          y[0] = bf_lo(s1); y[1] = bf_hi(s1); y[2] = bf_lo(sc.x); y[3] = bf_hi(sc.x); y[4] = bf_lo(sc.y); y[5] = bf_hi(sc.y);
          y[6] = bf_lo(sc.z); y[7] = bf_hi(sc.z); y[8] = bf_lo(sc.w); y[9] = bf_hi(sc.w);
          const int rel = wq * 8 + (int)(lv >> 6) - (int)((lv >> 3) & 6);
          const float NEG = -999292928.f;
#pragma unroll
          for (int e = 0; e < 4; e++) {
            if (e * 8 > rel) y[2 * e + 2] = NEG;
            if (e * 8 + 1 > rel) y[2 * e + 3] = NEG;
          }
          float my = fmaxf(fmaxf(fmaxf(y[0], y[1]), fmaxf(y[2], y[3])), fmaxf(fmaxf(y[4], y[5]), fmaxf(y[6], y[7])));
          my = quad_max(fmaxf(my, fmaxf(y[8], y[9])));
#pragma unroll
          for (int i = 0; i < 10; i++) y[i] = ex2((y[i] - my) * L2E);
          if (!more) finish_p();
        }
        if (!xok && more) wait_x();
      }
    }
    if (more) {
      float acc[16];
      const uint32_t xph = (s + 1) & 1;
      auto batch = [&](const uint32_t (&a)[24][4], int o) {
        wg_fence();
#pragma unroll
        for (int ks = NTMP; ks < 8; ks++) wgmma_m64n32_ss_ta(acc, wdesc<WG>(o, ks), xdesc<WG>(24 + ks), ks != NTMP);
#pragma unroll
        for (int ks = 0; ks < NTMP; ks++) wgmma_m64n32_rs(acc, tmp[ks], xdesc<WG>(24 + ks), 1);
#pragma unroll
        for (int ks = 0; ks < 24; ks++) wgmma_m64n32_rs(acc, a[ks], xdesc<WG>(ks), 1);
        wg_commit();
        SFENCE(50 + o);
      };
      if (WG == 0) named_bar(12, 256);
      else if (__builtin_expect(s >= 0, 1)) named_bar(10, 256);
      batch(aW[1], 1);
      named_bar_arrive(WG ? 12 : 13, 256);
      if (WG == 0 && s >= 0) {
        NEWZ(7);
        const uint32_t g1 = xh + slot_off(sv + 1);
        if (J == 0) gather_issue(sb + OFF_VT + tv, gptr(xhi, g1) + xo::VT);
        else {
          finish_p();
          st_relaxed4(gptr(xhi, g1) + xo::PT, EMPTY, EMPTY, EMPTY, EMPTY);
          st_relaxed1(gptr(xhi, g1 - lv + (lv >> 2)) + xo::PM, EMPTY);
        }
      }
      wg_wait<0>();
      acc_fence(acc);
      load_tmp(0);
#pragma unroll
      for (int i = 0; i < 4; i++) sts128f(sb + OFF_FP + WG * 8192 + t16 + i * 512, make_float4(acc[4 * i], acc[4 * i + 1], acc[4 * i + 2], acc[4 * i + 3]));
      NEWZ(4);
      uint32_t esrc = 0;
      if (WG == 1) { esrc = xm + t16 - l16 + 2048 + slot_off(sv + 1); tref += lds32(sb + CT_T); }
      named_bar(WG ? 13 : 14, 256);
      batch(aW[0], 0);
      NEWZ(5);
      if (WG == 1) {
        named_bar(14, 256);
        if (last_warp) {
          if (s + 2 < NSEG) { expect_elect(sb + BAR_TOK + 8 * (xph ^ 1), 8192); expect_elect(sb + BAR_X, 32768); expect_elect(sb + BAR_X + 8, 32768); }
          if (J == 0) expect_elect(sb + BAR_EX, 2048);
          if (s == NSEG - 3) asm volatile("griddepcontrol.launch_dependents;");
        }
      }
      const uint32_t tb = lds32(sb + CT_TT) + xph * 8192 + WG * 4096 + ((tv + l16) >> 1);
      float4 oth[4];
#pragma unroll
      for (int i = 0; i < 4; i++) oth[i] = lds128f(sb + OFF_FP + (WG ^ 1) * 8192 + t16 + i * 512);
      if (WG == 1 && __builtin_expect(s >= 0, 1)) {
        const uint32_t edst = sb + OFF_MEM + tv + t16 - l16;
        WAIT_UNTIL(tref, aW[0][0], 0, J ? 7 : 0);
        gather_issue<2, 2048>(edst, gptr(xhi, esrc) - 2048);
      }
      wg_wait<0>();
      acc_fence(acc);
      uint32_t lt[4], ht[4];
#pragma unroll
      for (int i = 0; i < 4; i++) {
        const float4 o = oth[i];
        lt[i] = pack_bf16(acc[4 * i] + o.x, acc[4 * i + 1] + o.y); ht[i] = pack_bf16(acc[4 * i + 2] + o.z, acc[4 * i + 3] + o.w);
      }
      stsm_x4_t(tb, lt[0], ht[0], lt[1], ht[1]); stsm_x4_t(tb + 512, lt[2], ht[2], lt[3], ht[3]);
      NEWZ(6);
      if (WG == 0 && last_warp) {
        load_ws();
        named_bar(11, 256);
        fence_async_smem();
        const uint32_t tt = (J ? OFF_KT : OFF_QT) + xph * 8192;
        asm volatile("{.reg .pred p; elect.sync _|p, 0xffffffff;\n"
                     "@p cp.async.bulk.shared::cluster.shared::cta.mbarrier::complete_tx::bytes [%0], [%1], 8192, [%2];}"
                     ::"r"(rsb + tt), "r"(sb + tt), "r"(rsb + BAR_TOK + 8 * xph) : "memory");
      } else {
        named_bar_arrive(11, 256);
        load_ws();
      }
    }
    if (!more) break;
    if (__builtin_expect(s < 0, 0)) {
      tref = gtime() / T_SLIP * T_SLIP - T_SLIP;
    }
  }
  cp_async_wait_group<0>();
  if (J == 0) { mbar_wait(sb + BAR_TOK + 8, 1); mbar_wait(sb + BAR_EX, 1); }
}

__device__ __forceinline__ constexpr bool o_fixed(int i) { return 2 * (7 - (i & 7)) + (i < 8) < O_FIX; }
template <int WG>
__device__ __forceinline__ void role_v(const ChainMaps& maps, const bf16* __restrict__ mem0, const uint32_t sb, const uint32_t xbase_hi) {
  using namespace chain;
  const int h = blockIdx.x >> 2;
  const uint32_t u16 = (threadIdx.x & 96) * 64 + (threadIdx.x & 31) * 16;
  const uint32_t t16 = keep(u16), l16 = keep((threadIdx.x & 31) * 16);
  const uint32_t xhi = keep(xbase_hi + (t16 >> 16));
#define j (sb >> 24)
  auto wv_addr = [&](uint32_t t) { return WG * 32768 + ((t & 256) << 2) + ((t & 112) << 3) + ((((t >> 6) & 96) + ((t >> 3) & 16)) ^ (t & 112)); };
  auto wo_addr = [&](uint32_t t) { return OFF_WOR + WG * 32768 + ((t & 6144) << 2) + ((t & 256) << 1) + ((t & 112) << 2) + ((((j ^ 1) << 5) + ((t >> 3) & 16)) ^ ((t >> 1) & 48)); };
#define ovt (((tv + l16) >> 1) + (xo::VT + WG * 512 + j * 4096))
#define ovm (((tv & 4096) >> 1) + ((tv & 2048) >> 3) + (lv >> 1) + (xo::VM + j * 4096))
#define xvt (lds32(sb + CT_HEAD) + ovt)
#define xvm (lds32(sb + CT_HEAD) + ovm)
#define xom (lds32(sb + CT_OM) + t16 + WG * 8192)
#define warp_is(q) __any_sync(0xffffffffu, (tv >> 11) == (q))
#define upper_warps (WG == 1 || __any_sync(0xffffffffu, tv >= 4096))

  uint32_t aV[16][4];
  uint32_t aO[16][4];
  uint32_t bO[16][4];
  uint32_t rot[16][4];
  if (WG == 1 && __any_sync(0xffffffffu, t16 >= 6144)) {
    expect_elect(sb + BAR_X, 32768); expect_elect(sb + BAR_X + 8, 32768);
    issue_x(sb, &maps.x, 0, 0); issue_x(sb, &maps.x, 0, 1);
    prefetch_l2(maps.xp + 65536 + (h * 2 + j) * 3072, 3072);
  }
  cluster_arrive();
  { uint2 m0[8]; load_mem0(m0, mem0); store_mem0(sb, m0); }
  mbar_wait(sb + BAR_P, 0);
#pragma unroll
  for (int ks = 0; ks < 16; ks++) ldsm_x4_t(aV[ks], sb + wv_addr(t16) + OFF_WOR + ks * 2048);
  auto load_v = [&](uint32_t t) {
#pragma unroll
    for (int ks = 0; ks < 16; ks++) ldsm_x4_t(rot[ks], sb + wv_addr(t) + OFF_WVR + ks * 2048);
  };
  load_v(t16);
  named_bar(0, 256);
  if (threadIdx.x == 0) {
    fence_async_smem();
    mbar_expect_tx(sb + BAR_P + 8, 4 * 16384);
    for (int q = 0; q < 4; q++) tma_load_2d(sb + OFF_WOR + q * 16384, &maps.wo, h * 32, j * 2048 + q * 256, sb + BAR_P + 8);
    for (int q = 0; q < 4; q++) tma_prefetch_2d(&maps.wo, h * 32, j * 2048 + 1024 + q * 256);
  }
  __syncwarp();
  cluster_wait();
  const uint32_t rsb = sb ^ RANK_BIT;

  uint32_t tref = 0;
#pragma unroll 1
  for (int n = 0; n <= NSEG; n++) {
    const bool more = __builtin_expect(s + 1 < NSEG, 1);
    uint32_t zr = loop_zero<0>(n);
    bool xok = false;
    if (__builtin_expect(s >= 0, 1)) {
      if (__builtin_expect(s > 0, 1)) {
        const uint32_t dst = sb + OFF_MEM + WG * 8192 + t16 + ((lv >> 5) & 12);
        uint32_t tries = zr;
#pragma unroll 1
        do {
          if (tries) { const char* src = gptr(xhi, xm + WG * 8192 + slot_off(sv)); tref += T_SLIP; WAIT_UNTIL(tref, aV[0], 1, -1); gather_issue(sb + OFF_MEM + WG * 8192 + tv, src); }
          KEEPALIVE(aV[0], zr);
          cp_async_wait_group<0>();
        } while (gather_incomplete<1, 0>(dst) && ++tries < POLL_LIMIT);
        named_bar(1 + WG, 128);
      }
      const uint32_t a_mem = sb + OFF_MEM + WG * 8192 + l16;
      float c[2][4];
      c[0][0] = c[0][1] = c[0][2] = c[0][3] = c[1][0] = c[1][1] = c[1][2] = c[1][3] = 0.f;
      constexpr int NBUF = (48 - 8 - 4 * O_FIX) / 4;
      uint32_t b[NBUF][4];
#pragma unroll
      for (int p = 0; p < NBUF - 1; p++) ldsm_x4_t(b[p], a_mem + p * 512);
#pragma unroll
      for (int p = 0; p < 16; p++) {
        if (p + NBUF - 1 < 16) ldsm_x4_t(b[(p + NBUF - 1) % NBUF], a_mem + (p + NBUF - 1) * 512);
        if (p < 8) { mma16816(c[0], aV[2 * p], b[p % NBUF][0], b[p % NBUF][1]); mma16816(c[1], aV[2 * p + 1], b[p % NBUF][2], b[p % NBUF][3]); }
        else { mma16816(c[0], rot[2 * p - 16], b[p % NBUF][0], b[p % NBUF][1]); mma16816(c[1], rot[2 * p - 15], b[p % NBUF][2], b[p % NBUF][3]); }
      }
      xok = mbar_test(sb + BAR_X + 8 * WG, n & 1);
      SFENCE(15);
      const float4 own = make_float4(c[0][0] + c[1][0], c[0][1] + c[1][1], c[0][2] + c[1][2], c[0][3] + c[1][3]);
      NEWZ(1);
      const uint32_t pvm = WG == 0 ? xvm + slot_off(sv) : 0;
      if (WG == 1) sts128f(sb + OFF_VPX + wq * 512 + l16, own);
      named_bar(3, 256);
      if (WG == 0) {
        const float4 o = lds128f(sb + OFF_VPX + wq * 512 + l16);
        st_relaxed2(gptr(xhi, pvm), pack_bf16(own.x + o.x, own.y + o.y), pack_bf16(own.z + o.z, own.w + o.w));
      }
    }
    auto stage = [&](uint32_t o) { return sb + OFF_MEM + o; };
    auto stage_pv = [&](int seg) {
      const uint32_t o = WG ? ovt - 512 : tv + 512, dst = stage(o);
      const char* src = gptr(xhi, lds32(sb + CT_HEAD) + slot_off(seg) + o);
#pragma unroll
      for (int i = 0; i < 3 - WG; i++) cp_async16(dst + i * 512, src + i * 512);
    };
    constexpr int NU = 2 - WG;
    uint32_t ot[NU][4], oaddr;
    auto store_ot = [&]() {
#pragma unroll
      for (int i = 0; i < 2 * NU; i++)
        asm volatile("st.global.v2.u32 [%0], {%1, %2};" ::"l"(gptr(xhi, oaddr) + (i & 1) * 8 * HD * 2 - (i >> 1) * 64), "r"(ot[i >> 1][(i & 1) * 2]), "r"(ot[i >> 1][(i & 1) * 2 + 1]) : "memory");
    };
    auto send_ot = [&]() {
      fence_async_smem();
      asm volatile("{.reg .pred p; elect.sync _|p, 0xffffffff;\n"
                   "@p cp.async.bulk.tensor.2d.global.shared::cta.bulk_group [%0, {%2, %3}], [%1];\n"
                   "cp.async.bulk.commit_group;}"
                   ::"l"(&maps.o), "r"(sb + OFF_OT + WG * 8192), "r"(lds32(sb + CT_PF) >> 4), "r"((s - 2) * SEG + WG * 16) : "memory");
    };
    auto token_pv = [&](int seg, bool staged) {
      uint4 pt0, pt1, v0[NU], v1[NU]; uint32_t pm0, pm1; uint2 vm[NU];
      const uint32_t ap = l16 + WG * 4096 + xo::PT, am = (lv >> 2) + WG * 4096 + xo::PM;
      const uint32_t at = ovt - WG * 512;
      if (staged) {
        constexpr int BS = 2048;
        const uint32_t sp = stage(ap), sm = stage(am), st = stage(at), sv2 = stage(ovm);
        pt0 = lds128(sp); pt1 = lds128(sp + BS); pm0 = lds32(sm); pm1 = lds32(sm + BS);
#pragma unroll
        for (int u = 0; u < NU; u++) { v0[u] = lds128(st - u * BS); v1[u] = lds128(st + 512 - u * BS); vm[u] = lds64(sv2 - u * BS); }
      } else {
        const uint32_t b = lds32(sb + CT_HEAD) + slot_off(seg);
        pt0.x = EMPTY;
#pragma unroll
        for (int u = 0; u < NU; u++) {
          v0[u] = ld_relaxed4(gptr(xhi, b + at) - u * 2048); v1[u] = ld_relaxed4(gptr(xhi, b + at) + 512 - u * 2048);
          vm[u] = ld_relaxed2(gptr(xhi, b + ovm) - u * 2048);
        }
      }
      const bool odd = lv & 16;
      oaddr = lds32(sb + CT_O) + (seg * SEG + WG * 16 + (lv >> 6)) * (HD * 2) + wq * 32 + (lv & 16) + ((lv >> 2) & 8);
      if (!staged || __builtin_expect(warp_incomplete(umax4(pt0.x, pt1.x, pm0, pm1)), 0)) {
        const uint32_t b = lds32(sb + CT_HEAD) + slot_off(seg);
        uint32_t tries = zr;
#pragma unroll 1
        do {
          pt0 = ld_relaxed4(gptr(xhi, b + ap)); pt1 = ld_relaxed4(gptr(xhi, b + ap) + 2048);
          pm0 = ld_relaxed1(gptr(xhi, b + am)); pm1 = ld_relaxed1(gptr(xhi, b + am) + 2048);
        } while (warp_incomplete(umax4(pt0.x, pt1.x, pm0, pm1)) && ++tries < POLL_LIMIT);
      }
      const uint32_t pa[4] = {pt0.x, pt1.x, pt0.y, pt1.y}, pb[4] = {pt0.z, pt1.z, pt0.w, pt1.w};
#pragma unroll
      for (int u = 0; u < NU; u++) {
        float o0[4] = {0.f, 0.f, 0.f, 0.f}, o1[4] = {0.f, 0.f, 0.f, 0.f};
        mma1688(o0, pm0, pm1, vm[u].x); mma1688(o1, pm0, pm1, vm[u].y);
        mma16816(o0, pa, v0[u].x, v0[u].y); mma16816(o1, pa, v1[u].x, v1[u].y);
        if (WG) { mma16816(o0, pb, v0[u].z, v0[u].w); mma16816(o1, pb, v1[u].z, v1[u].w); }
        if (staged) {
          stsm_x4(sb + OFF_OT + WG * 8192 + (lv & 240) * 8 + ((((wq - 2 * u) * 32 + ((lv >> 4) & 16)) ^ (lv & 112))),
                  pack_bf16(o0[0], o0[1]), pack_bf16(o0[2], o0[3]), pack_bf16(o1[0], o1[1]), pack_bf16(o1[2], o1[3]));
          continue;
        }
#pragma unroll
        for (int r = 0; r < 2; r++) {
          const uint32_t w0 = pack_bf16(o0[2 * r], o0[2 * r + 1]), w1 = pack_bf16(o1[2 * r], o1[2 * r + 1]);
          const uint32_t rv = __shfl_xor_sync(~0u, odd ? w0 : w1, 1);
          ot[u][2 * r] = odd ? rv : w0; ot[u][2 * r + 1] = odd ? w1 : rv;
        }
      }
    };
    if (!more) {
      named_bar(3, 256);
      if (warp_is(1)) { send_ot(); bulk_wait<0>(); }
      if (upper_warps) {
#pragma unroll 1
        for (int seg = NSEG - 2; seg < NSEG; seg++) { token_pv(seg, false); store_ot(); }
      }
      break;
    }
    {
      if (__builtin_expect(s > 0, 1)) { stage_pv(sv - 1); cp_async_commit(); }
      bool xw;
      {
        float acc[16];
        if (__builtin_expect(!xok, 0)) mbar_wait<0>(sb + BAR_X + 8 * WG, (s + 1) & 1);
        wg_fence();
#pragma unroll
        for (int ks = 0; ks < 16; ks++) wgmma_m64n32_rs(acc, rot[ks], xdesc<WG>(16 + ks), ks != 0);
        wg_commit();
#pragma unroll
        for (int ks = 0; ks < 16; ks++) wgmma_m64n32_rs(acc, aV[ks], xdesc<WG>(ks), 1);
        wg_commit();
        SFENCE(50);
        NEWZ(2);
        xw = warp_is(3) && s + 2 < NSEG;
        tref += lds32(sb + CT_T + 4) + WG * T_LAG - T_SLIP;
        const uint32_t pvt = xvt + slot_off(sv + 1), awo = sb + wo_addr(tv);
        if (warp_is(1)) {
          if (WG == 0 && s >= 0) expect_elect(sb + BAR_EX, 4096);
          if (s >= 2) send_ot();
        }
        if (xw) {
          expect_elect(sb + BAR_X + 8 * WG, 32768);
          if (WG == 1 && s == NSEG - 3) asm volatile("griddepcontrol.launch_dependents;");
          if (WG == 1 && s + 5 < NSEG) prefetch_l2(maps.xp + (s + 5) * 65536 + lds32(sb + CT_PF), 1024);
        }
        wg_wait<1>();
        if (xw) issue_x(sb, &maps.xq, s + 2, WG, 1);
        if (__builtin_expect(s == 0, 0)) {
          mbar_wait(sb + BAR_P + 16, 0);
#pragma unroll
          for (int ks = 0; ks < 16; ks++) if (o_fixed(ks)) ldsm_x4_t(bO[ks], (ks < 8 ? awo : awo ^ 32) + (ks & 7) * 1024);
        }
#pragma unroll
        for (int ks = 0; ks < 16; ks++) if (!o_fixed(ks)) ldsm_x4_t(bO[ks], (ks < 8 ? awo : awo ^ 32) + (ks & 7) * 1024);
        wg_wait<0>();
        acc_fence(acc);
        constexpr int K = WG * 2, G = 2 - K;
        sts128f(sb + OFF_RED + WG * 1024 + t16, make_float4(acc[G], acc[G + 1], acc[4 + G], acc[5 + G]));
        sts128f(sb + OFF_RED + WG * 1024 + 512 + t16, make_float4(acc[8 + G], acc[9 + G], acc[12 + G], acc[13 + G]));
        cp_async_wait_group<0>();
        bulk_wait_read<0>();
        named_bar(3, 256);
        const float4 o0 = lds128f(sb + OFF_RED + (WG ^ 1) * 1024 + t16), o1 = lds128f(sb + OFF_RED + (WG ^ 1) * 1024 + 512 + t16);
        st_relaxed4(gptr(xhi, pvt),
                    pack_bf16(acc[K] + o0.x, acc[K + 1] + o0.y), pack_bf16(acc[4 + K] + o0.z, acc[5 + K] + o0.w),
                    pack_bf16(acc[8 + K] + o1.x, acc[9 + K] + o1.y), pack_bf16(acc[12 + K] + o1.z, acc[13 + K] + o1.w));
      }
      if (__builtin_expect(s >= 0, 1)) {
        uint32_t tries = 0;
#pragma unroll
        for (int ks = 0; ks < 16; ks++) if (!o_fixed(ks)) tries |= bO[ks][0];
        const char* po = gptr(xhi, xom + slot_off(sv) + (tries & zr));
        tries = zr;
        float d[2][2][4];
        uint32_t mx;
#pragma unroll 1
        do {
          tref += T_SLIP;
          WAIT_UNTIL(tref, aV[0], 1, 1);
          uint4 o[8];
#pragma unroll
          for (int i = 0; i < 4; i++) o[i] = ld_relaxed4(po + i * 512);
#pragma unroll
          for (int i = 0; i < 4; i++) o[4 + i] = ld_relaxed4(po + 16384 + i * 512);
          __syncwarp();
#pragma unroll
          for (int i = 0; i < 2; i++)
#pragma unroll
            for (int q = 0; q < 2; q++) { d[i][q][0] = d[i][q][1] = d[i][q][2] = d[i][q][3] = 0.f; }
#pragma unroll
          for (int i = 0; i < 4; i++) {
            mma16816(d[0][0], aO[2 * i], o[i].x, o[i].y); mma16816(d[1][0], aO[8 + 2 * i], o[i].x, o[i].y);
            mma16816(d[0][1], aO[2 * i + 1], o[i].z, o[i].w); mma16816(d[1][1], aO[9 + 2 * i], o[i].z, o[i].w);
          }
          mx = umax4(o[0].w, o[1].w, o[2].w, o[3].w);
          SFENCE(33 + tries);
#pragma unroll
          for (int i = 0; i < 4; i++) {
            mma16816(d[0][0], bO[2 * i], o[4 + i].x, o[4 + i].y); mma16816(d[1][0], bO[8 + 2 * i], o[4 + i].x, o[4 + i].y);
            mma16816(d[0][1], bO[2 * i + 1], o[4 + i].z, o[4 + i].w); mma16816(d[1][1], bO[9 + 2 * i], o[4 + i].z, o[4 + i].w);
          }
          mx = max(mx, umax4(o[4].w, o[5].w, o[6].w, o[7].w));
        } while (warp_incomplete(mx) && ++tries < POLL_LIMIT);
        NEWZ(3);
        {
          const uint32_t rr = rsb + (WG ? OFF_RX1 : OFF_RX) + wq * 512 + (lv >> 1);
          st_async2(rr, __float_as_uint(d[0][0][0] + d[0][1][0]), __float_as_uint(d[0][0][1] + d[0][1][1]), rsb + BAR_EX);
          st_async2(rr + 256, __float_as_uint(d[0][0][2] + d[0][1][2]), __float_as_uint(d[0][0][3] + d[0][1][3]), rsb + BAR_EX);
          const uint32_t rd = sb + OFF_RED + (WG ^ 1) * 1024 + t16 - (lv >> 1);
          sts64(rd, __float_as_uint(d[1][0][0] + d[1][1][0]), __float_as_uint(d[1][0][1] + d[1][1][1]));
          sts64(rd + 256, __float_as_uint(d[1][0][2] + d[1][1][2]), __float_as_uint(d[1][0][3] + d[1][1][3]));
        }
        if (upper_warps) {
          named_bar_arrive(7, 256);
          if (xw) issue_x(sb, &maps.xq, s + 2, WG, 0);
          if (__builtin_expect(s > 0, 1)) token_pv(sv - 1, true);
        } else {
          const uint32_t mp = lds32(sb + CT_MP) + (lv >> 2) + wq * 128, ra = sb + wq * 256 + (lv >> 1);
          char* pp = gptr(xhi, mp + slot_off(sv + 1));
          named_bar(7, 256);
          uint2 p[8];
#pragma unroll
          for (int i = 0; i < 8; i++) p[i] = lds64(ra + OFF_RED + i * 1024);
#define SUM8(c) (((__uint_as_float(p[0].c) + __uint_as_float(p[1].c)) + (__uint_as_float(p[2].c) + __uint_as_float(p[3].c))) + \
                 ((__uint_as_float(p[4].c) + __uint_as_float(p[5].c)) + (__uint_as_float(p[6].c) + __uint_as_float(p[7].c))))
          const float r0 = SUM8(x), r1 = SUM8(y);
          mbar_wait(sb + BAR_EX, s & 1);
#pragma unroll
          for (int i = 0; i < 8; i++) p[i] = lds64(ra + (i < 4 ? OFF_RX : OFF_RX1) + (i & 3) * 512);
          st_relaxed1(pp, pack_bf16(r0 + SUM8(x), r1 + SUM8(y)));
          st_relaxed1(gptr(xhi, mp + slot_off(sv + 3)), EMPTY);
        }
        NEWZ(4);
        const char* src = gptr(xhi, xm + WG * 8192 + slot_off(sv + 1));
        const uint32_t awv = sb + wv_addr(tv) + OFF_WVR;
        tref += lds32(sb + CT_T + 8) - WG * T_LAG;
        named_bar(8, 256);
#pragma unroll
        for (int ks = 0; ks < V_PRE; ks++) ldsm_x4_t(rot[ks], awv + ks * 2048);
        WAIT_UNTIL(tref, aV[0], 1, 2);
        gather_issue(sb + OFF_MEM + WG * 8192 + tv, src);
#pragma unroll
        for (int ks = V_PRE; ks < 16; ks++) ldsm_x4_t(rot[ks], awv + ks * 2048);
        NEWZ(6);
        st_relaxed4(gptr(xhi, xvt + slot_off(sv + 2)), EMPTY, EMPTY, EMPTY, EMPTY);
        if (WG == 0) st_relaxed2(gptr(xhi, xvm + slot_off(sv + 2)), EMPTY, EMPTY);
      } else {
        load_v(tv);
        if (xw) issue_x(sb, &maps.xq, s + 2, WG, 0);
        mbar_wait(sb + BAR_P + 8, 0);
#pragma unroll
        for (int ks = 0; ks < 8; ks++) { ldsm_x4_t(aO[ks], sb + wo_addr(tv) + ks * 1024); ldsm_x4_t(aO[8 + ks], sb + (wo_addr(tv) ^ 32) + ks * 1024); }
        named_bar(0, 256);
        if (threadIdx.x == 0) {
          fence_async_smem();
          mbar_expect_tx(sb + BAR_P + 16, 4 * 16384);
          for (int q = 0; q < 4; q++) tma_load_2d(sb + OFF_WOR + q * 16384, &maps.wo, h * 32, j * 2048 + 1024 + q * 256, sb + BAR_P + 16);
        }
        __syncwarp();
        tref = gtime() / T_SLIP * T_SLIP - T_SLIP;
      }
    }
  }
}

#undef j
#undef s
#undef sv
#undef xm
#undef wq

__global__ void __launch_bounds__(256, 1) __cluster_dims__(2, 1, 1)
chain_kernel(const __grid_constant__ ChainMaps maps, const bf16* __restrict__ mem0, const uint64_t xbase) {
  using namespace chain;
  extern __shared__ uint8_t smem_raw[];
  uint32_t sb = smem_u32(smem_raw);
  PIN(sb);
  if (sb != SB_LO + (blockIdx.x & 1) * RANK_BIT || mapa(sb, (blockIdx.x & 1) ^ 1) != (sb ^ RANK_BIT)) __trap();
  const int tid = threadIdx.x;
  const int h = blockIdx.x >> 2, role = (blockIdx.x >> 1) & 1, j = blockIdx.x & 1;
  if (tid == 0) {
    for (int i = 0; i < 9; i++) mbar_init(sb + OFF_BAR + 8 * i, 1);
    asm volatile("fence.mbarrier_init.release.cluster;" ::: "memory");
    const uint32_t xl = (uint32_t)xbase;
    sts32(sb + CT_BASE, xl); sts32(sb + CT_HEAD, xl + h * xo::HEAD); sts32(sb + CT_OM, xl + xo::OM + (role ? j * 32768 : h * 2048));
    sts32(sb + CT_MP, xl + xo::MEM + (h * 2 + j) * 256); sts32(sb + CT_O, xl + xo::O + (h * 2 + j) * 128); sts32(sb + CT_PF, (h * 2 + j) * 1024);
    sts32(sb + CT_TT, sb + (j ? OFF_KT : OFF_QT));
    if (role == 0) {
      const CUtensorMap* wm = j ? &maps.wk : &maps.wq;
      mbar_expect_tx(sb + BAR_P, 6 * 16384);
      for (int c = 0; c < 3; c++)
        for (int q = 0; q < 2; q++) tma_load_2d(sb + OFF_X + (q * 3 + c) * 16384, wm, h * DH + q * 64, q * 512 + c * 128, sb + BAR_P);
      mbar_expect_tx(sb + BAR_P + 8, 4 * 16384);
      for (int c = 0; c < 2; c++)
        for (int q = 0; q < 2; q++) tma_load_2d(sb + OFF_X + (6 + q * 2 + c) * 16384, wm, h * DH + (q ^ 1) * 64, q * 512 + c * 128, sb + BAR_P + 8);
      mbar_expect_tx(sb + BAR_P + 24, 4 * 16384);
      for (int q = 0; q < 2; q++)
        for (int o = 0; o < 2; o++) tma_load_2d(sb + OFF_WS + (q * 2 + o) * 16384, wm, h * DH + (q ^ o) * 64, q * 512 + 384, sb + BAR_P + 24);
      for (int q = 0; q < 2; q++) tma_prefetch_2d(wm, h * DH + (q ^ 1) * 64, q * 512 + 256);
    } else {
      mbar_expect_tx(sb + BAR_P, 8 * 16384);
      for (int q = 0; q < 4; q++) tma_load_2d(sb + OFF_WOR + q * 16384, &maps.wv, h * DH + j * 64, (q >> 1) * 512 + (q & 1) * 128, sb + BAR_P);
      for (int q = 0; q < 4; q++) tma_load_2d(sb + OFF_WVR + q * 16384, &maps.wv, h * DH + j * 64, (q >> 1) * 512 + 256 + (q & 1) * 128, sb + BAR_P);
    }
  }
  for (int r = 0; r < RING; r++) {
    char* p = (char*)xbase + r * xo::SLOT;
    const int wq = (tid >> 5) & 3;
    if (role == 1) st_relaxed4(p + h * xo::HEAD + xo::VT + (8 * j + 2 * wq + (tid >> 7)) * 512 + (tid & 31) * 16, EMPTY, EMPTY, EMPTY, EMPTY);
    else if (j == 0) st_relaxed4(p + (tid < 128 ? xo::OM + h * 2048 + tid * 16 : h * xo::HEAD + wq * 2048 + xo::VM + (tid & 31) * 16), EMPTY, EMPTY, EMPTY, EMPTY);
    else {
      st_relaxed4(p + h * xo::HEAD + (tid >> 6) * 2048 + 1024 + (tid & 63) * 16, EMPTY, EMPTY, EMPTY, EMPTY);
      if (tid < 32) st_relaxed4(p + xo::MEM + h * 512 + tid * 16, EMPTY, EMPTY, EMPTY, EMPTY);
    }
  }
  __syncthreads();
  if (__shfl_sync(0xffffffffu, tid >> 5, 0) == 0) {
    uint32_t t[2], c[2], ka[4] = {0, 0, 0, 0};
    const uint32_t z = maps.t_step >> 24;
#pragma unroll
    for (int i = 0; i < 2; i++) {
      const uint32_t end = (gtime() & ~31u) + (i ? 2048 : 1024);
      for (int g = z; g < 256 && (int)(gtime() - (end - 96)) < 0; g++) KEEPALIVE(ka, z);
      for (int g = z; g < 256 && (int)((t[i] = gtime()) - end) < 0; g++) {}
      c[i] = (uint32_t)clock64();
    }
    uint32_t v = 0, target = 0;
    if (tid == 0) {
      st_relaxed1(&g_rate[blockIdx.x], (t[1] - t[0]) * 4096u / (c[1] - c[0]));
      __threadfence();
      target = (atomicAdd(&g_epoch, 1u) & ~127u) + 128u;
    }
    target = __shfl_sync(0xffffffffu, target, 0);
    int guard = 0;
    do { asm volatile("ld.acquire.gpu.global.u32 %0, [%1];" : "=r"(v) : "l"(&g_epoch) : "memory"); }
    while (__any_sync(0xffffffffu, (int)(v - target) < 0) && ++guard < (1 << 20));
    const uint4 r4 = ld_relaxed4(&g_rate[tid * 4]);
    uint32_t r = min(__reduce_max_sync(0xffffffffu, umax4(r4.x, r4.y, r4.z, r4.w)), 4 * RATE0);
    if (r < RATE0 + 28) r = RATE0;
    const uint32_t a = (maps.t_step * r / RATE0 + 31) & ~31u, b = (maps.t_phase * r / RATE0 + 31) & ~31u;
    sts128(sb + CT_T, make_uint4(a, b, a - b, r));
  }
  const uint32_t xhi = (uint32_t)(xbase >> 32);
  const int wg = __shfl_sync(0xffffffffu, tid >> 7, 0);
  if (role == 0) {
    if (wg == 0) role_a<0>(maps, mem0, sb, xhi); else role_a<1>(maps, mem0, sb, xhi);
  } else {
    if (wg == 0) role_v<0>(maps, mem0, sb, xhi); else role_v<1>(maps, mem0, sb, xhi);
  }
  __syncwarp();
  cluster_arrive();
  cluster_wait();
}

struct BMaps {
  CUtensorMap q, k, v, out, k8;
  const bf16 *shift_k, *ssm_k, *ssm_D;
};

#define B_SLEEP 200
namespace bp {
constexpr int U_PITCH = (2048 + 128) * 2 + 16;
constexpr int KR_WORDS = 1048;
constexpr int KR_PITCH = 8704;
constexpr int OFF_U = 0;
constexpr int OFF_KR = (8 * U_PITCH + 127) / 128 * 128;
constexpr int Q_OFF = 4352;
constexpr int OFF_BAR = OFF_KR + 8 * KR_PITCH;
constexpr int GROUP_BYTES = OFF_BAR + 128;
constexpr int SMEM = 2 * GROUP_BYTES + 128;
constexpr int NTASK = DM / 8;
static_assert(Q_OFF >= 4224 && Q_OFF + 4096 <= KR_PITCH, "staging does not fit");
}

__device__ __forceinline__ uint32_t bmul2(uint32_t a, uint32_t b) { uint32_t r; asm("mul.rn.bf16x2 %0, %1, %2;" : "=r"(r) : "r"(a), "r"(b)); return r; }
__device__ __forceinline__ uint32_t badd2(uint32_t a, uint32_t b) { uint32_t r; asm("add.rn.bf16x2 %0, %1, %2;" : "=r"(r) : "r"(a), "r"(b)); return r; }

__device__ __forceinline__ void mbar_wait_sleep(uint32_t bar, uint32_t parity) {
  int guard = 0;
  while (!mbar_try(bar, parity)) { __nanosleep(B_SLEEP); if (++guard > (1 << 22)) __trap(); }
}

__device__ __forceinline__ void bpart_body(const BMaps& maps, int first, int stride, int end) {
  using namespace bp;
  extern __shared__ uint8_t smem_all[];
  const int grp = __shfl_sync(0xffffffffu, threadIdx.x >> 8, 0);
  const int lane = keep(threadIdx.x & 31), g = lane >> 2, t = lane & 3;
  const int w = __shfl_sync(0xffffffffu, (threadIdx.x >> 5) & 7, 0);
  const uint32_t sb = ((smem_u32(smem_all) + 127) & ~127u) + grp * GROUP_BYTES;
  const uint32_t kr = sb + OFF_KR + w * KR_PITCH, bar_k = sb + OFF_BAR + 8 * w, bar_q = bar_k + 64;
  if (lane == 0) { mbar_init(bar_k, 1); mbar_init(bar_q, 1); asm volatile("fence.mbarrier_init.release.cluster;" ::: "memory"); }
  if (lane < 16) sts128(sb + OFF_U + w * U_PITCH + lane * 16, make_uint4(0, 0, 0, 0));
  __syncwarp();
  if (grp == 1) { named_bar_arrive(3, 512); named_bar(5, 512); }
  const int lm = lane >> 3, lr = lane & 7;
  uint32_t ph = 0;
  for (int task = first + grp; task < end; task += stride, ph ^= 1) {
    const int d0 = task * 8;
    uint4 x[8];
    {
      const uint4* kf = (const uint4*)(maps.ssm_k + (size_t)(d0 + w) * S_LEN);
#pragma unroll
      for (int it = 0; it < 8; it++) x[it] = __ldg(kf + it * 32 + lane);
    }
    const uint4 ska = __ldg((const uint4*)(maps.shift_k + (d0 + 2 * t) * 4));
    __syncwarp();
    if (lane == 0) {
      mbar_expect_tx(bar_k, 2 * 4096 + 128);
      tma_load_2d(kr + 4096, &maps.k8, d0, w * 256 + 248, bar_k);
      tma_load_2d(kr, &maps.k, d0, w * 256 - 8, bar_k);
      bulk_wait_read<0>();
      tma_load_2d(kr + Q_OFF, &maps.v, d0, w * 256, bar_k);
    }
    __syncwarp();
    if (task == first) named_bar_arrive(5, 512);
    const uint32_t sk[4] = {__byte_perm(ska.x, ska.z, 0x5410), __byte_perm(ska.x, ska.z, 0x7632), __byte_perm(ska.y, ska.w, 0x5410), __byte_perm(ska.y, ska.w, 0x7632)};
    mbar_wait_sleep(bar_k, ph);
    {
      const uint32_t ka = kr + (lane + 8) * 16;
#pragma unroll
      for (int i = 0; i < 8; i++) {
        uint32_t k0[4], k1[4], k2[4], k3[4], v[4], r[4];
        ldsm_x4(k3, ka + i * 512 - 48); ldsm_x4(k2, ka + i * 512 - 32); ldsm_x4(k1, ka + i * 512 - 16); ldsm_x4(k0, ka + i * 512);
        ldsm_x4(v, ka + (Q_OFF - 128) + i * 512);
#pragma unroll
        for (int b = 0; b < 4; b++) {
          uint32_t acc = bmul2(k3[b], sk[3]);
          acc = badd2(acc, bmul2(k2[b], sk[2]));
          acc = badd2(acc, bmul2(k1[b], sk[1]));
          acc = badd2(acc, bmul2(k0[b], sk[0]));
          r[b] = bmul2(acc, v[b]);
        }
        const int ch = 16 + w * 32 + i * 4 + lm;
        stsm_x4_t(sb + OFF_U + lr * U_PITCH + ((ch ^ ((ch >> 3) & 1)) << 4), r[0], r[1], r[2], r[3]);
      }
    }
    __syncwarp();
    {
      const uint32_t c0 = kr, c1 = c0 + (KR_WORDS + 16) * 4;
      uint32_t carry = 0;
#pragma unroll
      for (int it = 0; it < 8; it++) {
        const int blk = it * 32 + lane;
        uint32_t prev = __shfl_up_sync(0xffffffffu, x[it].w, 1);
        if (lane == 0) prev = carry;
        carry = __shfl_sync(0xffffffffu, x[it].w, 31);
        sts128(c0 + (1028 - 4 * blk) * 4, make_uint4(__byte_perm(x[it].w, 0, 0x1032), __byte_perm(x[it].z, 0, 0x1032),
                                                     __byte_perm(x[it].y, 0, 0x1032), __byte_perm(x[it].x, 0, 0x1032)));
        sts128(c1 + (1028 - 4 * blk) * 4, make_uint4(__byte_perm(x[it].w, x[it].z, 0x7610), __byte_perm(x[it].z, x[it].y, 0x7610),
                                                     __byte_perm(x[it].y, x[it].x, 0x7610), __byte_perm(x[it].x, prev, 0x7610)));
      }
      if (lane < 4) { sts128(c0 + (1032 + 4 * lane) * 4, make_uint4(0, 0, 0, 0)); sts128(c1 + (1032 + 4 * lane) * 4, make_uint4(0, 0, 0, 0)); }
      __syncwarp();
    }
    named_bar(3 + grp, 512);
    float acc[16][4];
#pragma unroll
    for (int jn = 0; jn < 16; jn++) { acc[jn][0] = acc[jn][1] = acc[jn][2] = acc[jn][3] = 0.f; }
    {
      const uint32_t ub = sb + OFF_U + w * U_PITCH;
      uint32_t kd = kr + (((g & 1) ? 0 : KR_WORDS + 16) + ((((g & 1) ? 2063 : 2062) - (g - 2 * t)) >> 1)) * 4;
      uint32_t uc = 2 * (8 + lr + (lm >> 1) * 8) + (lm & 1);
#pragma unroll 1
      for (int d0s = 0; d0s < 8; d0s++, kd -= 32, uc -= 2) {
        const uint32_t uf = ub + ((uc ^ ((uc >> 3) & 1)) << 4);
        uint32_t A[3][4];
        A[0][0] = lds32v(kd); A[0][1] = lds32v(kd - 16); A[0][2] = lds32v(kd + 16); A[0][3] = lds32v(kd);
        uint32_t F[8][4];
#pragma unroll
        for (int m = 7; m >= 0; m--) ldsm_x4(F[m], uf + m * 512);
#pragma unroll
        for (int i = 0; i < 16; i++) {
          if (i + 1 < 16) {
            A[(i + 1) % 3][0] = lds32v(kd - 256 * (i + 1)); A[(i + 1) % 3][1] = lds32v(kd - 256 * (i + 1) - 16);
            A[(i + 1) % 3][2] = lds32v(kd - 256 * (i + 1) + 16); A[(i + 1) % 3][3] = lds32v(kd - 256 * (i + 1));
          }
#pragma unroll
          for (int jn = 15; jn >= i; jn--) mma16816(acc[jn], A[i % 3], F[(jn - i) >> 1][((jn - i) & 1) * 2], F[(jn - i) >> 1][((jn - i) & 1) * 2 + 1]);
        }
      }
    }
    named_bar_arrive(3 + (grp ^ 1), 512);
    __syncwarp();
    fence_async_smem();
    __syncwarp();
    if (lane == 0) { mbar_expect_tx(bar_q, 4096); tma_load_2d(kr + Q_OFF, &maps.q, d0, w * 256, bar_q); }
    const uint32_t dpair = __ldg((const uint32_t*)(maps.ssm_D + d0) + t);
    {
      const uint32_t ya = kr + w * 16 + (((lm >> 1) * 8 + lr) * 32) + (lm & 1) * 16;
#pragma unroll
      for (int jn = 0; jn < 16; jn += 2)
        stsm_x4_t(ya + jn * 256, pack_bf16(acc[jn][0], acc[jn][1]), pack_bf16(acc[jn][2], acc[jn][3]),
                  pack_bf16(acc[jn + 1][0], acc[jn + 1][1]), pack_bf16(acc[jn + 1][2], acc[jn + 1][3]));
    }
    named_bar(1 + grp, 256);
    mbar_wait_sleep(bar_q, ph);
    {
      const uint32_t ya = sb + OFF_KR + lr * (KR_PITCH + 16) + (w * 256 + lm * 8) * 2;
#pragma unroll
      for (int i = 0; i < 8; i++) {
        uint32_t y[4], u[4], q[4], r[4];
        ldsm_x4(q, kr + Q_OFF + lane * 16 + i * 512);
        ldsm_x4_t(y, ya + i * 64);
        const int ch = 16 + w * 32 + i * 4 + lm;
        ldsm_x4_t(u, sb + OFF_U + lr * U_PITCH + ((ch ^ ((ch >> 3) & 1)) << 4));
#pragma unroll
        for (int b = 0; b < 4; b++) r[b] = bmul2(q[b], badd2(y[b], bmul2(u[b], dpair)));
        stsm_x4(kr + Q_OFF + lane * 16 + i * 512, r[0], r[1], r[2], r[3]);
      }
      fence_async_smem();
      __syncwarp();
      if (lane == 0) { tma_store_2d(&maps.out, kr + Q_OFF, DM + d0, w * 256); bulk_commit(); }
    }
    named_bar(1 + grp, 256);
  }
  if (lane == 0) bulk_wait<0>();
}

__global__ void __launch_bounds__(512, 1) __cluster_dims__(2, 1, 1) bpart_kernel(const __grid_constant__ BMaps maps, int end) {
  bpart_body(maps, blockIdx.x * 2, gridDim.x * 2, end);
}

struct GemmMaps {
  CUtensorMap o;
  CUtensorMap w;
  CUtensorMap c;
};
namespace k3 {
constexpr int STAGES = 6;
constexpr int W_BYTES = 2 * 8192, O_BYTES = K3_N * 128, STAGE_BYTES = W_BYTES + O_BYTES;
constexpr int TT = (S_LEN + K3_N - 1) / K3_N, NGEMM = TT * (DM / 128), NB = 128 - NGEMM, KSTEPS = HD / 64;
constexpr int SMEM_G = STAGES * STAGE_BYTES + 1024 + 256;
constexpr int SMEM = SMEM_G > bp::SMEM ? SMEM_G : bp::SMEM;
static_assert(STAGE_BYTES % 1024 == 0, "swizzle atoms");
}

__global__ void __launch_bounds__(512, 1)
tail_kernel(const __grid_constant__ GemmMaps maps, const __grid_constant__ BMaps bmaps) {
  using namespace k3;
  if (blockIdx.x < NB) {
    bpart_body(bmaps, bp::NTASK - 2 * NB + 2 * blockIdx.x, bp::NTASK, bp::NTASK);
    return;
  }
  extern __shared__ uint8_t smem_raw[];
  const uint32_t sbase = (smem_u32(smem_raw) + 1023) & ~1023u;
  const uint32_t bars = sbase + STAGES * STAGE_BYTES;
  const int tid = threadIdx.x, warp = tid >> 5;
  const int tt = (blockIdx.x - NB) / 8, ct = (blockIdx.x - NB) % 8;

  if (tid == 0) {
    for (int s = 0; s < STAGES; s++) { mbar_init(bars + 8 * s, 1); mbar_init(bars + 8 * (STAGES + s), 2); }
    asm volatile("fence.mbarrier_init.release.cluster;" ::: "memory");
  }
  __syncthreads();

  if (warp >= 8) {
    if (tid == 256) {
      tma_prefetch_desc(&maps.o);
      for (int k = 0; k < STAGES; k++) {
        const uint32_t full = bars + 8 * k, sa = sbase + k * STAGE_BYTES;
        mbar_expect_tx(full, STAGE_BYTES);
#pragma unroll
        for (int j = 0; j < 2; j++) tma_load_2d(sa + j * 8192, &maps.w, ct * 128 + j * 64, k * 64, full);
      }
      asm volatile("griddepcontrol.wait;" ::: "memory");
      int stage = 0; uint32_t ph = 1;
      for (int k = 0; k < KSTEPS; k++) {
        mbar_wait(bars + 8 * (STAGES + stage), ph);
        const uint32_t full = bars + 8 * stage, sa = sbase + stage * STAGE_BYTES;
        const bool pre = k < STAGES;
        if (!pre) mbar_expect_tx(full, STAGE_BYTES);
        tma_load_2d(sa + W_BYTES, &maps.o, k * 64, tt * K3_N, full);
        if (!pre) {
#pragma unroll
          for (int j = 0; j < 2; j++) tma_load_2d(sa + j * 8192, &maps.w, ct * 128 + j * 64, k * 64, full);
        }
        if (++stage == STAGES) { stage = 0; ph ^= 1; }
      }
    }
  } else {
    const int wg = warp >> 2, lane = tid & 31, wq = warp & 3;
    int stage = 0; uint32_t ph = 0;
    float acc[K3_N / 2];
    int prev = -1;
    for (int k = 0; k < KSTEPS; k++) {
      mbar_wait(bars + 8 * stage, ph);
      const uint32_t sa = sbase + stage * STAGE_BYTES;
      wg_fence();
#pragma unroll
      for (int kk = 0; kk < 4; kk++) {
        const uint64_t da = make_desc(sa + wg * 8192 + kk * 2048, 16, 1024, 1);
        const uint64_t db = make_desc(sa + W_BYTES + kk * 32, 16, 1024, 1);
        wgmma_k3_ss_ta(acc, da, db, (k | kk) != 0);
      }
      wg_commit();
      if (prev >= 0) { wg_wait<1>(); if ((tid & 127) == 0) mbar_arrive(bars + 8 * (STAGES + prev)); }
      prev = stage;
      if (++stage == STAGES) { stage = 0; ph ^= 1; }
    }
    wg_wait<0>();
#pragma unroll
    for (int i = 0; i < K3_N / 2; i++) asm volatile("" : "+f"(acc[i]) :: "memory");
    named_bar(1, 256);
    const uint32_t ebuf = sbase + wg * STAGE_BYTES;
    const uint32_t ea = ebuf + ((lane >> 4) * 8 + (lane & 7)) * 128 + (((2 * wq + ((lane >> 3) & 1)) ^ (lane & 7)) << 4);
#pragma unroll
    for (int i = 0; i < K3_N / 8; i += 2) {
      const int i1 = i + 1 < K3_N / 8 ? i + 1 : i;
      stsm_x4_t(ea + i * 1024, pack_bf16(acc[4 * i], acc[4 * i + 1]), pack_bf16(acc[4 * i + 2], acc[4 * i + 3]),
                pack_bf16(acc[4 * i1], acc[4 * i1 + 1]), pack_bf16(acc[4 * i1 + 2], acc[4 * i1 + 3]));
    }
    fence_async_smem();
    named_bar(2 + wg, 128);
    if ((tid & 127) == 0) {
      tma_store_2d(&maps.c, ebuf, ct * 128 + wg * 64, tt * K3_N);
      bulk_commit();
      bulk_wait<0>();
    }
  }
}

typedef CUresult (*EncodeFn)(CUtensorMap*, CUtensorMapDataType, cuuint32_t, void*, const cuuint64_t*, const cuuint64_t*,
                             const cuuint32_t*, const cuuint32_t*, CUtensorMapInterleave, CUtensorMapSwizzle,
                             CUtensorMapL2promotion, CUtensorMapFloatOOBfill);

void make_map(EncodeFn enc, CUtensorMap* m, const void* ptr, uint64_t cols, uint64_t rows, uint64_t pitch_elems,
              uint32_t box_cols, uint32_t box_rows, CUtensorMapSwizzle swz,
              CUtensorMapL2promotion promo = CU_TENSOR_MAP_L2_PROMOTION_L2_128B) {
  cuuint64_t dims[2] = {cols, rows};
  cuuint64_t strides[1] = {pitch_elems * 2};
  cuuint32_t box[2] = {box_cols, box_rows};
  cuuint32_t es[2] = {1, 1};
  enc(m, CU_TENSOR_MAP_DATA_TYPE_BFLOAT16, 2, const_cast<void*>(ptr), dims, strides, box, es, CU_TENSOR_MAP_INTERLEAVE_NONE, swz,
      promo, CU_TENSOR_MAP_FLOAT_OOB_FILL_NONE);
}

void make_map_nd(EncodeFn enc, CUtensorMap* m, const void* ptr, int rank, const uint64_t* dims, const uint64_t* strides_elems,
                 const uint32_t* box, CUtensorMapSwizzle swz) {
  cuuint64_t d[5], st[4]; cuuint32_t b[5], es[5];
  for (int i = 0; i < rank; i++) { d[i] = dims[i]; b[i] = box[i]; es[i] = 1; if (i) st[i - 1] = strides_elems[i] * 2; }
  enc(m, CU_TENSOR_MAP_DATA_TYPE_BFLOAT16, rank, const_cast<void*>(ptr), d, st, b, es, CU_TENSOR_MAP_INTERLEAVE_NONE, swz,
      CU_TENSOR_MAP_L2_PROMOTION_L2_128B, CU_TENSOR_MAP_FLOAT_OOB_FILL_NONE);
}

}

extern "C" void kernel_launch(void* const* d_in, const int* in_sizes, int n_in, void* d_out, int out_size) {
  (void)in_sizes; (void)n_in; (void)out_size;
  const bf16* x = (const bf16*)d_in[0];
  const bf16* mem0 = (const bf16*)d_in[1];
  const bf16* Wq = (const bf16*)d_in[2];
  const bf16* Wk = (const bf16*)d_in[3];
  const bf16* Wv = (const bf16*)d_in[4];
  const bf16* Wo = (const bf16*)d_in[5];
  const bf16* Bq = (const bf16*)d_in[7];
  const bf16* Bk = (const bf16*)d_in[8];
  const bf16* Bv = (const bf16*)d_in[9];
  const bf16* shift_k = (const bf16*)d_in[10];
  const bf16* ssm_k = (const bf16*)d_in[11];
  const bf16* ssm_D = (const bf16*)d_in[12];
  bf16* out = (bf16*)d_out;

  static EncodeFn enc = nullptr;
  static uint64_t xbase0;
  static int nsm = 132;
  static cudaStream_t s1;
  static cudaEvent_t ev_fork, ev_join;
  if (!enc) {
    cudaDriverEntryPointQueryResult qr;
    void* fn = nullptr;
    cudaGetDriverEntryPoint("cuTensorMapEncodeTiled", &fn, cudaEnableDefault, &qr);
    enc = (EncodeFn)fn;
    void* ps = nullptr;
    cudaGetSymbolAddress(&ps, g_scratch);
    xbase0 = (uint64_t)ps;
    if ((xbase0 >> 32) != ((xbase0 + xo::BYTES - 1) >> 32)) xbase0 += xo::BYTES;
    cudaFuncSetAttribute(tail_kernel, cudaFuncAttributeMaxDynamicSharedMemorySize, k3::SMEM);
    cudaFuncSetAttribute(chain_kernel, cudaFuncAttributeMaxDynamicSharedMemorySize, chain::SMEM);
    cudaFuncSetAttribute(bpart_kernel, cudaFuncAttributeMaxDynamicSharedMemorySize, bp::SMEM);
    cudaStreamCreateWithFlags(&s1, cudaStreamNonBlocking);
    cudaEventCreateWithFlags(&ev_fork, cudaEventDisableTiming);
    cudaEventCreateWithFlags(&ev_join, cudaEventDisableTiming);
    int dev = 0; cudaGetDevice(&dev);
    cudaDeviceGetAttribute(&nsm, cudaDevAttrMultiProcessorCount, dev);
  }
  uint64_t xbase = xbase0;
  const CUtensorMapSwizzle SW128 = CU_TENSOR_MAP_SWIZZLE_128B, SW64 = CU_TENSOR_MAP_SWIZZLE_64B;
  GemmMaps m3; ChainMaps mc;
  make_map(enc, &m3.o, (void*)(xbase + xo::O), HD, S_LEN, HD, 64, K3_N, SW128);
  make_map(enc, &m3.w, Wo, DM, HD, DM, 64, 64, SW128);
  make_map(enc, &m3.c, out, DM, S_LEN, OUT_LD, 64, K3_N, SW128);
  const CUtensorMapL2promotion P256 = CU_TENSOR_MAP_L2_PROMOTION_L2_256B;
  make_map(enc, &mc.wq, Wq, HD, DM, HD, 64, 128, SW128, P256);
  make_map(enc, &mc.wk, Wk, HD, DM, HD, 64, 128, SW128, P256);
  make_map(enc, &mc.wv, Wv, HD, DM, HD, 64, 128, SW128, P256);
  make_map(enc, &mc.wo, Wo, DM, HD, DM, 32, 256, SW64, P256);
  {
    const uint64_t dx[3] = {64, S_LEN, DM / 64}, sx[3] = {1, DM, 64};
    const uint32_t bx[3] = {64, SEG, 8};
    make_map_nd(enc, &mc.x, x, 3, dx, sx, bx, SW128);
    const uint32_t bq[3] = {64, SEG, 4};
    make_map_nd(enc, &mc.xq, x, 3, dx, sx, bq, SW128);
    make_map(enc, &mc.o, (void*)(xbase + xo::O), HD, S_LEN, HD, 64, 16, SW128);
    mc.xp = (const char*)x;
  }

  const int skip = 0;
  mc.t_step = T_STEP; mc.t_phase = T_PHASE;
  BMaps mb;
  const CUtensorMapSwizzle SWN = CU_TENSOR_MAP_SWIZZLE_NONE;
  make_map(enc, &mb.k, Bk, DM, S_LEN, DM, 8, 256, SWN);
  make_map(enc, &mb.q, Bq, DM, S_LEN, DM, 8, 256, SWN);
  make_map(enc, &mb.v, Bv, DM, S_LEN, DM, 8, 256, SWN);
  mb.shift_k = shift_k; mb.ssm_k = ssm_k; mb.ssm_D = ssm_D;
  make_map(enc, &mb.out, out, OUT_LD, S_LEN, OUT_LD, 8, 256, SWN);
  make_map(enc, &mb.k8, Bk, DM, S_LEN, DM, 8, 8, SWN);
  cudaStream_t s0 = cudaStreamPerThread;
  const int nb = nsm >= 132 ? 4 : 2, ntask1 = bp::NTASK - 2 * k3::NB;
  const bool fork = nsm >= 130 && !(skip & 16);
  if (fork) {
    cudaEventRecord(ev_fork, s0);
    cudaStreamWaitEvent(s1, ev_fork, 0);
    if (!(skip & 1)) bpart_kernel<<<nb, 512, bp::SMEM, s1>>>(mb, ntask1);
    cudaEventRecord(ev_join, s1);
  } else if (!(skip & 1)) {
    bpart_kernel<<<ntask1 / 2, 512, bp::SMEM, s0>>>(mb, ntask1);
  }
  if (!(skip & 4)) chain_kernel<<<128, 256, chain::SMEM, s0>>>(mc, mem0, xbase);
  if (!(skip & 8)) {
    cudaLaunchAttribute pdl[1];
    pdl[0].id = cudaLaunchAttributeProgrammaticStreamSerialization;
    pdl[0].val.programmaticStreamSerializationAllowed = 1;
    cudaLaunchConfig_t cfg = {};
    cfg.gridDim = dim3(128); cfg.blockDim = dim3(512); cfg.dynamicSmemBytes = k3::SMEM; cfg.stream = s0;
    cfg.attrs = pdl; cfg.numAttrs = 1;
    cudaLaunchKernelEx(&cfg, tail_kernel, m3, mb);
  }
  if (fork) cudaStreamWaitEvent(s0, ev_join, 0);
}
```
